```python
import torch

def _softmax(x, axis=-1):
    return torch.softmax(x, dim=axis)
def _gelu(x):
    return torch.nn.functional.gelu(x, approximate="tanh")
def _silu(x):
    return torch.nn.functional.silu(x)
def _sigmoid(x):
    return torch.sigmoid(x)
def _layernorm(x, axis=-1, eps=1e-5):
    m = x.mean(dim=axis, keepdim=True)
    v = x.var(dim=axis, keepdim=True, unbiased=False)
    return (x - m) / torch.sqrt(v + eps)
def _scatter_add(tgt, idx, src, axis=0):
    return tgt.clone().index_add_(axis, idx, src)
def _segment_sum(src, seg, n):
    out = torch.zeros((n,) + src.shape[1:], dtype=src.dtype)
    return out.index_add_(0, seg, src)
def _pad(x, pw):
    flat = tuple(v for pair in reversed(pw) for v in pair)
    return torch.nn.functional.pad(x, flat)

kernel_name = 'gated_mix__compressed_kv_cla__ssm_conv_h3__prompt'

def setup_inputs():

    _w = (lambda a: (lambda t: t.to(torch.bfloat16) if t.is_floating_point() else t)(torch.as_tensor(a)))
    def _A_setup():
        B, H, Sq, Sk, D, M = 1, 32, 2048, 2048, 128, 1024
        Dc = 4 * D
        return {
            "x": _w((lambda *s: torch.randn(*s, dtype=torch.bfloat16) * 0.05)(B, Sq, M)),
            "c_kv": _w((lambda *s: torch.randn(*s, dtype=torch.bfloat16) * 0.8)(B, Sk, Dc)),
            "w_q": _w((lambda *s: torch.randn(*s, dtype=torch.bfloat16) * 6.4)(M, H, D) * (M ** -0.5)),
            "w_uk": _w((lambda *s: torch.randn(*s, dtype=torch.bfloat16) * 6.4)(Dc, H, D) * (Dc ** -0.5)),
            "w_uv": _w((lambda *s: torch.randn(*s, dtype=torch.bfloat16) * 0.8)(Dc, H, D) * (Dc ** -0.5)),
            "w_o": _w((lambda *s: torch.randn(*s, dtype=torch.bfloat16) * 0.8)(H, D, M) * ((H * D) ** -0.5)),
        }
    _A_in = _A_setup()

    def _B_setup():
        B, S, D = 1, 2048, 1024
        ks = 4
        return {
            "q": _w((lambda *s: torch.randn(*s, dtype=torch.bfloat16) * 0.05)(B, S, D)),
            "k": _w((lambda *s: torch.randn(*s, dtype=torch.bfloat16) * 0.8)(B, S, D)),
            "v": _w((lambda *s: torch.randn(*s, dtype=torch.bfloat16) * 0.8)(B, S, D)),
            "shift_k": _w((lambda *s: torch.randn(*s, dtype=torch.bfloat16) * 0.8)(D, ks) * 0.5),
            "ssm_k": _w((lambda *s: torch.randn(*s, dtype=torch.bfloat16) * 1.6)(D, S) * (1.0 / S ** 0.5)),
            "ssm_D": _w((lambda *s: torch.randn(*s, dtype=torch.bfloat16) * 0.8)(D)),
        }
    _B_in = _B_setup()

    return {
        "A_x": _A_in["x"],
        "A_c_kv": _A_in["c_kv"],
        "A_w_q": _A_in["w_q"],
        "A_w_uk": _A_in["w_uk"],
        "A_w_uv": _A_in["w_uv"],
        "A_w_o": _A_in["w_o"],
        "B_q": _B_in["q"],
        "B_k": _B_in["k"],
        "B_v": _B_in["v"],
        "B_shift_k": _B_in["shift_k"],
        "B_ssm_k": _B_in["ssm_k"],
        "B_ssm_D": _B_in["ssm_D"],
        "gate_w": _w((lambda *s: torch.randn(*s, dtype=torch.bfloat16) * 0.05)(1024) * 16.0),
    }

def reference(A_x, A_c_kv, A_w_q, A_w_uk, A_w_uv, A_w_o, B_q, B_k, B_v, B_shift_k, B_ssm_k, B_ssm_D, gate_w):
    def _A_ref(x, c_kv, w_q, w_uk, w_uv, w_o):
        B, Sq, M = x.shape[0], x.shape[1], x.shape[2]
        Sk = c_kv.shape[1]
        H, D = w_q.shape[1], w_q.shape[2]
        q = torch.einsum("bqm,mhd->bhqd", x, w_q)
        k = torch.einsum("bkc,chd->bhkd", c_kv, w_uk)
        v = torch.einsum("bkc,chd->bhkd", c_kv, w_uv)
        scores = torch.einsum("bhqd,bhkd->bhqk", q, k) * (D ** -0.5)
        off = Sk - Sq
        qi = torch.arange(Sq)[:, None]
        kj = torch.arange(Sk)[None, :]
        cmask = kj <= (qi + off)
        scores = torch.where(cmask[None, None], scores, -1e9)
        p = _softmax(scores, axis=-1)
        ctx = torch.einsum("bhqk,bhkd->bhqd", p, v)
        return torch.einsum("bhqd,hdm->bqm", ctx, w_o)

    def _B_ref(q, k, v, shift_k, ssm_k, ssm_D):
        B, S, D = q.shape
        ks = shift_k.shape[-1]
        k_pad = _pad(k, ((0, 0), (ks - 1, 0), (0, 0)))
        k_shift = torch.zeros_like(k)
        for t in range(ks):
            k_shift = k_shift + k_pad[:, t:t + S, :] * shift_k[:, ks - 1 - t][None, None, :]
        kv = k_shift * v
        L = 2 * S
        kv_pad = _pad(kv, ((0, 0), (0, S), (0, 0)))
        kf_pad = _pad(ssm_k, ((0, 0), (0, S)))
        kv_f = (lambda x, axes=(-2,-1): torch.fft.rfft2(x.float(), dim=axes))(kv_pad[:, None, :, :], axes=(1, 2))
        kf_f = (lambda x, axes=(-2,-1): torch.fft.rfft2(x.float(), dim=axes))(kf_pad[:, None, :], axes=(1, 2))
        kf_f = (lambda x, *d: x.permute(*d))(kf_f, 1, 2, 0)
        y_f = kv_f * kf_f[None, :, :, :]
        y = (lambda x, s, axes=(-2,-1): torch.fft.irfft2(x, s=s, dim=axes).to(torch.bfloat16))(y_f, (1, L), axes=(1, 2))[:, 0, :S, :]
        y = y + kv * ssm_D[None, None, :]
        return q * y

    x = A_x
    g = _sigmoid((x * gate_w).sum(-1, keepdims=True))
    a = _A_ref(x, A_c_kv, A_w_q, A_w_uk, A_w_uv, A_w_o)
    b = _B_ref(x, B_k, B_v, B_shift_k, B_ssm_k, B_ssm_D)
    return g * a + (1 - g) * b
```

```cpp
#include <cuda_runtime.h>
#include <cuda_bf16.h>
#include <cuda.h>
#include <stdint.h>

typedef __nv_bfloat16 bf16;
#define INPLACE 3

constexpr int S_LEN = 2048;
constexpr int DM = 1024;
constexpr int NH = 32;
constexpr int HD = 128;
constexpr int DC = 512;
constexpr int HDIM = NH * HD;

__device__ __align__(1024) bf16 g_q[S_LEN * HDIM];
__device__ __align__(1024) bf16 g_k[S_LEN * HDIM];
__device__ __align__(1024) bf16 g_v[S_LEN * HDIM];
#define g_ctx g_q
__device__ __align__(1024) bf16 g_kvT[DM * S_LEN];
#define g_y2T g_kvT
__device__ __align__(1024) float g_gate[S_LEN];
enum { CNT_KV = 0, CNT_PREP = CNT_KV + 2, CNT_CTX, CNT_Y2 = CNT_CTX + 2, CNT_DONE = CNT_Y2 + 2, CNT_N };
__device__ unsigned int g_cnt[CNT_N * 32];

#define TL(k, i)
#define TL2(k, i)
#define TD(i)
#define CLK_DECL
#define CLK_SAMPLE
#define CLK_END
#define CT(i)
#define GT(i)
#define GA(i)
#define ST(i)

__device__ __forceinline__ uint32_t smem_u32(const void* p) { return (uint32_t)__cvta_generic_to_shared(p); }

__device__ __forceinline__ void mbar_init(uint32_t bar, uint32_t count) {
  asm volatile("mbarrier.init.shared::cta.b64 [%0], %1;" ::"r"(bar), "r"(count));
}
__device__ __forceinline__ void mbar_expect_tx(uint32_t bar, uint32_t bytes) {
  asm volatile("mbarrier.arrive.expect_tx.shared::cta.b64 _, [%0], %1;" ::"r"(bar), "r"(bytes) : "memory");
}
__device__ __forceinline__ void mbar_arrive(uint32_t bar) {
  asm volatile("mbarrier.arrive.shared::cta.b64 _, [%0];" ::"r"(bar) : "memory");
}
__device__ __forceinline__ void mbar_wait(uint32_t bar, uint32_t parity) {
  uint32_t done;
  uint32_t spins = 0;
  do {
    asm volatile(
        "{\n.reg .pred p;\n"
        "mbarrier.try_wait.parity.shared::cta.b64 p, [%1], %2;\n"
        "selp.u32 %0, 1, 0, p;\n}\n"
        : "=r"(done)
        : "r"(bar), "r"(parity)
        : "memory");
    if (++spins > (1u << 22)) break;
  } while (!done);
}
__device__ __forceinline__ bool mbar_try(uint32_t bar, uint32_t parity) {
  uint32_t done;
  asm volatile(
      "{\n.reg .pred p;\n"
      "mbarrier.try_wait.parity.shared::cta.b64 p, [%1], %2;\n"
      "selp.u32 %0, 1, 0, p;\n}\n"
      : "=r"(done)
      : "r"(bar), "r"(parity)
      : "memory");
  return done != 0;
}
__device__ __forceinline__ bool elect_one() {
  uint32_t pred;
  asm volatile("{\n.reg .pred p;\nelect.sync _|p, 0xffffffff;\nselp.u32 %0, 1, 0, p;\n}\n" : "=r"(pred));
  return pred != 0;
}
__device__ __forceinline__ void mbar_arrive_if(uint32_t bar, bool pred) {
  asm volatile(
      "{\n.reg .pred p;\nsetp.ne.b32 p, %1, 0;\n"
      "@p mbarrier.arrive.shared::cta.b64 _, [%0];\n}\n" ::"r"(bar),
      "r"((uint32_t)pred)
      : "memory");
}
__device__ __forceinline__ void mbar_wait_sleep(uint32_t bar, uint32_t parity) {
  uint32_t done;
  uint32_t spins = 0;
  do {
    asm volatile(
        "{\n.reg .pred p;\n"
        "mbarrier.try_wait.parity.shared::cta.b64 p, [%1], %2, %3;\n"
        "selp.u32 %0, 1, 0, p;\n}\n"
        : "=r"(done)
        : "r"(bar), "r"(parity), "r"(20000u)
        : "memory");
    if (++spins > (1u << 16)) break;
  } while (!done);
}
__device__ __forceinline__ void fence_barrier_init() {
  asm volatile("fence.mbarrier_init.release.cluster;" ::: "memory");
}
__device__ __forceinline__ void fence_proxy_async() {
  asm volatile("fence.proxy.async.shared::cta;" ::: "memory");
}
__device__ __forceinline__ void named_bar_sync(int id, int nthreads) {
  asm volatile("bar.sync %0, %1;" ::"r"(id), "r"(nthreads) : "memory");
}
__device__ __forceinline__ void named_bar_arrive(int id, int nthreads) {
  asm volatile("bar.arrive %0, %1;" ::"r"(id), "r"(nthreads) : "memory");
}
__device__ __forceinline__ void tma_load_2d(uint32_t dst, const CUtensorMap* m, uint32_t bar, int c0, int c1) {
  asm volatile(
      "cp.async.bulk.tensor.2d.shared::cluster.global.mbarrier::complete_tx::bytes [%0], [%1, {%3, %4}], [%2];" ::"r"(dst),
      "l"(reinterpret_cast<uint64_t>(m)), "r"(bar), "r"(c0), "r"(c1)
      : "memory");
}
__device__ __forceinline__ void tma_load_3d(uint32_t dst, const CUtensorMap* m, uint32_t bar, int c0, int c1, int c2) {
  asm volatile(
      "cp.async.bulk.tensor.3d.shared::cluster.global.mbarrier::complete_tx::bytes [%0], [%1, {%3, %4, %5}], [%2];" ::"r"(dst),
      "l"(reinterpret_cast<uint64_t>(m)), "r"(bar), "r"(c0), "r"(c1), "r"(c2)
      : "memory");
}
__device__ __forceinline__ void tma_store_2d(const CUtensorMap* m, uint32_t src, int c0, int c1) {
  asm volatile("cp.async.bulk.tensor.2d.global.shared::cta.bulk_group [%0, {%2, %3}], [%1];" ::"l"(
                   reinterpret_cast<uint64_t>(m)),
               "r"(src), "r"(c0), "r"(c1)
               : "memory");
}
__device__ __forceinline__ void bulk_load(uint32_t dst, const void* src, uint32_t bytes, uint32_t bar) {
  asm volatile("cp.async.bulk.shared::cluster.global.mbarrier::complete_tx::bytes [%0], [%1], %2, [%3];" ::"r"(dst),
               "l"(src), "r"(bytes), "r"(bar)
               : "memory");
}
__device__ __forceinline__ void tma_load_2d_mc(uint32_t dst, const CUtensorMap* m, uint32_t bar, int c0, int c1,
                                               uint16_t mask) {
  asm volatile(
      "cp.async.bulk.tensor.2d.shared::cluster.global.mbarrier::complete_tx::bytes.multicast::cluster [%0], [%1, {%3, "
      "%4}], [%2], %5;" ::"r"(dst),
      "l"(reinterpret_cast<uint64_t>(m)), "r"(bar), "r"(c0), "r"(c1), "h"(mask)
      : "memory");
}
__device__ __forceinline__ void mbar_arrive_cluster_if(uint32_t bar, uint32_t cta, bool pred) {
  asm volatile(
      "{\n.reg .b32 ra;\n.reg .pred p;\nsetp.ne.b32 p, %2, 0;\n"
      "mapa.shared::cluster.u32 ra, %0, %1;\n"
      "@p mbarrier.arrive.shared::cluster.b64 _, [ra];\n}\n" ::"r"(bar),
      "r"(cta), "r"((uint32_t)pred)
      : "memory");
}
__device__ __forceinline__ uint64_t policy_evict_first() {
  uint64_t pol;
  asm volatile("createpolicy.fractional.L2::evict_first.b64 %0, 1.0;" : "=l"(pol));
  return pol;
}
__device__ __forceinline__ void tma_load_2d_hint(uint32_t dst, const CUtensorMap* m, uint32_t bar, int c0, int c1,
                                                 uint64_t pol) {
  asm volatile(
      "cp.async.bulk.tensor.2d.shared::cluster.global.mbarrier::complete_tx::bytes.L2::cache_hint [%0], [%1, {%3, %4}], "
      "[%2], %5;" ::"r"(dst),
      "l"(reinterpret_cast<uint64_t>(m)), "r"(bar), "r"(c0), "r"(c1), "l"(pol)
      : "memory");
}
__device__ __forceinline__ void tma_load_3d_hint(uint32_t dst, const CUtensorMap* m, uint32_t bar, int c0, int c1,
                                                 int c2, uint64_t pol) {
  asm volatile(
      "cp.async.bulk.tensor.3d.shared::cluster.global.mbarrier::complete_tx::bytes.L2::cache_hint [%0], [%1, {%3, %4, "
      "%5}], [%2], %6;" ::"r"(dst),
      "l"(reinterpret_cast<uint64_t>(m)), "r"(bar), "r"(c0), "r"(c1), "r"(c2), "l"(pol)
      : "memory");
}
__device__ __forceinline__ void bulk_load_hint(uint32_t dst, const void* src, uint32_t bytes, uint32_t bar, uint64_t pol) {
  asm volatile(
      "cp.async.bulk.shared::cluster.global.mbarrier::complete_tx::bytes.L2::cache_hint [%0], [%1], %2, [%3], %4;" ::"r"(dst),
      "l"(src), "r"(bytes), "r"(bar), "l"(pol)
      : "memory");
}
__device__ __forceinline__ void cnt_signal_release(int which, uint32_t n) {
  asm volatile("red.release.gpu.global.add.u32 [%0], %1;" ::"l"(g_cnt + which * 32), "r"(n) : "memory");
}
__device__ __forceinline__ void cnt_wait(int which, uint32_t target) {
  uint32_t v, spins = 0;
  while (true) {
    asm volatile("ld.acquire.gpu.global.u32 %0, [%1];" : "=r"(v) : "l"(g_cnt + which * 32) : "memory");
    if (v >= target || ++spins > (1u << 18)) break;
    __nanosleep(64);
  }
  asm volatile("fence.proxy.async.global;" ::: "memory");
}
__device__ __forceinline__ void tma_store_commit() { asm volatile("cp.async.bulk.commit_group;" ::: "memory"); }
template <int N>
__device__ __forceinline__ void tma_store_wait_read() {
  asm volatile("cp.async.bulk.wait_group.read %0;" ::"n"(N) : "memory");
}
template <int N>
__device__ __forceinline__ void tma_store_wait() {
  asm volatile("cp.async.bulk.wait_group %0;" ::"n"(N) : "memory");
}
__device__ __forceinline__ void wgmma_fence() { asm volatile("wgmma.fence.sync.aligned;" ::: "memory"); }
__device__ __forceinline__ void wgmma_commit() { asm volatile("wgmma.commit_group.sync.aligned;" ::: "memory"); }
template <int N>
__device__ __forceinline__ void wgmma_wait() {
  asm volatile("wgmma.wait_group.sync.aligned %0;" ::"n"(N) : "memory");
}
template <int R>
__device__ __forceinline__ void reg_alloc() { asm volatile("setmaxnreg.inc.sync.aligned.u32 %0;" ::"n"(R)); }
template <int R>
__device__ __forceinline__ void reg_dealloc() { asm volatile("setmaxnreg.dec.sync.aligned.u32 %0;" ::"n"(R)); }

__device__ __forceinline__ void stmatrix_x4(uint32_t addr, uint32_t r0, uint32_t r1, uint32_t r2, uint32_t r3) {
  asm volatile("stmatrix.sync.aligned.m8n8.x4.shared.b16 [%0], {%1, %2, %3, %4};" ::"r"(addr), "r"(r0), "r"(r1),
               "r"(r2), "r"(r3)
               : "memory");
}
__device__ __forceinline__ uint32_t pack_bf16(float lo, float hi) {
  uint32_t r;
  asm("cvt.rn.bf16x2.f32 %0, %1, %2;" : "=r"(r) : "f"(hi), "f"(lo));
  return r;
}
__device__ __forceinline__ float bf16_round(float x) { return __bfloat162float(__float2bfloat16_rn(x)); }
__device__ __forceinline__ float bf_lo(uint32_t v) { return __uint_as_float(v << 16); }
__device__ __forceinline__ float bf_hi(uint32_t v) { return __uint_as_float(v & 0xffff0000u); }
__device__ __forceinline__ uint4 lds128(uint32_t a) {
  uint4 v;
  asm volatile("ld.shared.v4.u32 {%0, %1, %2, %3}, [%4];" : "=r"(v.x), "=r"(v.y), "=r"(v.z), "=r"(v.w) : "r"(a));
  return v;
}
__device__ __forceinline__ void sts128(uint32_t a, uint4 v) {
  asm volatile("st.shared.v4.u32 [%0], {%1, %2, %3, %4};" ::"r"(a), "r"(v.x), "r"(v.y), "r"(v.z), "r"(v.w) : "memory");
}
__device__ __forceinline__ uint32_t mul_bf2(uint32_t a, uint32_t b) {
  uint32_t r;
  asm("mul.rn.bf16x2 %0, %1, %2;" : "=r"(r) : "r"(a), "r"(b));
  return r;
}
__device__ __forceinline__ uint32_t add_bf2(uint32_t a, uint32_t b) {
  uint32_t r;
  asm("add.rn.bf16x2 %0, %1, %2;" : "=r"(r) : "r"(a), "r"(b));
  return r;
}
__device__ __forceinline__ float ex2(float x) {
  float y;
  asm("ex2.approx.ftz.f32 %0, %1;" : "=f"(y) : "f"(x));
  return y;
}
__device__ __forceinline__ float rcp(float x) {
  float y;
  asm("rcp.approx.ftz.f32 %0, %1;" : "=f"(y) : "f"(x));
  return y;
}
template <int N>
__device__ __forceinline__ void fence_regs(float (&r)[N]) {
#pragma unroll
  for (int i = 0; i < N; i++) asm volatile("" : "+f"(r[i])::"memory");
}

template <int N>
__device__ __forceinline__ void undef_regs(float (&r)[N]) {
#pragma unroll
  for (int i = 0; i < N; i++) asm volatile("" : "=f"(r[i]));
}
template <int N>
__device__ __forceinline__ void fence_regs_u(uint32_t (&r)[N]) {
#pragma unroll
  for (int i = 0; i < N; i++) asm volatile("" : "+r"(r[i])::"memory");
}

constexpr uint64_t DESC_SW128 = 1ull << 62;
__device__ __forceinline__ uint64_t make_desc(uint32_t addr, uint32_t lbo_bytes, uint32_t sbo_bytes, uint64_t swz) {
  return (uint64_t)((addr & 0x3FFFF) >> 4) | ((uint64_t)((lbo_bytes & 0x3FFFF) >> 4) << 16) |
         ((uint64_t)((sbo_bytes & 0x3FFFF) >> 4) << 32) | swz;
}

__device__ __forceinline__ uint64_t desc_add(uint64_t d, uint32_t off16) {
  return (d & 0xFFFFFFFF00000000ull) | (uint64_t)((uint32_t)d + off16);
}

__device__ __forceinline__ void wgmma_m64n256_ss_tb(float (&d)[128], uint64_t da, uint64_t db, int sd) {
  asm volatile(
    "{\n.reg .pred p;\nsetp.ne.b32 p, %130, 0;\n"
    "wgmma.mma_async.sync.aligned.m64n256k16.f32.bf16.bf16 "
    "{%0, %1, %2, %3, %4, %5, %6, %7, %8, %9, %10, %11, %12, %13, %14, %15, %16, %17, %18, %19, %20, %21, %22, %23, %24, %25, %26, %27, %28, %29, %30, %31, %32, %33, %34, %35, %36, %37, %38, %39, %40, %41, %42, %43, %44, %45, %46, %47, %48, %49, %50, %51, %52, %53, %54, %55, %56, %57, %58, %59, %60, %61, %62, %63, %64, %65, %66, %67, %68, %69, %70, %71, %72, %73, %74, %75, %76, %77, %78, %79, %80, %81, %82, %83, %84, %85, %86, %87, %88, %89, %90, %91, %92, %93, %94, %95, %96, %97, %98, %99, %100, %101, %102, %103, %104, %105, %106, %107, %108, %109, %110, %111, %112, %113, %114, %115, %116, %117, %118, %119, %120, %121, %122, %123, %124, %125, %126, %127}, %128, %129, p, 1, 1, 0, 1;\n}\n"
    : "+f"(d[0]), "+f"(d[1]), "+f"(d[2]), "+f"(d[3]), "+f"(d[4]), "+f"(d[5]), "+f"(d[6]), "+f"(d[7]), "+f"(d[8]), "+f"(d[9]), "+f"(d[10]), "+f"(d[11]), "+f"(d[12]), "+f"(d[13]), "+f"(d[14]), "+f"(d[15]), "+f"(d[16]), "+f"(d[17]), "+f"(d[18]), "+f"(d[19]), "+f"(d[20]), "+f"(d[21]), "+f"(d[22]), "+f"(d[23]), "+f"(d[24]), "+f"(d[25]), "+f"(d[26]), "+f"(d[27]), "+f"(d[28]), "+f"(d[29]), "+f"(d[30]), "+f"(d[31]), "+f"(d[32]), "+f"(d[33]), "+f"(d[34]), "+f"(d[35]), "+f"(d[36]), "+f"(d[37]), "+f"(d[38]), "+f"(d[39]), "+f"(d[40]), "+f"(d[41]), "+f"(d[42]), "+f"(d[43]), "+f"(d[44]), "+f"(d[45]), "+f"(d[46]), "+f"(d[47]), "+f"(d[48]), "+f"(d[49]), "+f"(d[50]), "+f"(d[51]), "+f"(d[52]), "+f"(d[53]), "+f"(d[54]), "+f"(d[55]), "+f"(d[56]), "+f"(d[57]), "+f"(d[58]), "+f"(d[59]), "+f"(d[60]), "+f"(d[61]), "+f"(d[62]), "+f"(d[63]), "+f"(d[64]), "+f"(d[65]), "+f"(d[66]), "+f"(d[67]), "+f"(d[68]), "+f"(d[69]), "+f"(d[70]), "+f"(d[71]), "+f"(d[72]), "+f"(d[73]), "+f"(d[74]), "+f"(d[75]), "+f"(d[76]), "+f"(d[77]), "+f"(d[78]), "+f"(d[79]), "+f"(d[80]), "+f"(d[81]), "+f"(d[82]), "+f"(d[83]), "+f"(d[84]), "+f"(d[85]), "+f"(d[86]), "+f"(d[87]), "+f"(d[88]), "+f"(d[89]), "+f"(d[90]), "+f"(d[91]), "+f"(d[92]), "+f"(d[93]), "+f"(d[94]), "+f"(d[95]), "+f"(d[96]), "+f"(d[97]), "+f"(d[98]), "+f"(d[99]), "+f"(d[100]), "+f"(d[101]), "+f"(d[102]), "+f"(d[103]), "+f"(d[104]), "+f"(d[105]), "+f"(d[106]), "+f"(d[107]), "+f"(d[108]), "+f"(d[109]), "+f"(d[110]), "+f"(d[111]), "+f"(d[112]), "+f"(d[113]), "+f"(d[114]), "+f"(d[115]), "+f"(d[116]), "+f"(d[117]), "+f"(d[118]), "+f"(d[119]), "+f"(d[120]), "+f"(d[121]), "+f"(d[122]), "+f"(d[123]), "+f"(d[124]), "+f"(d[125]), "+f"(d[126]), "+f"(d[127])
    : "l"(da), "l"(db), "r"(sd));
}

__device__ __forceinline__ void wgmma_m64n128_ss(float (&d)[64], uint64_t da, uint64_t db, int sd) {
  asm volatile(
    "{\n.reg .pred p;\nsetp.ne.b32 p, %66, 0;\n"
    "wgmma.mma_async.sync.aligned.m64n128k16.f32.bf16.bf16 "
    "{%0, %1, %2, %3, %4, %5, %6, %7, %8, %9, %10, %11, %12, %13, %14, %15, %16, %17, %18, %19, %20, %21, %22, %23, %24, %25, %26, %27, %28, %29, %30, %31, %32, %33, %34, %35, %36, %37, %38, %39, %40, %41, %42, %43, %44, %45, %46, %47, %48, %49, %50, %51, %52, %53, %54, %55, %56, %57, %58, %59, %60, %61, %62, %63}, %64, %65, p, 1, 1, 0, 0;\n}\n"
    : "+f"(d[0]), "+f"(d[1]), "+f"(d[2]), "+f"(d[3]), "+f"(d[4]), "+f"(d[5]), "+f"(d[6]), "+f"(d[7]), "+f"(d[8]), "+f"(d[9]), "+f"(d[10]), "+f"(d[11]), "+f"(d[12]), "+f"(d[13]), "+f"(d[14]), "+f"(d[15]), "+f"(d[16]), "+f"(d[17]), "+f"(d[18]), "+f"(d[19]), "+f"(d[20]), "+f"(d[21]), "+f"(d[22]), "+f"(d[23]), "+f"(d[24]), "+f"(d[25]), "+f"(d[26]), "+f"(d[27]), "+f"(d[28]), "+f"(d[29]), "+f"(d[30]), "+f"(d[31]), "+f"(d[32]), "+f"(d[33]), "+f"(d[34]), "+f"(d[35]), "+f"(d[36]), "+f"(d[37]), "+f"(d[38]), "+f"(d[39]), "+f"(d[40]), "+f"(d[41]), "+f"(d[42]), "+f"(d[43]), "+f"(d[44]), "+f"(d[45]), "+f"(d[46]), "+f"(d[47]), "+f"(d[48]), "+f"(d[49]), "+f"(d[50]), "+f"(d[51]), "+f"(d[52]), "+f"(d[53]), "+f"(d[54]), "+f"(d[55]), "+f"(d[56]), "+f"(d[57]), "+f"(d[58]), "+f"(d[59]), "+f"(d[60]), "+f"(d[61]), "+f"(d[62]), "+f"(d[63])
    : "l"(da), "l"(db), "r"(sd));
}

__device__ __forceinline__ void wgmma_m64n128_ss_tb(float (&d)[64], uint64_t da, uint64_t db, int sd) {
  asm volatile(
    "{\n.reg .pred p;\nsetp.ne.b32 p, %66, 0;\n"
    "wgmma.mma_async.sync.aligned.m64n128k16.f32.bf16.bf16 "
    "{%0, %1, %2, %3, %4, %5, %6, %7, %8, %9, %10, %11, %12, %13, %14, %15, %16, %17, %18, %19, %20, %21, %22, %23, %24, %25, %26, %27, %28, %29, %30, %31, %32, %33, %34, %35, %36, %37, %38, %39, %40, %41, %42, %43, %44, %45, %46, %47, %48, %49, %50, %51, %52, %53, %54, %55, %56, %57, %58, %59, %60, %61, %62, %63}, %64, %65, p, 1, 1, 0, 1;\n}\n"
    : "+f"(d[0]), "+f"(d[1]), "+f"(d[2]), "+f"(d[3]), "+f"(d[4]), "+f"(d[5]), "+f"(d[6]), "+f"(d[7]), "+f"(d[8]), "+f"(d[9]), "+f"(d[10]), "+f"(d[11]), "+f"(d[12]), "+f"(d[13]), "+f"(d[14]), "+f"(d[15]), "+f"(d[16]), "+f"(d[17]), "+f"(d[18]), "+f"(d[19]), "+f"(d[20]), "+f"(d[21]), "+f"(d[22]), "+f"(d[23]), "+f"(d[24]), "+f"(d[25]), "+f"(d[26]), "+f"(d[27]), "+f"(d[28]), "+f"(d[29]), "+f"(d[30]), "+f"(d[31]), "+f"(d[32]), "+f"(d[33]), "+f"(d[34]), "+f"(d[35]), "+f"(d[36]), "+f"(d[37]), "+f"(d[38]), "+f"(d[39]), "+f"(d[40]), "+f"(d[41]), "+f"(d[42]), "+f"(d[43]), "+f"(d[44]), "+f"(d[45]), "+f"(d[46]), "+f"(d[47]), "+f"(d[48]), "+f"(d[49]), "+f"(d[50]), "+f"(d[51]), "+f"(d[52]), "+f"(d[53]), "+f"(d[54]), "+f"(d[55]), "+f"(d[56]), "+f"(d[57]), "+f"(d[58]), "+f"(d[59]), "+f"(d[60]), "+f"(d[61]), "+f"(d[62]), "+f"(d[63])
    : "l"(da), "l"(db), "r"(sd));
}

__device__ __forceinline__ void wgmma_m64n128_rs_tb(float* d, uint32_t a0, uint32_t a1, uint32_t a2, uint32_t a3, uint64_t db, int sd) {
  asm volatile(
    "{\n.reg .pred p;\nsetp.ne.b32 p, %69, 0;\n"
    "wgmma.mma_async.sync.aligned.m64n128k16.f32.bf16.bf16 "
    "{%0, %1, %2, %3, %4, %5, %6, %7, %8, %9, %10, %11, %12, %13, %14, %15, %16, %17, %18, %19, %20, %21, %22, %23, %24, %25, %26, %27, %28, %29, %30, %31, %32, %33, %34, %35, %36, %37, %38, %39, %40, %41, %42, %43, %44, %45, %46, %47, %48, %49, %50, %51, %52, %53, %54, %55, %56, %57, %58, %59, %60, %61, %62, %63}, {%64, %65, %66, %67}, %68, p, 1, 1, 1;\n}\n"
    : "+f"(d[0]), "+f"(d[1]), "+f"(d[2]), "+f"(d[3]), "+f"(d[4]), "+f"(d[5]), "+f"(d[6]), "+f"(d[7]), "+f"(d[8]), "+f"(d[9]), "+f"(d[10]), "+f"(d[11]), "+f"(d[12]), "+f"(d[13]), "+f"(d[14]), "+f"(d[15]), "+f"(d[16]), "+f"(d[17]), "+f"(d[18]), "+f"(d[19]), "+f"(d[20]), "+f"(d[21]), "+f"(d[22]), "+f"(d[23]), "+f"(d[24]), "+f"(d[25]), "+f"(d[26]), "+f"(d[27]), "+f"(d[28]), "+f"(d[29]), "+f"(d[30]), "+f"(d[31]), "+f"(d[32]), "+f"(d[33]), "+f"(d[34]), "+f"(d[35]), "+f"(d[36]), "+f"(d[37]), "+f"(d[38]), "+f"(d[39]), "+f"(d[40]), "+f"(d[41]), "+f"(d[42]), "+f"(d[43]), "+f"(d[44]), "+f"(d[45]), "+f"(d[46]), "+f"(d[47]), "+f"(d[48]), "+f"(d[49]), "+f"(d[50]), "+f"(d[51]), "+f"(d[52]), "+f"(d[53]), "+f"(d[54]), "+f"(d[55]), "+f"(d[56]), "+f"(d[57]), "+f"(d[58]), "+f"(d[59]), "+f"(d[60]), "+f"(d[61]), "+f"(d[62]), "+f"(d[63])
    : "r"(a0), "r"(a1), "r"(a2), "r"(a3), "l"(db), "r"(sd));
}

__device__ __forceinline__ void wgmma_m64n96_ss(float (&d)[48], uint64_t da, uint64_t db, int sd) {
  asm volatile(
    "{\n.reg .pred p;\nsetp.ne.b32 p, %50, 0;\n"
    "wgmma.mma_async.sync.aligned.m64n96k16.f32.bf16.bf16 "
    "{%0, %1, %2, %3, %4, %5, %6, %7, %8, %9, %10, %11, %12, %13, %14, %15, %16, %17, %18, %19, %20, %21, %22, %23, %24, %25, %26, %27, %28, %29, %30, %31, %32, %33, %34, %35, %36, %37, %38, %39, %40, %41, %42, %43, %44, %45, %46, %47}, %48, %49, p, 1, 1, 0, 0;\n}\n"
    : "+f"(d[0]), "+f"(d[1]), "+f"(d[2]), "+f"(d[3]), "+f"(d[4]), "+f"(d[5]), "+f"(d[6]), "+f"(d[7]), "+f"(d[8]), "+f"(d[9]), "+f"(d[10]), "+f"(d[11]), "+f"(d[12]), "+f"(d[13]), "+f"(d[14]), "+f"(d[15]), "+f"(d[16]), "+f"(d[17]), "+f"(d[18]), "+f"(d[19]), "+f"(d[20]), "+f"(d[21]), "+f"(d[22]), "+f"(d[23]), "+f"(d[24]), "+f"(d[25]), "+f"(d[26]), "+f"(d[27]), "+f"(d[28]), "+f"(d[29]), "+f"(d[30]), "+f"(d[31]), "+f"(d[32]), "+f"(d[33]), "+f"(d[34]), "+f"(d[35]), "+f"(d[36]), "+f"(d[37]), "+f"(d[38]), "+f"(d[39]), "+f"(d[40]), "+f"(d[41]), "+f"(d[42]), "+f"(d[43]), "+f"(d[44]), "+f"(d[45]), "+f"(d[46]), "+f"(d[47])
    : "l"(da), "l"(db), "r"(sd));
}

__device__ __forceinline__ void wgmma_m64n64_ss(float (&d)[32], uint64_t da, uint64_t db, int sd) {
  asm volatile(
    "{\n.reg .pred p;\nsetp.ne.b32 p, %34, 0;\n"
    "wgmma.mma_async.sync.aligned.m64n64k16.f32.bf16.bf16 "
    "{%0, %1, %2, %3, %4, %5, %6, %7, %8, %9, %10, %11, %12, %13, %14, %15, %16, %17, %18, %19, %20, %21, %22, %23, %24, %25, %26, %27, %28, %29, %30, %31}, %32, %33, p, 1, 1, 0, 0;\n}\n"
    : "+f"(d[0]), "+f"(d[1]), "+f"(d[2]), "+f"(d[3]), "+f"(d[4]), "+f"(d[5]), "+f"(d[6]), "+f"(d[7]), "+f"(d[8]), "+f"(d[9]), "+f"(d[10]), "+f"(d[11]), "+f"(d[12]), "+f"(d[13]), "+f"(d[14]), "+f"(d[15]), "+f"(d[16]), "+f"(d[17]), "+f"(d[18]), "+f"(d[19]), "+f"(d[20]), "+f"(d[21]), "+f"(d[22]), "+f"(d[23]), "+f"(d[24]), "+f"(d[25]), "+f"(d[26]), "+f"(d[27]), "+f"(d[28]), "+f"(d[29]), "+f"(d[30]), "+f"(d[31])
    : "l"(da), "l"(db), "r"(sd));
}

__device__ __forceinline__ void wgmma_m64n32_ss(float (&d)[16], uint64_t da, uint64_t db, int sd) {
  asm volatile(
    "{\n.reg .pred p;\nsetp.ne.b32 p, %18, 0;\n"
    "wgmma.mma_async.sync.aligned.m64n32k16.f32.bf16.bf16 "
    "{%0, %1, %2, %3, %4, %5, %6, %7, %8, %9, %10, %11, %12, %13, %14, %15}, %16, %17, p, 1, 1, 0, 0;\n}\n"
    : "+f"(d[0]), "+f"(d[1]), "+f"(d[2]), "+f"(d[3]), "+f"(d[4]), "+f"(d[5]), "+f"(d[6]), "+f"(d[7]), "+f"(d[8]), "+f"(d[9]), "+f"(d[10]), "+f"(d[11]), "+f"(d[12]), "+f"(d[13]), "+f"(d[14]), "+f"(d[15])
    : "l"(da), "l"(db), "r"(sd));
}

constexpr int G_STAGES = 4;
constexpr int G_A_BYTES = 128 * 64 * 2;
constexpr int G_B_BYTES = 256 * 64 * 2;
constexpr int G_STAGE_BYTES = G_A_BYTES + G_B_BYTES;
constexpr int G_STG_OFF = G_STAGES * G_STAGE_BYTES;
constexpr int BAR_OFF = G_STG_OFF + 32768 + 2048;
constexpr int SMEM_BYTES = BAR_OFF + 1024;
constexpr int B_GFULL = 0, B_GEMPTY = 32, B_OY2 = 64, B_PFULL = 224;
constexpr int B_KFULL = 80, B_KEMPTY = 96, B_VFULL = 112, B_VEMPTY = 128, B_QFULL = 144, B_QEMPTY = 160,
              B_QDONE = 184;
constexpr int B_CFULL = 192;
constexpr int B_OFREE = 256, B_OFULL = 272, B_OEMPTY = 320, B_OY = 368;
constexpr int B_SFULL = 392, B_SFREE = 424, B_PEND = 456, B_SCMD = 512;

#define PHASE_PROLOGUE                                                                \
  uint32_t tid, rt_zero;                                                              \
  asm volatile("mov.u32 %0, %%tid.x;" : "=r"(tid));                                   \
  asm volatile("mov.u32 %0, %%nctaid.y;" : "=r"(rt_zero));                            \
  asm volatile("" : "+r"(smem0));                                                     \
  rt_zero = __shfl_sync(0xffffffffu, rt_zero >> 8, 0);   \
  const uint32_t sbase = __shfl_sync(0xffffffffu, smem0, 0);                          \
  const uint32_t bar = sbase + BAR_OFF;                                               \
  const int wg = __shfl_sync(0xffffffffu, tid >> 7, 0);                               \
  const int warp = (tid >> 5) & 3, lane = tid & 31, wtid = tid & 127;                 \
  (void)rt_zero; (void)bar; (void)warp; (void)lane; (void)wtid;

enum { ST_END = 0, ST_BOX1, ST_BOX2, ST_BOX2Q, ST_BOX2L };
__device__ __forceinline__ void st_post(uint32_t bar, int wg, int wtid, uint32_t n, int kind, const void* dst,
                                        uint32_t src, int c0, int c1, int sig) {
  if (wtid == 0) {
    const uint32_t c = bar + B_SCMD + wg * 64 + (n & 1) * 32;
    const uint64_t d = reinterpret_cast<uint64_t>(dst);
    sts128(c, make_uint4(kind, src, c0, c1));
    sts128(c + 16, make_uint4((uint32_t)d, (uint32_t)(d >> 32), sig, 0));
  }
  fence_proxy_async();
  __syncwarp();
  mbar_arrive_if(bar + B_SFULL + wg * 16 + (n & 1) * 8, (wtid & 31) == 0);
}
__device__ __forceinline__ void st_wait(uint32_t bar, int wg, uint32_t n) {
  const uint32_t b = bar + B_SFREE + wg * 16 + (n & 1) * 8;
  if (!mbar_try(b, ~(n >> 1) & 1)) mbar_wait(b, ~(n >> 1) & 1);
}
__device__ __forceinline__ void note(uint32_t bar, uint32_t cnt) {
  asm volatile("red.release.cta.shared.add.u32 [%0], 1;" ::"r"(bar + B_PEND + 4 * cnt) : "memory");
}
__device__ __forceinline__ void store_agent(uint32_t bar, int wg) {
  mbar_arrive(bar + B_SFREE + wg * 16);
  mbar_arrive(bar + B_SFREE + wg * 16 + 8);
  bool more = true;
  for (uint32_t n = 0;; n++) {
    mbar_wait_sleep(bar + B_SFULL + wg * 16 + (n & 1) * 8, (n >> 1) & 1);
    const uint4 c = lds128(bar + B_SCMD + wg * 64 + (n & 1) * 32);
    const uint4 d = lds128(bar + B_SCMD + wg * 64 + (n & 1) * 32 + 16);
    if (c.x == ST_END) break;
    const CUtensorMap* dst = reinterpret_cast<const CUtensorMap*>((uint64_t)d.x | ((uint64_t)d.y << 32));
    tma_store_2d(dst, c.y, c.z, c.w);
    if (c.x >= ST_BOX2) tma_store_2d(dst, c.y + 8192, c.z + 64, c.w);
    tma_store_commit();
    tma_store_wait_read<0>();
    mbar_arrive(bar + B_SFREE + wg * 16 + (n & 1) * 8);
    if (c.x == ST_BOX2L) mbar_arrive(bar + B_OFREE + 8 * wg);
    if ((int)d.z >= 0) {
      tma_store_wait<0>();
      if (d.z == 0) { TD(6) }
      asm volatile("fence.proxy.async.global;" ::: "memory");
      if (c.x == ST_BOX2Q) mbar_arrive(bar + B_QDONE);
      else note(bar, d.z);
      if (c.x == ST_BOX2L) {
        note(bar, CNT_DONE);
        more = false;
      }
    }
  }
  if (more) note(bar, CNT_DONE);
}

struct Maps {
  const bf16 *shift_k, *x, *gate_w, *ssm_k, *ssm_D;
  uint8_t id[128][4];
  CUtensorMap a[2];
  CUtensorMap b[3];
  CUtensorMap c[3];
  CUtensorMap bk, bv;
  CUtensorMap q, k, v, o;
  CUtensorMap oa, ob, oc;
  CUtensorMap y, y2;
};

constexpr int P_SLOT = 67 * 128, P_V = 35 * 128, P_TAPS = 2 * P_SLOT;
__device__ __forceinline__ void ldsm4t(uint32_t (&r)[4], uint32_t a) {
  asm volatile("ldmatrix.sync.aligned.m8n8.x4.trans.shared.b16 {%0, %1, %2, %3}, [%4];"
               : "=r"(r[0]), "=r"(r[1]), "=r"(r[2]), "=r"(r[3])
               : "r"(a));
}
__device__ __forceinline__ uint32_t fma_bf2(uint32_t a, uint32_t b, uint32_t c) {
  uint32_t r;
  asm("fma.rn.bf16x2 %0, %1, %2, %3;" : "=r"(r) : "r"(a), "r"(b), "r"(c));
  return r;
}
__device__ __forceinline__ void prep_agent(const Maps& maps, uint32_t sbase, int w, int lane) {
  const uint32_t bar = sbase + BAR_OFF, pb = bar + B_PFULL + w * 16;
  const int d0 = (blockIdx.x >> 3) * 64, t0 = (blockIdx.x & 7) * 256 + w * 128;
  mbar_wait_sleep(bar + B_GFULL + 8 * (G_STAGES - 1), 0);
#pragma unroll 1
  for (int i = -1; i < 4; i++) {
    GA(82 + 2 * i)
    if (i >= 0) mbar_wait_sleep(pb + (i & 1) * 8, i >> 1);
    GA(83 + 2 * i)
    const uint32_t so = sbase + G_STG_OFF + w * (P_TAPS + 512) + (i & 1) * P_SLOT;
    if (i < 3 && elect_one()) {
      const uint32_t b = pb + (~i & 1) * 8, dst = so + (i & 1 ? -P_SLOT : P_SLOT);
      mbar_expect_tx(b, i < 0 ? P_SLOT + 512 : P_SLOT);
      const uint64_t pol = policy_evict_first();
      tma_load_2d_hint(dst, &maps.bk, b, d0, t0 + 32 * i + 29, pol);
      tma_load_2d_hint(dst + P_V, &maps.bv, b, d0, t0 + 32 * i + 32, pol);
      if (i < 0) bulk_load(sbase + G_STG_OFF + P_TAPS, maps.shift_k + d0 * 4, 512, b);
    }
    if (i < 0) continue;
    uint32_t ak[4];
#pragma unroll
    for (int r = 0; r < 4; r++) {
      const uint32_t a = so / 128 + r + 4 * (lane & 6) + (((lane >> 2) ^ lane) & 6) + (lane & 1);
      ak[r] = a * 128 + (a & 7) * 16;
    }
    bf16* dst = g_kvT + (size_t)(d0 + (lane >> 2)) * S_LEN + t0 + (((lane & 3) + 4 * i) ^ ((t0 >> 6) & 6)) * 8;
#pragma unroll 1
    for (int cg = 0; cg < 128; cg += 16) {
      uint32_t t01, t23, k[4][4], v[4];
      asm volatile("ld.shared.v2.u32 {%0, %1}, [%2];"
                   : "=r"(t01), "=r"(t23)
                   : "r"(sbase + G_STG_OFF + P_TAPS + cg * 4 + (lane >> 2) * 8));
#pragma unroll
      for (int r = 0; r < 4; r++) ldsm4t(k[r], ak[r] ^ cg);
      ldsm4t(v, (ak[3] ^ cg) + 4096);
      const uint32_t w0 = __byte_perm(t01, 0, 0x1010), w1 = __byte_perm(t01, 0, 0x3232);
      const uint32_t w2 = __byte_perm(t23, 0, 0x1010), w3 = __byte_perm(t23, 0, 0x3232);
#pragma unroll
      for (int j = 0; j < 4; j++)
        v[j] = mul_bf2(fma_bf2(k[3][j], w0, fma_bf2(k[2][j], w1, fma_bf2(k[1][j], w2, mul_bf2(k[0][j], w3)))), v[j]);
      const bool s1 = lane & 1, s2 = lane & 2;
      const uint32_t a0 = s1 ? v[1] : v[0], a1 = s1 ? v[0] : v[1], a2 = s1 ? v[3] : v[2], a3 = s1 ? v[2] : v[3];
      *reinterpret_cast<uint4*>(dst) = make_uint4(s2 ? a2 : a0, s2 ? a3 : a1, s2 ? a0 : a2, s2 ? a1 : a3);
      dst += 8 * S_LEN;
    }
    fence_proxy_async();
    __syncwarp();
  }
  GA(90)
  if (lane == 0) note(bar, CNT_PREP);
  __syncwarp();
  GA(91)
}

__device__ __forceinline__ void qkv_tile(const Maps& maps, int it, int& which, int& m_tile, int& n_tile) {
  const bool q = it == 0 || it >= 5;
  const int b = maps.id[blockIdx.x][it >= 5];
  which = q ? 0 : 2 - (it & 1);
  m_tile = b & 15;
  n_tile = (b >> 4) * 2 + ((0x19 >> it) & 1);
}

constexpr int G_NTILES = 6;
__device__ __forceinline__ void qkv_producer(const Maps& maps, uint32_t sbase, bool first) {
  const uint32_t bar = sbase + BAR_OFF;
  uint32_t stage = 0, phase = 0;
#pragma unroll 1
  for (int it = 0; it < (first ? 1 : G_NTILES); it++) {
    int which, m_tile, n_tile;
    qkv_tile(maps, it, which, m_tile, n_tile);
    const CUtensorMap* ma = &maps.a[which == 0 ? 0 : 1];
    const CUtensorMap* mb = &maps.b[which];
    const int nk = first ? G_STAGES : which == 0 ? 16 : 8;
#pragma unroll 1
    for (int kt = (it == 0 && !first) ? G_STAGES : 0; kt < nk; kt++) {
      if (!first) mbar_wait_sleep(bar + B_GEMPTY + 8 * stage, phase);
      const uint32_t fb = bar + B_GFULL + 8 * stage;
      const uint32_t sa = sbase + stage * G_STAGE_BYTES;
      mbar_expect_tx(fb, G_STAGE_BYTES);
      tma_load_2d(sa, ma, fb, kt * 64, m_tile * 128);
      tma_load_3d(sa + G_A_BYTES, mb, fb, 0, kt * 64, n_tile * 4);
      if (++stage == G_STAGES) { stage = 0; phase ^= 1; }
      {
        const int b = maps.id[blockIdx.x][1];
        if (it == 2 && kt == (b & 7)) {
          for (int i = 0; i < 2; i++)
            asm volatile("cp.async.bulk.prefetch.tensor.2d.L2.global.tile [%0, {%1, %2}];" ::"l"(&maps.a[0]),
                         "r"((b >> 4) * 128 + i * 64), "r"((b & 15) * 128)
                         : "memory");
        }
        if (it == 3 && kt == (b & 7))
          asm volatile("cp.async.bulk.prefetch.tensor.3d.L2.global.tile [%0, {%1, %2, %3}];" ::"l"(&maps.b[0]), "r"(0),
                       "r"((b & 15) * 64), "r"((b >> 4) * 8)
                       : "memory");
      }
    }
  }
}

__device__ __noinline__ void publisher(uint32_t bar, int lane, uint32_t nsrc) {
  uint32_t done = 0;
  CLK_DECL
#pragma unroll 1
  for (uint32_t spins = 0; done < nsrc && spins < (1u << 20); spins++) {
    CLK_SAMPLE
    uint32_t v = 0;
    if (lane < CNT_N)
      asm volatile("atom.acquire.cta.shared.exch.b32 %0, [%1], 0;" : "=r"(v) : "r"(bar + B_PEND + 4 * lane) : "memory");
    done += __shfl_sync(0xffffffffu, v, CNT_DONE);
    if (lane == CNT_DONE) v = 0;
    if (done == nsrc && lane < CNT_DONE) {
      uint32_t w;
      asm volatile("atom.acquire.cta.shared.exch.b32 %0, [%1], 0;" : "=r"(w) : "r"(bar + B_PEND + 4 * lane) : "memory");
      v += w;
    }
    if (v && lane == 0) { TD(0) }
    if (v) cnt_signal_release(lane, v);
    if (v && lane == 0) { TD(1) }
    if (!__any_sync(0xffffffffu, v != 0)) __nanosleep(200);
  }
  CLK_END
  __threadfence();
  __syncwarp();
}

__device__ __forceinline__ void gate_rows(const Maps& maps, uint32_t sbase, int w48, int w12, int lane) {
  const uint32_t buf = sbase + w12 * 16384, gb = sbase + BAR_OFF + 768 + w12 * 16;
  if (lane == 0) {
    mbar_init(gb, 1);
    mbar_init(gb + 8, 1);
    fence_barrier_init();
    for (int i = 0; i < 2; i++) {
      mbar_expect_tx(gb + 8 * i, 8192);
      bulk_load(buf + i * 8192, maps.x + (size_t)(w48 + 48 * i) * 4 * DM, 8192, gb + 8 * i);
    }
  }
  __syncwarp();
  uint4 wv[4];
#pragma unroll
  for (int i = 0; i < 4; i++) wv[i] = __ldg(reinterpret_cast<const uint4*>(maps.gate_w + (i * 32 + lane) * 8));
  int it = 0;
#pragma unroll 1
  for (int row = w48 * 4; row < S_LEN; row += 48 * 4, it++) {
    mbar_wait(gb + 8 * (it & 1), (it >> 1) & 1);
    uint4 xv[4][4];
#pragma unroll
    for (int r = 0; r < 4; r++)
#pragma unroll
      for (int i = 0; i < 4; i++) xv[r][i] = lds128(buf + (it & 1) * 8192 + r * 2048 + (i * 32 + lane) * 16);
    float d[2][4];
#pragma unroll
    for (int pr = 0; pr < 2; pr++) {
      d[pr][0] = d[pr][1] = d[pr][2] = d[pr][3] = 0.f;
      auto acc = [&](uint32_t a0, uint32_t a2, uint32_t b0, uint32_t b2, uint32_t w0, uint32_t w2) {
        asm volatile(
            "mma.sync.aligned.m16n8k16.row.col.f32.bf16.bf16.f32 {%0, %1, %2, %3}, {%4, %5, %6, %7}, {%8, %8}, "
            "{%0, %1, %2, %3};"
            : "+f"(d[pr][0]), "+f"(d[pr][1]), "+f"(d[pr][2]), "+f"(d[pr][3])
            : "r"(mul_bf2(a0, w0)), "r"(mul_bf2(b0, w0)), "r"(mul_bf2(a2, w2)), "r"(mul_bf2(b2, w2)), "r"(0x3f803f80u));
      };
#pragma unroll
      for (int i = 0; i < 4; i++) {
        acc(xv[2 * pr][i].x, xv[2 * pr][i].y, xv[2 * pr + 1][i].x, xv[2 * pr + 1][i].y, wv[i].x, wv[i].y);
        acc(xv[2 * pr][i].z, xv[2 * pr][i].w, xv[2 * pr + 1][i].z, xv[2 * pr + 1][i].w, wv[i].z, wv[i].w);
      }
    }
    float sum = (lane & 2) ? ((lane & 1) ? d[1][2] : d[1][0]) : ((lane & 1) ? d[0][2] : d[0][0]);
#pragma unroll
    for (int off = 16; off >= 4; off >>= 1) sum += __shfl_xor_sync(0xffffffffu, sum, off);
    if (lane < 4) g_gate[row + lane] = bf16_round(rcp(1.0f + __expf(-bf16_round(sum))));
    if (lane == 0 && row + 2 * 48 * 4 < S_LEN) {
      mbar_expect_tx(gb + 8 * (it & 1), 8192);
      bulk_load(buf + (it & 1) * 8192, maps.x + (size_t)(row + 2 * 48 * 4) * DM, 8192, gb + 8 * (it & 1));
    }
  }
}

constexpr float Q_SCALE = 0.08838834764831845f * 1.4426950408889634f;
__device__ __forceinline__ uint32_t qkv_consumer(const Maps& maps, uint32_t smem0, bool fused, float (&rest)[64]) {
  PHASE_PROLOGUE
  constexpr int NTILES = G_NTILES;
  float acc[128];
  uint32_t stage = 0, phase = 0;
  const uint32_t stg = sbase + G_STG_OFF + wg * 18432;
  const int st_row = warp * 16 + (lane & 7) + ((lane >> 3) & 1) * 8;
  const int st_cb = lane >> 4;
  uint32_t pend[64];
  const CUtensorMap* pend_map = nullptr;
  int pend_c0 = 0, pend_c1 = 0;
  uint32_t sn = 0;
  auto put_box = [&](uint32_t buf, const uint32_t* v) {
#pragma unroll
    for (int jp = 0; jp < 4; jp++) {
      const int chunk = jp * 2 + st_cb;
      const uint32_t addr = buf + st_row * 128 + ((chunk ^ (st_row & 7)) << 4);
      stmatrix_x4(addr, v[jp * 4], v[jp * 4 + 1], v[jp * 4 + 2], v[jp * 4 + 3]);
    }
  };
  GT(gti++)
#pragma unroll 1
  for (int it = 0; it <= NTILES; it++) {
    int which, m_tile, n_tile;
    qkv_tile(maps, it, which, m_tile, n_tile);
    const int nk = (which == 0 && it < NTILES) ? 16 : 8;
    uint32_t prev_stage = 0;
#pragma unroll 1
    for (int kt = 0; kt < nk; kt++) {
      if (it < NTILES) {
        mbar_wait((bar + B_GFULL) + 8 * stage, phase);
        GT(gti++)
        const uint64_t da0 = make_desc(sbase + stage * G_STAGE_BYTES + wg * 8192, 16, 1024, DESC_SW128);
        const uint64_t db0 = make_desc(sbase + stage * G_STAGE_BYTES + G_A_BYTES, 8192, 1024, DESC_SW128);
        wgmma_fence();
#pragma unroll
        for (int kk = 0; kk < 4; kk++) {
          wgmma_m64n256_ss_tb(acc, desc_add(da0, kk * 2), desc_add(db0, kk * 128), (kt | kk) != 0);
        }
        wgmma_commit();
      }
      const uint32_t when = it == 0 ? 0 : it == 5 ? 0x922 << wg : wg ? 0xAA : 0x55;
      if ((when >> kt) & 1) {
        const int c = __popc(when & ~(~0u << kt));
        st_wait(bar, wg, sn - 2);
        const uint32_t buf = stg + (c & 1) * 8192;
        switch (c) {
          case 0: put_box(buf, pend); break;
          case 1: put_box(buf, pend + 16); break;
          case 2: put_box(buf, pend + 32); break;
          default: put_box(buf, pend + 48); break;
        }
        st_post(bar, wg, wtid, sn, ST_BOX1, pend_map, buf, pend_c0 + c * 64, pend_c1, (c == 3 && it > 1) ? CNT_KV + (it > 3) : -1);
        sn++;
      }
      if (it < NTILES) {
        wgmma_wait<1>();
        mbar_arrive_if((bar + B_GEMPTY) + 8 * prev_stage, wtid == 32 && kt > 0);
        prev_stage = stage;
        if (++stage == G_STAGES) { stage = 0; phase ^= 1; }
      }
    }
    wgmma_wait<0>();
    fence_regs(acc);
    if (it == NTILES) break;
    GT(gti++)
    mbar_arrive_if((bar + B_GEMPTY) + 8 * prev_stage, wtid == 32);
    if (it == NTILES - 1 && fused) break;
    if (which == 0) {
#pragma unroll
      for (int j = 0; j < 128; j++) acc[j] *= Q_SCALE;
    }
#pragma unroll
    for (int j = 0; j < 64; j++) pend[j] = pack_bf16(acc[2 * j], acc[2 * j + 1]);
    pend_map = &maps.c[which];
    pend_c0 = n_tile * 256;
    pend_c1 = m_tile * 128 + wg * 64;
  }
  mbar_wait(bar + B_GEMPTY, 1);
#pragma unroll
  for (int j = 0; j < 32; j++) pend[j] = pack_bf16(acc[2 * j] * Q_SCALE, acc[2 * j + 1] * Q_SCALE);
  put_box(sbase + wg * 8192, pend);
  put_box(sbase + 16384 + wg * 8192, pend + 16);
  fence_proxy_async();
#pragma unroll
  for (int j = 0; j < 64; j++) rest[j] = acc[64 + j];
  GT(gti++)
  return sn;
}

constexpr int A_TILE = 128 * 128 * 2;
constexpr int A_Q_OFF = 0;
constexpr int A_K_OFF = 2 * A_TILE;
constexpr int A_V_OFF = 4 * A_TILE;
constexpr int A_O_OFF = 6 * A_TILE;
constexpr int A_ITEMS = NH * (S_LEN / 128);

constexpr uint32_t A_ORDER = 0x3120, A_STEPS = 34;
__device__ __forceinline__ int item_m(uint32_t it) { return it & 15; }
__device__ __forceinline__ int item_h(uint32_t it) { return it >> 4; }

constexpr int C_TP = 2064;
constexpr int C_SLOT = 256 + 4096;
constexpr int C_S_OFF = 16 * C_TP + 256;
constexpr int C_X_OFF = 16 * C_TP + 3 * C_SLOT;
constexpr uint32_t C_XBASE = 0x2117'0c00u;

template <int A>
__device__ __forceinline__ void conv_put(const float (&acc)[64], uint32_t keep, uint32_t xl, uint32_t xm) {
#pragma unroll
  for (int blk = 4 * A; blk < 4 * A + 4; blk++) {
    const float* v = &acc[(15 - blk) * 4];
    asm volatile(
        "{\n.reg .pred p;\nsetp.eq.u32 p, %5, 0;\n@p st.shared.v4.f32 [%0], {%1, %2, %3, %4};\n}\n" ::"r"(
            (blk < 4 ? xl : blk < 9 ? xm : xl - 2048) + blk * 512),
        "f"(v[0]), "f"(v[1]), "f"(v[2]), "f"(v[3]), "r"(keep & (1u << blk))
        : "memory");
  }
}
template <int W>
__device__ __forceinline__ void conv_keep(const float (&acc)[64], float (&own)[16]) {
#pragma unroll
  for (int i = 0; i < 16; i++)
    asm volatile("mov.b32 %0, %1;" : "=f"(own[i]) : "f"(acc[(15 - 3 * W - (i >> 2)) * 4 + (i & 3)]));
}

__device__ __forceinline__ uint32_t item_of(const Maps& maps, uint32_t r) {
  const uint32_t b = maps.id[blockIdx.x & 127][1];
  return (b >> 4) * 64 + ((A_ORDER >> (4 * r)) & 3) * 16 + ((b ^ ((r & 1) * 15)) & 15);
}

constexpr uint32_t C_SIDE = 34;
__device__ __forceinline__ uint32_t conv_first(const Maps& maps) {
  const uint32_t b = maps.id[blockIdx.x & 127][1];
  return (b >> 4) * 128 + C_SIDE + ((b + 33 - C_SIDE) & 15);
}

__device__ __forceinline__ void conv_consumer(const Maps& maps, uint32_t smem0, uint32_t first, uint32_t step,
                                              uint32_t end) {
  PHASE_PROLOGUE
  const uint32_t h_full = bar + B_CFULL + wg * 16, u_full = h_full + 8;
  const uint32_t ca = sbase + (wg ? A_V_OFF + A_TILE : A_Q_OFF);
  const int w4 = __shfl_sync(0xffffffffu, warp, 0);
  uint32_t ba[3], tdst;
  {
    const int b = lane & 3, hf = (lane >> 2) & 1, c = (lane >> 3) + 4 * warp;
    const int own = b * 256 + ((c ^ (2 * b)) << 4);
    const int prev = c ? b * 256 + (((c - 1) ^ (2 * b)) << 4) : (b - 1) * 256 + ((15 ^ (2 * ((b - 1) & 3))) << 4);
    ba[0] = prev + 8 * hf;
    ba[1] = hf ? own : prev + 8;
    ba[2] = own + 8 * hf;
    tdst = ca + (15 - b) * C_TP + (15 - c) * 128 + hf * 64;
  }
  auto load_u = [&](uint32_t (&l)[6], uint32_t us, int Q) {
#pragma unroll
    for (int i = 0; i < 3; i++)
      asm volatile("ld.shared.v2.u32 {%0, %1}, [%2];" : "=r"(l[2 * i]), "=r"(l[2 * i + 1]) : "r"(us + ba[i] + Q * 1024));
  };
  auto build = [&](const uint32_t (&l)[6], int Q, bool on) {
    auto pp = [&](int x) {
      return (x & 1) ? __byte_perm(l[x >> 1], 0, 0x1032) : __byte_perm(l[x >> 1], l[(x >> 1) - 1], 0x7610);
    };
#pragma unroll
    for (int j = 0; j < 4; j++)
      asm volatile("{\n.reg .pred p;\nsetp.ne.u32 p, %5, 0;\n@p st.shared.v4.u32 [%0], {%1, %2, %3, %4};\n}\n" ::"r"(
                       tdst - Q * 4 * C_TP + j * 16),
                   "r"(pp(8 + j)), "r"(pp(6 + j)), "r"(pp(4 + j)), "r"(pp(2 + j)), "r"((uint32_t)on)
                   : "memory");
  };
  const uint32_t xa = ca + C_X_OFF + lane * 16;
  uint32_t xg[3];
#pragma unroll
  for (int k = 0; k < 3; k++) {
    const int w = (w4 + k + 1) & 3;
    xg[k] = xa + (((C_XBASE >> (8 * w)) & 255) + 4 * w4 - w - (w < w4 ? 4 : 0)) * 512;
  }
  const uint32_t xl = xa + ((C_XBASE >> (8 * w4)) & 255) * 512, xm = xl - (w4 < 2 ? 2048 : 0);
  const uint32_t keep = (15u << (3 * w4)) | (0xffff0000u >> w4);
  auto fetch = [&](const bf16* src, uint32_t c, uint32_t dst, uint32_t fb) {
    if (w4 == 2 && c < end) {
      if (elect_one()) {
        mbar_expect_tx(fb, 4096);
        bulk_load_hint(dst, src + (size_t)c * S_LEN, 4096, fb, policy_evict_first());
      }
    }
  };
  const uint32_t su = ca + C_S_OFF, sh = su + C_SLOT;
  if (wtid == 96 && wg) { TD(15) }
  mbar_wait(bar + B_OFREE, 0);
  fetch(g_kvT, first, su, u_full);
  if (wtid < 48) sts128(su - 256 + (wtid >> 4) * C_SLOT + (wtid & 15) * 16, make_uint4(0, 0, 0, 0));
  float own[16];
  uint32_t sk[8], skn[8];
  uint4 q[12];
#pragma unroll
  for (int i = 0; i < 16; i++) own[i] = 0.f;
#pragma unroll
  for (int i = 0; i < 8; i++) sk[i] = skn[i] = 0;
  auto load_x = [&]() {
#pragma unroll
    for (int i = 0; i < 12; i++) {
      if (i / 3 > i % 3) {
        q[i] = lds128(xg[i % 3] + (i / 3) * 512);
      } else {
        q[i] = make_uint4(0, 0, 0, 0);
        asm volatile("{\n.reg .pred p;\nsetp.ne.u32 p, %5, 0;\n@p ld.shared.v4.u32 {%0, %1, %2, %3}, [%4];\n}\n"
                     : "+r"(q[i].x), "+r"(q[i].y), "+r"(q[i].z), "+r"(q[i].w)
                     : "r"(xg[i % 3] + (i / 3) * 512), "r"(w4));
      }
    }
  };
  auto sum = [&](uint32_t c) {
    uint32_t* dst = reinterpret_cast<uint32_t*>(g_y2T + (size_t)c * S_LEN) + 256 * w4 + lane;
#pragma unroll
    for (int f = 0; f < 4; f++) {
#pragma unroll
      for (int k = 0; k < 3; k++) {
        own[4 * f] += __uint_as_float(q[3 * f + k].x);
        own[4 * f + 1] += __uint_as_float(q[3 * f + k].y);
        own[4 * f + 2] += __uint_as_float(q[3 * f + k].z);
        own[4 * f + 3] += __uint_as_float(q[3 * f + k].w);
      }
      dst[64 * f] = add_bf2(pack_bf16(own[4 * f], own[4 * f + 1]), sk[2 * f]);
      dst[64 * f + 32] = add_bf2(pack_bf16(own[4 * f + 2], own[4 * f + 3]), sk[2 * f + 1]);
    }
  };
  uint32_t n = 0, nch = first;
  for (; nch < end + step; n++, nch += step) {
    CT(0)
    uint32_t l0[6], l1[6], l2[6], l3[6], ur[8];
    auto load_skip = [&]() {
#pragma unroll
      for (int i = 0; i < 8; i++)
        asm volatile("ld.shared.u32 %0, [%1];"
                     : "=r"(ur[i])
                     : "r"(su + (4 * w4 + (i >> 1)) * 256 + (i & 1) * 128 + (((lane >> 2) ^ (i & 6)) << 4) + (lane & 3) * 4));
    };
    uint32_t dsk = __ldg(reinterpret_cast<const unsigned short*>(maps.ssm_D) + ((nch & (DM - 1)) | (lane & rt_zero)));
    auto skip_terms = [&]() {
#pragma unroll
      for (int i = 0; i < 8; i++) {
        sk[i] = skn[i];
        skn[i] = mul_bf2(ur[i], dsk | (dsk << 16));
      }
    };
    const uint32_t par = (n & 1) ^ (nch < end ? 0 : 1);
#define CONV_PUT(A) conv_put<A>(acc, keep, xl, xm);
#define CONV_MMA(A, MMA, D)                                                                   \
    wgmma_fence();                                                                            \
    _Pragma("unroll") for (int b = 0; b < 8; b++)                                             \
        MMA(D, (8ull << 32) | (da + 64 * A + 2 * b), ((uint64_t)(C_TP / 16) << 32) | (db + (C_TP / 4) * A + 16 * b), b != 0); \
    wgmma_commit();
#define CONV_ADD(D, N)                                                                        \
    fence_regs(D);                                                                            \
    _Pragma("unroll") for (int i = 0; i < N; i++) acc[i] += D[i];
    if (n > 0) {
      uint32_t da = (uint32_t)make_desc(sh - 240 + (~n & 1) * C_SLOT, 16, 0, 0), db = (uint32_t)make_desc(ca, 128, 0, 0);
      asm volatile("" : "+r"(da), "+r"(db));
      float acc[64], a1[48], a2[32], a3[16];
      fetch(maps.ssm_k, nch, sh + (n & 1) * C_SLOT, h_full);
      load_x();
      CONV_MMA(0, wgmma_m64n128_ss, acc)
      mbar_wait(u_full, par);
      load_u(l3, su, 3);
      load_u(l2, su, 2);
      load_u(l1, su, 1);
      load_u(l0, su, 0);
      load_skip();
      if (n > 1) sum(nch - 2 * step);
      else mbar_wait(bar + B_OFREE + 8, 0);
      CT(1)
      CONV_MMA(1, wgmma_m64n96_ss, a1)
      CT(2)
      wgmma_wait<1>();
      fence_regs(acc);
      skip_terms();
      uint32_t dep = skn[0] | skn[1] | skn[2] | skn[3] | skn[4] | skn[5] | skn[6] | skn[7];
#pragma unroll
      for (int i = 0; i < 6; i += 2) dep |= l0[i] | l1[i] | l2[i] | l3[i];
      named_bar_sync((1 + wg) | (dep & rt_zero), 128);
      fetch(g_kvT, nch + step, su, u_full);
      if (wtid == 96 && n > 1) note(bar, CNT_Y2 + (step == 16 && nch >= end));
      CONV_PUT(0)
      build(l3, 3, nch < end);
      CT(3)
      CONV_MMA(2, wgmma_m64n64_ss, a2)
      wgmma_wait<1>();
      CONV_ADD(a1, 48)
      CONV_PUT(1)
      build(l2, 2, nch < end);
      CT(4)
      CONV_MMA(3, wgmma_m64n32_ss, a3)
      wgmma_wait<1>();
      CONV_ADD(a2, 32)
      CONV_PUT(2)
      build(l1, 1, nch < end);
      CT(5)
      wgmma_wait<0>();
      CONV_ADD(a3, 16)
      CONV_PUT(3)
      build(l0, 0, nch < end);
      if (w4 == 0) conv_keep<0>(acc, own);
      else if (w4 == 1) conv_keep<1>(acc, own);
      else if (w4 == 2) conv_keep<2>(acc, own);
      else conv_keep<3>(acc, own);
    } else {
      fetch(maps.ssm_k, nch, sh, h_full);
      mbar_wait(u_full, par);
      named_bar_sync(1 + wg, 128);
#pragma unroll 1
      for (int Q = 3; Q >= 0; Q--) {
        load_u(l0, su, Q);
        build(l0, Q, true);
      }
      load_skip();
      skip_terms();
      named_bar_sync((1 + wg) | ((skn[0] | skn[1] | skn[2] | skn[3] | skn[4] | skn[5] | skn[6] | skn[7]) & rt_zero), 128);
      fetch(g_kvT, nch + step, su, u_full);
    }
    CT(6)
    fence_proxy_async();
    mbar_wait(h_full, par);
    named_bar_sync(1 + wg, 128);
    CT(7)
  }
  load_x();
  sum(nch - 2 * step);
  named_bar_sync(1 + wg, 128);
  if (wtid == 96 && wg) { TD(8) }
  if (wtid == 96) cnt_signal_release(CNT_Y2 + (step == 16), 1);
  if (wtid == 64) note(bar, CNT_DONE);
  if (wtid == 96 && wg) { TD(9) }
  mbar_wait(bar + B_OFREE + 8, 0);
}

__device__ __forceinline__ void attn_producer(const Maps& maps, uint32_t sbase, bool after_qkv, bool to_out,
                                              bool dry) {
  const uint32_t bar = sbase + BAR_OFF;
  const uint32_t q_full = bar + B_QFULL, q_empty = bar + B_QEMPTY;
  const uint32_t k_full = bar + B_KFULL, k_empty = bar + B_KEMPTY, v_full = bar + B_VFULL, v_empty = bar + B_VEMPTY;
  int ndrained = after_qkv ? 0 : G_STAGES;
  auto wait = [&](uint32_t b, uint32_t par) {
    if (!dry) mbar_wait_sleep(b, par);
  };
  auto drained = [&](int upto) {
#pragma unroll 1
    for (; ndrained <= upto; ndrained++) wait(bar + B_GEMPTY + 8 * ndrained, 1);
  };
  uint32_t st = 0, ph = 1, vs = 0, vp = 1;
  int pend_j = -1, pend_h = 0;
  int round = -1, m = -1, h = 0;
  bool last = false;
#pragma unroll 1
  for (;; round++) {
    uint32_t nitem = 0;
    const int tpost = m >= 3 ? m - 1 : m;
#pragma unroll 1
    for (int t = m < 0 ? -1 : 0; t <= m; t++) {
      const int j = (t < m && (round & 1)) ? m - 1 - t : t;
      if (t >= 0) {
        drained(1 + st);
        wait(k_empty + 8 * st, ph);
        if (!dry) {
          mbar_expect_tx(k_full + 8 * st, A_TILE);
          tma_load_3d(sbase + A_K_OFF + st * A_TILE, &maps.k, k_full + 8 * st, 0, j * 128, h * 2);
        }
        if (++st == 2) { st = 0; ph ^= 1; }
      }
      if (pend_j >= 0) {
        drained(3);
        wait(v_empty + 8 * vs, vp);
        if (!dry) {
          mbar_expect_tx(v_full + 8 * vs, A_TILE);
          tma_load_3d(sbase + A_V_OFF + vs * A_TILE, &maps.v, v_full + 8 * vs, 0, pend_j * 128, pend_h * 2);
        }
        if (++vs == 2) { vs = 0; vp ^= 1; }
      }
      pend_j = j;
      pend_h = h;
      if (t == tpost && !last) {
        nitem = dry ? 1 : item_of(maps, round + 1);
        if (round == (dry ? 0 : 3) || blockIdx.x >= 128) {
          nitem = A_ITEMS;
          cnt_wait(CNT_PREP, dry ? 0 : 260);
          if (to_out) {
            cnt_wait(CNT_CTX, dry ? 0 : A_ITEMS);
            asm volatile("cp.async.bulk.prefetch.L2.global [%0], 4096;" ::"l"(maps.ssm_k + (size_t)conv_first(maps) * S_LEN));
            if (!dry)
              asm volatile("cp.async.bulk.prefetch.L2.global [%0], 4096;" ::"l"(g_kvT + (size_t)conv_first(maps) * S_LEN));
          }
        }
        const uint32_t qs = (round + 1) & 1;
        wait(q_empty + 8 * qs, (((round + 1) >> 1) & 1) ^ 1);
        if (round == 1 && after_qkv) wait(bar + B_QDONE, 0);
        if (round <= 0 && after_qkv) {
          if (!dry) { TD(2) }
          cnt_wait(CNT_KV + round + 1, dry ? 0 : 512);
          if (!dry) { TD(3) }
        }
        if (nitem >= A_ITEMS || (round < 0 && after_qkv && !dry)) {
          if (!dry) mbar_arrive(q_full + 8 * qs);
        } else {
          drained(qs);
          if (!dry) {
            mbar_expect_tx(q_full + 8 * qs, A_TILE);
            tma_load_3d_hint(sbase + A_Q_OFF + qs * A_TILE, &maps.q, q_full + 8 * qs, 0, item_m(nitem) * 128,
                             item_h(nitem) * 2, policy_evict_first());
          }
        }
      }
    }
    if (last) break;
    last = nitem >= A_ITEMS;
    m = last ? -1 : item_m(nitem);
    h = item_h(nitem);
  }
}

__device__ __forceinline__ uint32_t attn_consumer(const Maps& maps, uint32_t smem0, uint32_t sn,
                                                  float (&rest)[64], bool after_qkv) {
  PHASE_PROLOGUE
  const uint32_t q_full = bar + B_QFULL, q_empty = bar + B_QEMPTY;
  const uint32_t k_full = bar + B_KFULL, k_empty = bar + B_KEMPTY, v_full = bar + B_VFULL;
  float o[64], s[64];
  uint32_t p[32];
  float e[32];
  uint32_t dep = 0;
  constexpr int MIDJ = 5;
  float l0 = 0.f, l1 = 0.f, b0 = 0.f, b1 = 0.f;
  const int sched_own = 4 + wg, sched_other = 5 - wg;
  if (wg == 1) named_bar_arrive(4, 256);

  const uint32_t qd0 = (uint32_t)make_desc(sbase + A_Q_OFF + wg * 8192, 16, 0, 0);
  const uint32_t kd0 = (uint32_t)make_desc(sbase + A_K_OFF, 16, 0, 0);
  const uint32_t vd0 = (uint32_t)make_desc(sbase + A_V_OFF, 16384, 0, 0);
  constexpr uint64_t DHI = DESC_SW128 | ((uint64_t)(1024 >> 4) << 32);
  constexpr uint32_t DST = A_TILE >> 4;
  auto issue_qk = [&](uint32_t qd, uint32_t kd) {
#pragma unroll
    for (int kk = 0; kk < 8; kk++) {
      const uint32_t off = ((kk >> 2) * 16384 + (kk & 3) * 32) >> 4;
      wgmma_m64n128_ss(s, DHI | (qd + off), DHI | (kd + off), kk != 0);
    }
    wgmma_commit();
  };
  auto issue_pv = [&](uint32_t vd, bool accumulate, int nk) {
#pragma unroll
    for (int kk = 0; kk < 8; kk++) {
      if (kk < nk)
        wgmma_m64n128_rs_tb(o, p[4 * kk], p[4 * kk + 1], p[4 * kk + 2], p[4 * kk + 3], DHI | (vd + kk * 128),
                            accumulate || (kk != 0));
    }
    wgmma_commit();
  };
  auto exp_lo = [&](float& a0, float& a1) {
#pragma unroll
    for (int j = 0; j < 8; j++) {
      e[4 * j] = ex2(s[4 * j]);
      e[4 * j + 1] = ex2(s[4 * j + 1]);
      e[4 * j + 2] = ex2(s[4 * j + 2]);
      e[4 * j + 3] = ex2(s[4 * j + 3]);
      a0 += e[4 * j];
      a0 += e[4 * j + 1];
      a1 += e[4 * j + 2];
      a1 += e[4 * j + 3];
      if (j == MIDJ) dep = (__float_as_uint(a0) | __float_as_uint(a1)) & rt_zero;
    }
  };
  auto pack_lo = [&]() {
#pragma unroll
    for (int j = 0; j < 16; j++) p[j] = pack_bf16(e[2 * j], e[2 * j + 1]);
  };
  auto finish_p = [&](float& a0, float& a1) {
    pack_lo();
#pragma unroll
    for (int j = 8; j < 16; j++) {
      const float e0 = ex2(s[4 * j]), e1 = ex2(s[4 * j + 1]), e2 = ex2(s[4 * j + 2]), e3 = ex2(s[4 * j + 3]);
      a0 += e0;
      a0 += e1;
      a1 += e2;
      a1 += e3;
      p[2 * j] = pack_bf16(e0, e1);
      p[2 * j + 1] = pack_bf16(e2, e3);
      if (j == 8 + MIDJ) dep = __float_as_uint(a0) & rt_zero;
    }
  };
  auto quad_sum = [&](float t) {
    t += __shfl_xor_sync(0xffffffffu, t, 1);
    return t + __shfl_xor_sync(0xffffffffu, t, 2);
  };
  auto write_o = [&](float i0, float i1) {
    st_wait(bar, wg, sn - 1);
    const int st_row = warp * 16 + (lane & 7) + ((lane >> 3) & 1) * 8;
    const uint32_t so = sbase + A_O_OFF + wg * 16384 + st_row * 128;
#pragma unroll
    for (int j = 0; j < 16; j += 2)
      stmatrix_x4(so + (j >> 3) * 8192 + ((((j & 7) + (lane >> 4)) ^ (lane & 7)) << 4),
                  pack_bf16(o[4 * j] * i0, o[4 * j + 1] * i0), pack_bf16(o[4 * j + 2] * i1, o[4 * j + 3] * i1),
                  pack_bf16(o[4 * j + 4] * i0, o[4 * j + 5] * i0), pack_bf16(o[4 * j + 6] * i1, o[4 * j + 7] * i1));
  };
  auto store_o = [&](uint32_t r, int kind) {
    const uint32_t it = item_of(maps, r);
    st_post(bar, wg, wtid, sn, kind, (INPLACE & 1) || kind != ST_BOX2Q ? &maps.o : &maps.c[0], sbase + A_O_OFF + wg * 16384, item_h(it) * 128,
            item_m(it) * 128 + wg * 64, CNT_CTX + (r >> 1));
    sn++;
  };
  auto mask_half = [&](float* sh) {
    const int u = warp * 16 + (lane >> 2) - (lane & 3) * 2;
#pragma unroll
    for (int j = 0; j < 8; j++) {
      if (8 * j > u) sh[4 * j] = -INFINITY;
      if (8 * j + 1 > u) sh[4 * j + 1] = -INFINITY;
      if (8 * j - 8 > u) sh[4 * j + 2] = -INFINITY;
      if (8 * j - 7 > u) sh[4 * j + 3] = -INFINITY;
    }
  };
  ST(0)
  mbar_wait(q_full, 0);
  if (blockIdx.x >= 128) {
    mbar_arrive_if(bar + B_OFREE + 8 * wg, wtid == 0);
    return sn;
  }
  mbar_wait(k_full, 0);
  named_bar_sync(sched_own, 256);
  wgmma_fence();
  issue_qk(qd0, kd0);
  named_bar_arrive(sched_other, 256);
  fence_regs(rest);
#pragma unroll
  for (int i = 0; i < 64; i++) o[i] = rest[i] * Q_SCALE;
  fence_regs(o);
  wgmma_wait<0>();
  fence_regs(s);
  mbar_arrive_if(k_empty, wtid == 32);
  uint32_t g = 0;
  uint32_t rnd = 0;
  int rem = item_m(item_of(maps, 0));
  uint32_t first = 1;
  uint32_t fl = 0;
#define redo (fl & 1)
#define shifted (fl & 2)
  float d0 = 0.f, d1 = 0.f;
  float pi0 = 1.f, pi1 = 1.f;
  ST(1)
  for (;;) {
    if (shifted) {
#pragma unroll
      for (int j = 0; j < 16; j++) {
        s[4 * j] -= d0;
        s[4 * j + 1] -= d0;
        s[4 * j + 2] -= d1;
        s[4 * j + 3] -= d1;
      }
    }
    if (rem == 0 && !redo) {
      mbar_arrive_if(q_empty + 8 * (rnd & 1), wtid == 96);
      rnd++;
      if (wg == 0) mask_half(s);
      else mask_half(s + 32);
    }
    for (;;) {
      const bool kill = rem == 0 && wg == 0;
      const uint32_t kd = kd0 + ((g + 1) & 1) * DST, vd = vd0 + (g & 1) * DST;
      float a0 = 0.f, a1 = 0.f;
      exp_lo(a0, a1);
      fence_regs(e);
      const uint32_t kb = k_full + 8 * ((g + 1) & 1);
      const uint32_t kpar = ((((g + 1) >> 1) & 1) ^ (g == A_STEPS - 1 ? 1u : 0u)) | dep;
      if (!mbar_try(kb, kpar)) mbar_wait(kb, kpar | ((__float_as_uint(a0) | __float_as_uint(a1)) & rt_zero));
      wgmma_wait<0>();
      fence_regs(o);
      if (kill) {
        mbar_arrive_if(kb + (B_VEMPTY - B_KFULL), wtid == 64 && !redo && g > 0);
        fence_regs(e);
        pack_lo();
#pragma unroll
        for (int j = 16; j < 32; j++) asm volatile("mov.u32 %0, 0;" : "=r"(p[j]));
        goto check;
      }
#pragma unroll
      for (int i = 32; i < 64; i++) asm volatile("" : "+f"(s[i])::"memory");
      mbar_arrive_if(kb + (B_VEMPTY - B_KFULL), wtid == 64 && !redo && g > 0);
      finish_p(a0, a1);
      if (__any_sync(0xffffffffu, !(mbar_try(v_full + 8 * (g & 1), ((g >> 1) & 1) | dep) &
                                    mbar_try(q_full + 8 * (rnd & 1), ((rnd >> 1) & 1) | dep)) ||
                                      !(a0 + a1 < 1.0995116e12f) || !(fminf(a0, a1) > (first ? 9.094947e-13f : -1.f)))) {
      check:
        bool bad = !(a0 + a1 < 1.0995116e12f);
        if (first) bad |= !(fminf(quad_sum(a0), quad_sum(a1)) > 9.094947e-13f);
        if (!redo && __any_sync(0xffffffffu, bad)) {
          d0 = d1 = first ? -INFINITY : 0.f;
#pragma unroll
          for (int j = 0; j < 16; j++) {
            if (j < 8 || !kill) {
              d0 = fmaxf(d0, fmaxf(s[4 * j], s[4 * j + 1]));
              d1 = fmaxf(d1, fmaxf(s[4 * j + 2], s[4 * j + 3]));
            }
          }
#pragma unroll
          for (int x = 1; x <= 2; x++) {
            d0 = fmaxf(d0, __shfl_xor_sync(0xffffffffu, d0, x));
            d1 = fmaxf(d1, __shfl_xor_sync(0xffffffffu, d1, x));
          }
          b0 += d0;
          b1 += d1;
          if (!first) {
            const float al0 = ex2(-d0), al1 = ex2(-d1);
            l0 *= al0;
            l1 *= al1;
#pragma unroll
            for (int j = 0; j < 16; j++) {
              o[4 * j] *= al0;
              o[4 * j + 1] *= al0;
              o[4 * j + 2] *= al1;
              o[4 * j + 3] *= al1;
            }
          }
          fl = 3;
          break;
        }
        mbar_wait(v_full + 8 * (g & 1), (g >> 1) & 1);
        mbar_wait(q_full + 8 * (rnd & 1), (rnd >> 1) & 1);
      }
      named_bar_sync(sched_own, 256);
      if (g == A_STEPS - 1) {
        if (first) write_o(pi0, pi1);
        fence_regs(o);
        wgmma_fence();
        issue_pv(vd, !first, 8);
        named_bar_arrive(sched_other, 256);
        if (first) store_o(rnd - 2, ST_BOX2);
        pi0 = rcp(quad_sum(l0 + a0));
        pi1 = rcp(quad_sum(l1 + a1));
        goto done;
      }
      wgmma_fence();
      issue_qk(qd0 + (rnd & 1) * DST, kd);
      if (first) write_o(pi0, pi1);
      fence_regs(o);
      if (kill) {
        wgmma_fence();
        issue_pv(vd, !first, 4);
      } else {
        wgmma_fence();
        issue_pv(vd, !first, 8);
      }
      named_bar_arrive(sched_other, 256);
      fl &= 2;
      l0 += a0;
      l1 += a1;
      if (rem == 0 || first) {
        if (first && (g > 0 || after_qkv)) store_o(g ? rnd - (rem == 0 ? 2 : 1) : 2, g ? ST_BOX2 : ST_BOX2Q);
        first = rem == 0;
        if (first) {
          pi0 = rcp(quad_sum(l0));
          pi1 = rcp(quad_sum(l1));
          l0 = l1 = b0 = b1 = 0.f;
          fl = 0;
          rem = item_m(item_of(maps, rnd)) + 1;
        }
      }
      rem--;
      g++;
      wgmma_wait<1>();
      fence_regs(s);
      mbar_arrive_if(kb + (B_KEMPTY - B_KFULL), wtid == 32);
      ST(g + 1)
      if (rem == 0 || shifted) {
        d0 = b0;
        d1 = b1;
        break;
      }
    }
  }
done:
#undef redo
#undef shifted
  wgmma_wait<0>();
  fence_regs(o);
  write_o(pi0, pi1);
  store_o(3, ST_BOX2L);
  ST(35)
  return sn;
}

constexpr int O_STAGES = 5;
constexpr int O_STAGE_BYTES = 32768;
constexpr int O_Y_OFF = 5 * 32768;
constexpr int O_X_OFF = 6 * 32768;
constexpr int O_NK = HDIM / 64;

__device__ __forceinline__ uint32_t out_stage(uint32_t st) { return ((0x43120u >> (4 * st)) & 7) * O_STAGE_BYTES; }

__device__ __forceinline__ void out_producer(const Maps& maps, uint32_t sbase, bool after_attn, bool dry) {
  const uint32_t bar = sbase + BAR_OFF;
  const uint32_t rank = blockIdx.x & 1;
  const int m_tile = maps.id[blockIdx.x][2] & 15, n_tile = maps.id[blockIdx.x][2] >> 4;
  uint32_t stage = 0, phase = 0;
#pragma unroll 1
  for (int ki = 0; ki < (dry ? 1 : O_NK); ki++) {
    const int kt = (ki & 14) * 4 + ((A_ORDER >> ((ki >> 4) * 4)) & 3) * 2 + (ki & 1);
    const uint32_t fb = bar + B_OFULL + 8 * stage, eb = bar + B_OEMPTY + 8 * stage;
    const uint32_t sa = sbase + out_stage(stage);
    if (ki < O_STAGES) {
      constexpr uint32_t LASTB = B_KEMPTY | ((B_QEMPTY + 8) << 8) | ((B_KEMPTY + 8) << 16) | (B_VEMPTY << 24);
      if (ki > 0 && after_attn) mbar_wait_sleep(bar + ((LASTB >> (8 * ki - 8)) & 255), ki == 2);
      mbar_arrive_cluster_if(eb, 0, !dry);
      mbar_arrive_cluster_if(eb, 1, !dry);
    }
    if (ki == (dry ? 0 : 32)) cnt_wait(CNT_CTX + 1, dry ? 0 : A_ITEMS);
    if (!dry) {
      mbar_wait_sleep(eb, phase);
      mbar_expect_tx(fb, O_STAGE_BYTES);
      tma_load_2d_mc(sa + 16384 + rank * 8192, &maps.ob, fb, n_tile * 128 + rank * 64, kt * 64, (uint16_t)3);
      tma_load_2d(sa, &maps.oa, fb, kt * 64, m_tile * 128);
    }
    if (++stage == O_STAGES) { stage = 0; phase ^= 1; }
  }
  cnt_wait(CNT_Y2 + 1, after_attn && !dry ? 256 : 0);
  if (!dry) {
    TD(11)
    mbar_expect_tx(bar + B_OY2, 8192);
    for (int i = 0; i < 2; i++)
      tma_load_2d(sbase + O_Y_OFF + i * 16384 + 96 * 128, &maps.y2, bar + B_OY2, m_tile * 128 + i * 64,
                  n_tile * 128 + 96);
    mbar_wait_sleep(bar + B_OY, 0);
  }
}

__device__ __forceinline__ void out_side(const Maps& maps, uint32_t smem0, const float (&gv)[4]) {
  PHASE_PROLOGUE
  const int m_tile = maps.id[blockIdx.x][2] & 15, n_tile = maps.id[blockIdx.x][2] >> 4;
  if (__shfl_sync(0xffffffffu, warp, 0) == 0) {
    if (elect_one()) {
      mbar_expect_tx(bar + B_OY, 65536 - 8192);
      tma_load_2d(sbase + O_X_OFF, &maps.a[0], bar + B_OY, n_tile * 128, m_tile * 128);
      tma_load_2d(sbase + O_X_OFF + 16384, &maps.a[0], bar + B_OY, n_tile * 128 + 64, m_tile * 128);
      TD(10)
      cnt_wait(CNT_Y2, DM - 256);
      TD(7)
      tma_load_2d(sbase + O_Y_OFF, &maps.y, bar + B_OY, m_tile * 128, n_tile * 128);
      tma_load_2d(sbase + O_Y_OFF + 16384, &maps.y, bar + B_OY, m_tile * 128 + 64, n_tile * 128);
    }
  }
  mbar_wait_sleep(bar + B_OY, 0);
  const int st_row = warp * 16 + (lane & 7) + ((lane >> 3) & 1) * 8;
  const int mrow = (lane & 7) + ((lane >> 4) & 1) * 8;
  const int mchunk = warp * 2 + ((lane >> 3) & 1);
  const uint32_t xrow = sbase + O_X_OFF + st_row * 128;
  const uint32_t yrow = sbase + O_Y_OFF + mrow * 128 + ((mchunk ^ (lane & 7)) << 4);
  uint32_t y[6][4], x[6][4], om[4];
#pragma unroll
  for (int i = 0; i < 4; i++) om[i] = pack_bf16(1.0f - gv[i], 1.0f - gv[i]);
  auto xa = [&](int h, int i) { return xrow + h * 8192 + (i >> 2) * 16384 + ((((i & 3) * 2 + (lane >> 4)) ^ (lane & 7)) << 4); };
  auto load = [&](int r, int h, int i) {
    ldsm4t(y[r], yrow + h * 16384 + i * 2048);
    asm volatile("ldmatrix.sync.aligned.m8n8.x4.shared.b16 {%0, %1, %2, %3}, [%4];"
                 : "=r"(x[r][0]), "=r"(x[r][1]), "=r"(x[r][2]), "=r"(x[r][3])
                 : "r"(xa(h, i)));
  };
  auto store = [&](int r, int h, int i, uint32_t om0, uint32_t om1) {
    stmatrix_x4(xa(h, i), mul_bf2(om0, mul_bf2(x[r][0], y[r][0])), mul_bf2(om1, mul_bf2(x[r][1], y[r][1])),
                mul_bf2(om0, mul_bf2(x[r][2], y[r][2])), mul_bf2(om1, mul_bf2(x[r][3], y[r][3])));
  };
#pragma unroll 1
  for (int h = 0; h < 2; h++) {
#pragma unroll
    for (int i = 0; i < 6; i++) load(i, h, i);
#pragma unroll
    for (int i = 0; i < 6; i++) store(i, h, i, h ? om[2] : om[0], h ? om[3] : om[1]);
  }
  __syncwarp();
  mbar_arrive_if(bar + B_OY + 8, lane == 0);
  mbar_wait(bar + B_OY2, 0);
  if (wtid == 0) { TD(12) }
#pragma unroll
  for (int i = 0; i < 4; i++) load(i, i & 1, 6 + (i >> 1));
#pragma unroll
  for (int i = 0; i < 4; i++) store(i, i & 1, 6 + (i >> 1), om[2 * (i & 1)], om[2 * (i & 1) + 1]);
  __syncwarp();
  mbar_arrive_if(bar + B_OY + 16, lane == 0);
  if (wtid == 0) { TD(13) }
}

__device__ __forceinline__ uint32_t out_gemm(const Maps& maps, uint32_t smem0, uint32_t sn) {
  PHASE_PROLOGUE
  const int m_tile = maps.id[blockIdx.x][2] & 15, n_tile = maps.id[blockIdx.x][2] >> 4;
  float acc[2][64];
  undef_regs(acc[0]);
  undef_regs(acc[1]);
  uint32_t stage = 0, phase = 0, prev_stage = 0;
  GT(gti++)
  const float* gp = g_gate + m_tile * 128 + warp * 16 + (lane >> 2);
  const float gv[4] = {__ldcg(gp), __ldcg(gp + 8), __ldcg(gp + 64), __ldcg(gp + 72)};
  if (wg == 1) {
    out_side(maps, smem0, gv);
    return sn;
  }
#pragma unroll 1
  for (int kt = 0; kt < O_NK; kt++) {
    uint32_t da = (uint32_t)make_desc(sbase + out_stage(stage), 16, 0, 0);
    uint32_t db = (uint32_t)make_desc(sbase + out_stage(stage) + 16384, 8192, 0, 0);
    asm volatile("" : "+r"(da), "+r"(db));
    mbar_wait(bar + B_OFULL + 8 * stage, phase);
    GT(gti++)
    constexpr int OWAIT = 2;
    constexpr uint64_t DHI = DESC_SW128 | ((uint64_t)(1024 >> 4) << 32);
#pragma unroll
    for (int kk = 0; kk < 4; kk++) {
      wgmma_wait<OWAIT>();
      if (kk == OWAIT)
        mbar_arrive_cluster_if(bar + B_OEMPTY + 8 * prev_stage, wtid >> 6,
                               (wtid & 63) == 32 && kt > 0 && kt - 1 + O_STAGES < O_NK);
      wgmma_fence();
      wgmma_m64n128_ss_tb(acc[0], DHI | (da + kk * 2), DHI | (db + kk * 128), (kt | kk) != 0);
      wgmma_m64n128_ss_tb(acc[1], DHI | (da + 512 + kk * 2), DHI | (db + kk * 128), (kt | kk) != 0);
      wgmma_commit();
    }
    prev_stage = stage;
    if (++stage == O_STAGES) { stage = 0; phase ^= 1; }
  }
  if (tid == 0) { TD(14) }
  st_wait(bar, wg, sn - 1);
  const int st_row = warp * 16 + (lane & 7) + ((lane >> 3) & 1) * 8;
  const uint32_t rowa = sbase + O_X_OFF + st_row * 128;
  wgmma_wait<0>();
  fence_regs(acc[0]);
  fence_regs(acc[1]);
  GT(gti++)
  uint32_t gg[4];
#pragma unroll
  for (int i = 0; i < 4; i++) gg[i] = pack_bf16(gv[i], gv[i]);
#pragma unroll
  for (int i = 0; i < 16; i++) {
    const int h = i & 1, j = i & 14;
    if (i % 12 == 0) mbar_wait(bar + B_OY + 8 + 8 * (i / 12), 0);
    const uint32_t addr = rowa + h * 8192 + (j >> 3) * 16384 + ((((j & 7) + (lane >> 4)) ^ (st_row & 7)) << 4);
    uint32_t b0, b1, b2, b3;
    asm volatile("ldmatrix.sync.aligned.m8n8.x4.shared.b16 {%0, %1, %2, %3}, [%4];"
                 : "=r"(b0), "=r"(b1), "=r"(b2), "=r"(b3)
                 : "r"(addr));
    const float* a = acc[h] + 4 * j;
    const uint32_t gg0 = gg[2 * h], gg1 = gg[2 * h + 1];
    stmatrix_x4(addr, add_bf2(mul_bf2(gg0, pack_bf16(a[0], a[1])), b0),
                add_bf2(mul_bf2(gg1, pack_bf16(a[2], a[3])), b1), add_bf2(mul_bf2(gg0, pack_bf16(a[4], a[5])), b2),
                add_bf2(mul_bf2(gg1, pack_bf16(a[6], a[7])), b3));
    if (i == 7) st_post(bar, wg, wtid, sn, ST_BOX1, &maps.oc, sbase + O_X_OFF, n_tile * 128, m_tile * 128, -1);
  }
  fence_proxy_async();
  named_bar_sync(1, 128);
  if (__shfl_sync(0xffffffffu, warp, 0) == 0) {
    if (elect_one()) {
      tma_store_2d(&maps.oc, sbase + O_X_OFF + 16384, n_tile * 128 + 64, m_tile * 128);
      tma_store_commit();
    }
  }
  GT(gti++)
  return sn + 1;
}

__device__ __noinline__ void leave_kernel(int mask) {
  if (!(mask & 4)) return;
  if (atomicAdd(g_cnt + CNT_DONE * 32, 1u) == 2 * gridDim.x - 1) {
    for (int i = 0; i < CNT_N; i++) g_cnt[i * 32] = 0;
  }
}

__device__ __noinline__ void side_jobs(const Maps& maps, uint32_t sbase) {
  const int w12 = __shfl_sync(0xffffffffu, threadIdx.x >> 5, 0);
  gate_rows(maps, sbase, (blockIdx.x - 128) * 12 + w12, w12, threadIdx.x & 31);
  fence_proxy_async();
  __syncthreads();
  if (threadIdx.x == 320) cnt_signal_release(CNT_PREP, 1);
}

__global__ void __launch_bounds__(384, 1) fused_kernel(int mask, const __grid_constant__ Maps maps) {
  extern __shared__ __align__(1024) uint8_t smem_raw[];
  {
    const uint32_t sbase = __shfl_sync(0xffffffffu, smem_u32(smem_raw), 0);
    const uint32_t bar = sbase + BAR_OFF;
    const int tid = threadIdx.x;
    const bool do_qkv = (mask & 1) && blockIdx.x < 128;
    TL(0, 0)
    if (__shfl_sync(0xffffffffu, tid >> 5, 0) == 1 && do_qkv) {
      if (elect_one()) {
        for (int i = 0; i < G_STAGES; i++) mbar_init(bar + B_GFULL + 8 * i, 1);
        fence_barrier_init();
        qkv_producer(maps, sbase, true);
      }
    }
    if (tid == 0) {
      for (int i = 0; i < G_STAGES; i++) {
        mbar_init(bar + B_GEMPTY + 8 * i, 2);
        mbar_init(bar + B_SFULL + 8 * i, 4);
        mbar_init(bar + B_SFREE + 8 * i, 1);
      }
      for (int i = 0; i < 2; i++) {
        mbar_init(bar + B_OFREE + 8 * i, 1);
        mbar_init(bar + B_QFULL + 8 * i, 1);
        mbar_init(bar + B_QEMPTY + 8 * i, 2);
        mbar_init(bar + B_KFULL + 8 * i, 1);
        mbar_init(bar + B_KEMPTY + 8 * i, 2);
        mbar_init(bar + B_VFULL + 8 * i, 1);
        mbar_init(bar + B_VEMPTY + 8 * i, 2);
      }
      for (int i = 0; i < O_STAGES; i++) {
        mbar_init(bar + B_OFULL + 8 * i, 1);
        mbar_init(bar + B_OEMPTY + 8 * i, 2);
      }
      mbar_init(bar + B_OY, 1);
      mbar_init(bar + B_OY2, 1);
      mbar_init(bar + B_OY + 8, 4);
      mbar_init(bar + B_OY + 16, 4);
      mbar_init(bar + B_QDONE, 2);
      for (int i = 0; i < 8; i++) mbar_init(bar + B_CFULL + 8 * i, 1);
      for (int i = 0; i < CNT_N; i++) asm volatile("st.shared.u32 [%0], 0;" ::"r"(bar + B_PEND + 4 * i) : "memory");
      fence_barrier_init();
    }
    __syncthreads();
    asm volatile("barrier.cluster.arrive.relaxed.aligned;" ::: "memory");
    if ((mask & 1) && blockIdx.x >= 128) side_jobs(maps, sbase);
  }
  uint32_t smem0 = smem_u32(smem_raw);
  PHASE_PROLOGUE
  const bool do_qkv = (mask & 1) && blockIdx.x < 128, do_out = (mask & 4) && blockIdx.x < 128;
  TL(0, 1)

  if (wg != 2) {
    reg_alloc<232>();
    uint32_t sn = 0;
    float o[64];
    if (do_qkv) {
      sn = qkv_consumer(maps, smem_u32(smem_raw), mask & 2, o);
    } else {
      undef_regs(o);
    }
    TL(0, 2) TL(1, 0) TL(1, 1)
    asm volatile("barrier.cluster.wait.acquire.aligned;" ::: "memory");
    if (mask & 2) {
      sn = attn_consumer(maps, smem_u32(smem_raw), sn, o, mask & 1);
      TL(2, 0)
      if ((mask & 4) && blockIdx.x < 128 && __shfl_sync(0xffffffffu, threadIdx.x, 0) < 128) {
        named_bar_arrive(3, 256);
      } else {
        named_bar_sync(3, 256);
        const uint32_t b2 = blockIdx.x * 2 + (threadIdx.x >> 7);
        const bool fused = mask & 4, mainc = blockIdx.x < 128;
        const uint32_t first = __shfl_sync(0xffffffffu, !fused ? b2 : mainc ? conv_first(maps) : (b2 - 256) * 128, 0);
        conv_consumer(maps, smem_u32(smem_raw), first, !fused ? 264 : mainc ? 16 : 1,
                      !fused ? DM : mainc ? (first | 127) + 1 : first + C_SIDE);
      }
      TL(1, 2) TL(2, 1) TL(2, 2)
    }
    TL(3, 0) TL(3, 1)
    if ((mask & 4) && blockIdx.x < 128) sn = out_gemm(maps, smem_u32(smem_raw), sn);
    {
      uint32_t smem0 = smem_u32(smem_raw);
      PHASE_PROLOGUE
      st_wait(bar, wg, sn - 2);
      st_post(bar, wg, wtid, sn, ST_END, nullptr, 0, 0, 0, -1);
      tma_store_wait_read<0>();
    }
  } else {
    reg_dealloc<40>();
    asm volatile("barrier.cluster.wait.acquire.aligned;" ::: "memory");
    const int w = __shfl_sync(0xffffffffu, tid >> 5, 0) - 8;
    if (w < 2) {
      if (do_qkv) prep_agent(maps, sbase, w, lane);
      if (elect_one()) store_agent(bar, w);
      TL2(3, 2)
    } else {
      if (elect_one()) {
        const bool dry = w == 2;
        if (do_qkv && !dry) qkv_producer(maps, sbase, false);
        if (mask & 2) attn_producer(maps, sbase, do_qkv, do_out, dry);
        if (do_out) out_producer(maps, sbase, mask & 2, dry);
        if (dry) { TD(5) }
      }
      __syncwarp();
      if (w == 2) publisher(bar, tid & 31, !(mask & 2) ? 2 : do_out ? 3 : 4);
      if ((tid & 31) == 0) leave_kernel(mask);
    }
  }
}

typedef CUresult (*PFN_tmapEncode)(CUtensorMap*, CUtensorMapDataType, cuuint32_t, void*, const cuuint64_t*,
                                   const cuuint64_t*, const cuuint32_t*, const cuuint32_t*, CUtensorMapInterleave,
                                   CUtensorMapSwizzle, CUtensorMapL2promotion, CUtensorMapFloatOOBfill);
static PFN_tmapEncode s_encode = nullptr;

static void make_map_2d(CUtensorMap* m, const void* ptr, int rows, int cols, int box_rows) {
  cuuint64_t dims[2] = {(cuuint64_t)cols, (cuuint64_t)rows};
  cuuint64_t strides[1] = {(cuuint64_t)cols * 2};
  cuuint32_t box[2] = {64, (cuuint32_t)box_rows};
  cuuint32_t es[2] = {1, 1};
  s_encode(m, CU_TENSOR_MAP_DATA_TYPE_BFLOAT16, 2, const_cast<void*>(ptr), dims, strides, box, es,
           CU_TENSOR_MAP_INTERLEAVE_NONE, CU_TENSOR_MAP_SWIZZLE_128B, CU_TENSOR_MAP_L2_PROMOTION_L2_256B,
           CU_TENSOR_MAP_FLOAT_OOB_FILL_NONE);
}
static void make_map_3d(CUtensorMap* m, const void* ptr, int rows, int cols, int box_rows, int box_chunks) {
  cuuint64_t dims[3] = {64, (cuuint64_t)rows, (cuuint64_t)(cols / 64)};
  cuuint64_t strides[2] = {(cuuint64_t)cols * 2, 128};
  cuuint32_t box[3] = {64, (cuuint32_t)box_rows, (cuuint32_t)box_chunks};
  cuuint32_t es[3] = {1, 1, 1};
  s_encode(m, CU_TENSOR_MAP_DATA_TYPE_BFLOAT16, 3, const_cast<void*>(ptr), dims, strides, box, es,
           CU_TENSOR_MAP_INTERLEAVE_NONE, CU_TENSOR_MAP_SWIZZLE_128B, CU_TENSOR_MAP_L2_PROMOTION_L2_256B,
           CU_TENSOR_MAP_FLOAT_OOB_FILL_NONE);
}

static cudaLaunchConfig_t fused_cfg(cudaLaunchAttribute* at) {
  cudaLaunchConfig_t cfg = {};
  cfg.gridDim = dim3(132);
  cfg.blockDim = dim3(384);
  cfg.dynamicSmemBytes = SMEM_BYTES;
  cfg.stream = cudaStreamPerThread;
  at[0].id = cudaLaunchAttributeClusterDimension;
  at[0].val.clusterDim.x = 2;
  at[0].val.clusterDim.y = 1;
  at[0].val.clusterDim.z = 1;
  cfg.attrs = at;
  cfg.numAttrs = 1;
  return cfg;
}

extern "C" void kernel_launch(void* const* d_in, const int* in_sizes, int n_in, void* d_out, int out_size) {
  const bf16* x = (const bf16*)d_in[0];
  const bf16* ckv = (const bf16*)d_in[1];
  const bf16* wq = (const bf16*)d_in[2];
  const bf16* wuk = (const bf16*)d_in[3];
  const bf16* wuv = (const bf16*)d_in[4];
  const bf16* wo = (const bf16*)d_in[5];
  const bf16* bk = (const bf16*)d_in[7];
  const bf16* bv = (const bf16*)d_in[8];
  const bf16* shift_k = (const bf16*)d_in[9];
  const bf16* ssm_k = (const bf16*)d_in[10];
  const bf16* ssm_D = (const bf16*)d_in[11];
  const bf16* gate_w = (const bf16*)d_in[12];
  bf16* out = (bf16*)d_out;

  static void *pq = nullptr, *pk = nullptr, *pv = nullptr, *pctx = nullptr, *pb = nullptr;
  static int max_clusters = 0;
  if (!s_encode) {
    void* fn = nullptr;
    cudaDriverEntryPointQueryResult qres;
    cudaGetDriverEntryPoint("cuTensorMapEncodeTiled", &fn, cudaEnableDefault, &qres);
    s_encode = (PFN_tmapEncode)fn;
    cudaGetSymbolAddress(&pq, g_q);
    cudaGetSymbolAddress(&pk, g_k);
    cudaGetSymbolAddress(&pv, g_v);
    cudaGetSymbolAddress(&pctx, g_ctx);
    cudaGetSymbolAddress(&pb, g_y2T);
    cudaFuncSetAttribute(fused_kernel, cudaFuncAttributeMaxDynamicSharedMemorySize, SMEM_BYTES);
    cudaLaunchAttribute at[1];
    cudaLaunchConfig_t cfg = fused_cfg(at);
    if (cudaOccupancyMaxActiveClusters(&max_clusters, fused_kernel, &cfg) != cudaSuccess) max_clusters = 0;
  }

  Maps all = {};
  make_map_2d(&all.a[0], x, S_LEN, DM, 128);
  make_map_2d(&all.a[1], ckv, S_LEN, DC, 128);
  make_map_3d(&all.b[0], wq, DM, HDIM, 64, 4);
  make_map_3d(&all.b[1], wuk, DC, HDIM, 64, 4);
  make_map_3d(&all.b[2], wuv, DC, HDIM, 64, 4);
  make_map_2d(&all.c[0], pq, S_LEN, HDIM, 64);
  make_map_2d(&all.c[1], pk, S_LEN, HDIM, 64);
  make_map_2d(&all.c[2], pv, S_LEN, HDIM, 64);
  make_map_3d(&all.q, pq, S_LEN, HDIM, 128, 2);
  make_map_3d(&all.k, pk, S_LEN, HDIM, 128, 2);
  make_map_3d(&all.v, pv, S_LEN, HDIM, 128, 2);
  make_map_2d(&all.o, pctx, S_LEN, HDIM, 64);
  all.ssm_k = ssm_k;
  all.ssm_D = ssm_D;
  make_map_2d(&all.oa, pctx, S_LEN, HDIM, 128);
  make_map_2d(&all.ob, wo, HDIM, DM, 64);
  make_map_2d(&all.oc, out, S_LEN, DM, 128);
  make_map_2d(&all.y, pb, DM, S_LEN, 96);
  make_map_2d(&all.y2, pb, DM, S_LEN, 32);

  make_map_2d(&all.bk, bk, S_LEN, DM, 35);
  make_map_2d(&all.bv, bv, S_LEN, DM, 32);
  for (int b = 0; b < 128; b++) {
    const int c = b >> 1, r = b & 1;
    const int G = c < 4 ? 0 : c < 36 ? (c - 4) % 8 : 1 + (c - 36) % 7;
    const int i = c < 4 ? 4 + c : c < 36 ? (c - 4) / 8 : 4 + (c - 36) / 7;
    all.id[b][0] = r + 2 * (i & 1) + 4 * (G & 3) + 16 * (i >> 1) + 64 * (G >> 2);
    all.id[b][1] = r + 2 * i + 16 * G;
    all.id[b][2] = r + 2 * G + 16 * i;
  }
  all.shift_k = shift_k;
  all.x = x;
  all.gate_w = gate_w;
  cudaLaunchAttribute at[1];
  cudaLaunchConfig_t cfg = fused_cfg(at);
  if (max_clusters >= 66) {
    cudaLaunchKernelEx(&cfg, fused_kernel, 7, all);
  } else {
    for (int m = 1; m <= 4; m <<= 1) cudaLaunchKernelEx(&cfg, fused_kernel, m, all);
  }
}
```

```cpp
#include <cuda_runtime.h>
#include <cuda_bf16.h>
#include <cuda.h>
#include <stdint.h>

typedef __nv_bfloat16 bf16;
#define INPLACE 3

constexpr int S_LEN = 2048;
constexpr int DM = 1024;
constexpr int NH = 32;
constexpr int HD = 128;
constexpr int DC = 512;
constexpr int HDIM = NH * HD;

__device__ __align__(1024) bf16 g_q[S_LEN * HDIM];
__device__ __align__(1024) bf16 g_k[S_LEN * HDIM];
__device__ __align__(1024) bf16 g_v[S_LEN * HDIM];
#define g_ctx g_q
__device__ __align__(1024) bf16 g_kvT[DM * S_LEN];
#define g_y2T g_kvT
__device__ __align__(1024) float g_gate[S_LEN];
enum { CNT_KV = 0, CNT_PREP = CNT_KV + 2, CNT_CTX, CNT_Y2 = CNT_CTX + 2, CNT_DONE = CNT_Y2 + 2, CNT_N };
__device__ unsigned int g_cnt[CNT_N * 32];

#define TL(k, i)
#define TL2(k, i)
#define TD(i)
#define CLK_DECL
#define CLK_SAMPLE
#define CLK_END
#define CT(i)
#define GT(i)
#define GS(i)
#define GA(i)
#define ST(i)

__device__ __forceinline__ uint32_t smem_u32(const void* p) { return (uint32_t)__cvta_generic_to_shared(p); }

__device__ __forceinline__ void mbar_init(uint32_t bar, uint32_t count) {
  asm volatile("mbarrier.init.shared::cta.b64 [%0], %1;" ::"r"(bar), "r"(count));
}
__device__ __forceinline__ void mbar_expect_tx(uint32_t bar, uint32_t bytes) {
  asm volatile("mbarrier.arrive.expect_tx.shared::cta.b64 _, [%0], %1;" ::"r"(bar), "r"(bytes) : "memory");
}
__device__ __forceinline__ void mbar_arrive(uint32_t bar) {
  asm volatile("mbarrier.arrive.shared::cta.b64 _, [%0];" ::"r"(bar) : "memory");
}
__device__ __forceinline__ void mbar_wait(uint32_t bar, uint32_t parity) {
  uint32_t done;
  uint32_t spins = 0;
  do {
    asm volatile(
        "{\n.reg .pred p;\n"
        "mbarrier.try_wait.parity.shared::cta.b64 p, [%1], %2;\n"
        "selp.u32 %0, 1, 0, p;\n}\n"
        : "=r"(done)
        : "r"(bar), "r"(parity)
        : "memory");
    if (++spins > (1u << 22)) break;
  } while (!done);
}
__device__ __forceinline__ bool mbar_try(uint32_t bar, uint32_t parity) {
  uint32_t done;
  asm volatile(
      "{\n.reg .pred p;\n"
      "mbarrier.try_wait.parity.shared::cta.b64 p, [%1], %2;\n"
      "selp.u32 %0, 1, 0, p;\n}\n"
      : "=r"(done)
      : "r"(bar), "r"(parity)
      : "memory");
  return done != 0;
}
__device__ __forceinline__ bool elect_one() {
  uint32_t pred;
  asm volatile("{\n.reg .pred p;\nelect.sync _|p, 0xffffffff;\nselp.u32 %0, 1, 0, p;\n}\n" : "=r"(pred));
  return pred != 0;
}
__device__ __forceinline__ void mbar_arrive_if(uint32_t bar, bool pred) {
  asm volatile(
      "{\n.reg .pred p;\nsetp.ne.b32 p, %1, 0;\n"
      "@p mbarrier.arrive.shared::cta.b64 _, [%0];\n}\n" ::"r"(bar),
      "r"((uint32_t)pred)
      : "memory");
}
__device__ __forceinline__ void mbar_wait_sleep(uint32_t bar, uint32_t parity) {
  uint32_t done;
  uint32_t spins = 0;
  do {
    asm volatile(
        "{\n.reg .pred p;\n"
        "mbarrier.try_wait.parity.shared::cta.b64 p, [%1], %2, %3;\n"
        "selp.u32 %0, 1, 0, p;\n}\n"
        : "=r"(done)
        : "r"(bar), "r"(parity), "r"(20000u)
        : "memory");
    if (++spins > (1u << 16)) break;
  } while (!done);
}
__device__ __forceinline__ void fence_barrier_init() {
  asm volatile("fence.mbarrier_init.release.cluster;" ::: "memory");
}
__device__ __forceinline__ void fence_proxy_async() {
  asm volatile("fence.proxy.async.shared::cta;" ::: "memory");
}
__device__ __forceinline__ void named_bar_sync(int id, int nthreads) {
  asm volatile("bar.sync %0, %1;" ::"r"(id), "r"(nthreads) : "memory");
}
__device__ __forceinline__ void named_bar_arrive(int id, int nthreads) {
  asm volatile("bar.arrive %0, %1;" ::"r"(id), "r"(nthreads) : "memory");
}
__device__ __forceinline__ void tma_load_2d(uint32_t dst, const CUtensorMap* m, uint32_t bar, int c0, int c1) {
  asm volatile(
      "cp.async.bulk.tensor.2d.shared::cluster.global.mbarrier::complete_tx::bytes [%0], [%1, {%3, %4}], [%2];" ::"r"(dst),
      "l"(reinterpret_cast<uint64_t>(m)), "r"(bar), "r"(c0), "r"(c1)
      : "memory");
}
__device__ __forceinline__ void tma_load_3d(uint32_t dst, const CUtensorMap* m, uint32_t bar, int c0, int c1, int c2) {
  asm volatile(
      "cp.async.bulk.tensor.3d.shared::cluster.global.mbarrier::complete_tx::bytes [%0], [%1, {%3, %4, %5}], [%2];" ::"r"(dst),
      "l"(reinterpret_cast<uint64_t>(m)), "r"(bar), "r"(c0), "r"(c1), "r"(c2)
      : "memory");
}
__device__ __forceinline__ void tma_store_2d(const CUtensorMap* m, uint32_t src, int c0, int c1) {
  asm volatile("cp.async.bulk.tensor.2d.global.shared::cta.bulk_group [%0, {%2, %3}], [%1];" ::"l"(
                   reinterpret_cast<uint64_t>(m)),
               "r"(src), "r"(c0), "r"(c1)
               : "memory");
}
__device__ __forceinline__ void tma_load_4d(uint32_t dst, const CUtensorMap* m, uint32_t bar, int c0, int tile) {
  asm volatile(
      "cp.async.bulk.tensor.4d.shared::cluster.global.mbarrier::complete_tx::bytes [%0], [%1, {%3, %4, %4, %5}], [%2];" ::"r"(dst),
      "l"(reinterpret_cast<uint64_t>(m)), "r"(bar), "r"(c0), "r"(0), "r"(2 * tile)
      : "memory");
}
__device__ __forceinline__ void tma_store_4d(const CUtensorMap* m, uint32_t src, int c0, int c2, int group) {
  asm volatile("cp.async.bulk.tensor.4d.global.shared::cta.bulk_group [%0, {%2, %3, %4, %5}], [%1];" ::"l"(
                   reinterpret_cast<uint64_t>(m)),
               "r"(src), "r"(c0), "r"(0), "r"(c2), "r"(group)
               : "memory");
}
__device__ __forceinline__ void bulk_load(uint32_t dst, const void* src, uint32_t bytes, uint32_t bar) {
  asm volatile("cp.async.bulk.shared::cluster.global.mbarrier::complete_tx::bytes [%0], [%1], %2, [%3];" ::"r"(dst),
               "l"(src), "r"(bytes), "r"(bar)
               : "memory");
}
__device__ __forceinline__ void tma_load_2d_mc(uint32_t dst, const CUtensorMap* m, uint32_t bar, int c0, int c1,
                                               uint16_t mask) {
  asm volatile(
      "cp.async.bulk.tensor.2d.shared::cluster.global.mbarrier::complete_tx::bytes.multicast::cluster [%0], [%1, {%3, "
      "%4}], [%2], %5;" ::"r"(dst),
      "l"(reinterpret_cast<uint64_t>(m)), "r"(bar), "r"(c0), "r"(c1), "h"(mask)
      : "memory");
}
__device__ __forceinline__ void mbar_arrive_cluster_if(uint32_t bar, uint32_t cta, bool pred) {
  asm volatile(
      "{\n.reg .b32 ra;\n.reg .pred p;\nsetp.ne.b32 p, %2, 0;\n"
      "mapa.shared::cluster.u32 ra, %0, %1;\n"
      "@p mbarrier.arrive.shared::cluster.b64 _, [ra];\n}\n" ::"r"(bar),
      "r"(cta), "r"((uint32_t)pred)
      : "memory");
}
__device__ __forceinline__ uint64_t policy_evict_first() {
  uint64_t pol;
  asm volatile("createpolicy.fractional.L2::evict_first.b64 %0, 1.0;" : "=l"(pol));
  return pol;
}
__device__ __forceinline__ void tma_load_2d_hint(uint32_t dst, const CUtensorMap* m, uint32_t bar, int c0, int c1,
                                                 uint64_t pol) {
  asm volatile(
      "cp.async.bulk.tensor.2d.shared::cluster.global.mbarrier::complete_tx::bytes.L2::cache_hint [%0], [%1, {%3, %4}], "
      "[%2], %5;" ::"r"(dst),
      "l"(reinterpret_cast<uint64_t>(m)), "r"(bar), "r"(c0), "r"(c1), "l"(pol)
      : "memory");
}
__device__ __forceinline__ void tma_load_3d_hint(uint32_t dst, const CUtensorMap* m, uint32_t bar, int c0, int c1,
                                                 int c2, uint64_t pol) {
  asm volatile(
      "cp.async.bulk.tensor.3d.shared::cluster.global.mbarrier::complete_tx::bytes.L2::cache_hint [%0], [%1, {%3, %4, "
      "%5}], [%2], %6;" ::"r"(dst),
      "l"(reinterpret_cast<uint64_t>(m)), "r"(bar), "r"(c0), "r"(c1), "r"(c2), "l"(pol)
      : "memory");
}
__device__ __forceinline__ void bulk_load_hint(uint32_t dst, const void* src, uint32_t bytes, uint32_t bar, uint64_t pol) {
  asm volatile(
      "cp.async.bulk.shared::cluster.global.mbarrier::complete_tx::bytes.L2::cache_hint [%0], [%1], %2, [%3], %4;" ::"r"(dst),
      "l"(src), "r"(bytes), "r"(bar), "l"(pol)
      : "memory");
}
__device__ __forceinline__ void cnt_signal_release(int which, uint32_t n) {
  asm volatile("red.release.gpu.global.add.u32 [%0], %1;" ::"l"(g_cnt + which * 32), "r"(n) : "memory");
}
__device__ __forceinline__ void cnt_wait(int which, uint32_t target) {
  uint32_t v, spins = 0;
  while (true) {
    asm volatile("ld.acquire.gpu.global.u32 %0, [%1];" : "=r"(v) : "l"(g_cnt + which * 32) : "memory");
    if (v >= target || ++spins > (1u << 18)) break;
    __nanosleep(64);
  }
  asm volatile("fence.proxy.async.global;" ::: "memory");
}
__device__ __forceinline__ void tma_store_commit() { asm volatile("cp.async.bulk.commit_group;" ::: "memory"); }
template <int N>
__device__ __forceinline__ void tma_store_wait_read() {
  asm volatile("cp.async.bulk.wait_group.read %0;" ::"n"(N) : "memory");
}
template <int N>
__device__ __forceinline__ void tma_store_wait() {
  asm volatile("cp.async.bulk.wait_group %0;" ::"n"(N) : "memory");
}
__device__ __forceinline__ void wgmma_fence() { asm volatile("wgmma.fence.sync.aligned;" ::: "memory"); }
__device__ __forceinline__ void wgmma_commit() { asm volatile("wgmma.commit_group.sync.aligned;" ::: "memory"); }
template <int N>
__device__ __forceinline__ void wgmma_wait() {
  asm volatile("wgmma.wait_group.sync.aligned %0;" ::"n"(N) : "memory");
}
template <int R>
__device__ __forceinline__ void reg_alloc() { asm volatile("setmaxnreg.inc.sync.aligned.u32 %0;" ::"n"(R)); }
template <int R>
__device__ __forceinline__ void reg_dealloc() { asm volatile("setmaxnreg.dec.sync.aligned.u32 %0;" ::"n"(R)); }

__device__ __forceinline__ void stmatrix_x4(uint32_t addr, uint32_t r0, uint32_t r1, uint32_t r2, uint32_t r3) {
  asm volatile("stmatrix.sync.aligned.m8n8.x4.shared.b16 [%0], {%1, %2, %3, %4};" ::"r"(addr), "r"(r0), "r"(r1),
               "r"(r2), "r"(r3)
               : "memory");
}
__device__ __forceinline__ uint32_t pack_bf16(float lo, float hi) {
  uint32_t r;
  asm("cvt.rn.bf16x2.f32 %0, %1, %2;" : "=r"(r) : "f"(hi), "f"(lo));
  return r;
}
__device__ __forceinline__ float bf16_round(float x) { return __bfloat162float(__float2bfloat16_rn(x)); }
__device__ __forceinline__ float bf_lo(uint32_t v) { return __uint_as_float(v << 16); }
__device__ __forceinline__ float bf_hi(uint32_t v) { return __uint_as_float(v & 0xffff0000u); }
__device__ __forceinline__ uint4 lds128(uint32_t a) {
  uint4 v;
  asm volatile("ld.shared.v4.u32 {%0, %1, %2, %3}, [%4];" : "=r"(v.x), "=r"(v.y), "=r"(v.z), "=r"(v.w) : "r"(a));
  return v;
}
__device__ __forceinline__ void sts128(uint32_t a, uint4 v) {
  asm volatile("st.shared.v4.u32 [%0], {%1, %2, %3, %4};" ::"r"(a), "r"(v.x), "r"(v.y), "r"(v.z), "r"(v.w) : "memory");
}
__device__ __forceinline__ uint32_t mul_bf2(uint32_t a, uint32_t b) {
  uint32_t r;
  asm("mul.rn.bf16x2 %0, %1, %2;" : "=r"(r) : "r"(a), "r"(b));
  return r;
}
__device__ __forceinline__ uint32_t add_bf2(uint32_t a, uint32_t b) {
  uint32_t r;
  asm("add.rn.bf16x2 %0, %1, %2;" : "=r"(r) : "r"(a), "r"(b));
  return r;
}
__device__ __forceinline__ float ex2(float x) {
  float y;
  asm("ex2.approx.ftz.f32 %0, %1;" : "=f"(y) : "f"(x));
  return y;
}
__device__ __forceinline__ float rcp(float x) {
  float y;
  asm("rcp.approx.ftz.f32 %0, %1;" : "=f"(y) : "f"(x));
  return y;
}
template <int N>
__device__ __forceinline__ void fence_regs(float (&r)[N]) {
#pragma unroll
  for (int i = 0; i < N; i++) asm volatile("" : "+f"(r[i])::"memory");
}

template <int N>
__device__ __forceinline__ void undef_regs(float (&r)[N]) {
#pragma unroll
  for (int i = 0; i < N; i++) asm volatile("" : "=f"(r[i]));
}
template <int N>
__device__ __forceinline__ void fence_regs_u(uint32_t (&r)[N]) {
#pragma unroll
  for (int i = 0; i < N; i++) asm volatile("" : "+r"(r[i])::"memory");
}

constexpr uint64_t DESC_SW128 = 1ull << 62;
__device__ __forceinline__ uint64_t make_desc(uint32_t addr, uint32_t lbo_bytes, uint32_t sbo_bytes, uint64_t swz) {
  return (uint64_t)((addr & 0x3FFFF) >> 4) | ((uint64_t)((lbo_bytes & 0x3FFFF) >> 4) << 16) |
         ((uint64_t)((sbo_bytes & 0x3FFFF) >> 4) << 32) | swz;
}

__device__ __forceinline__ uint64_t desc_add(uint64_t d, uint32_t off16) {
  return (d & 0xFFFFFFFF00000000ull) | (uint64_t)((uint32_t)d + off16);
}

__device__ __forceinline__ void wgmma_m64n256_ss_tb(float (&d)[128], uint64_t da, uint64_t db, int sd) {
  asm volatile(
    "{\n.reg .pred p;\nsetp.ne.b32 p, %130, 0;\n"
    "wgmma.mma_async.sync.aligned.m64n256k16.f32.bf16.bf16 "
    "{%0, %1, %2, %3, %4, %5, %6, %7, %8, %9, %10, %11, %12, %13, %14, %15, %16, %17, %18, %19, %20, %21, %22, %23, %24, %25, %26, %27, %28, %29, %30, %31, %32, %33, %34, %35, %36, %37, %38, %39, %40, %41, %42, %43, %44, %45, %46, %47, %48, %49, %50, %51, %52, %53, %54, %55, %56, %57, %58, %59, %60, %61, %62, %63, %64, %65, %66, %67, %68, %69, %70, %71, %72, %73, %74, %75, %76, %77, %78, %79, %80, %81, %82, %83, %84, %85, %86, %87, %88, %89, %90, %91, %92, %93, %94, %95, %96, %97, %98, %99, %100, %101, %102, %103, %104, %105, %106, %107, %108, %109, %110, %111, %112, %113, %114, %115, %116, %117, %118, %119, %120, %121, %122, %123, %124, %125, %126, %127}, %128, %129, p, 1, 1, 0, 1;\n}\n"
    : "+f"(d[0]), "+f"(d[1]), "+f"(d[2]), "+f"(d[3]), "+f"(d[4]), "+f"(d[5]), "+f"(d[6]), "+f"(d[7]), "+f"(d[8]), "+f"(d[9]), "+f"(d[10]), "+f"(d[11]), "+f"(d[12]), "+f"(d[13]), "+f"(d[14]), "+f"(d[15]), "+f"(d[16]), "+f"(d[17]), "+f"(d[18]), "+f"(d[19]), "+f"(d[20]), "+f"(d[21]), "+f"(d[22]), "+f"(d[23]), "+f"(d[24]), "+f"(d[25]), "+f"(d[26]), "+f"(d[27]), "+f"(d[28]), "+f"(d[29]), "+f"(d[30]), "+f"(d[31]), "+f"(d[32]), "+f"(d[33]), "+f"(d[34]), "+f"(d[35]), "+f"(d[36]), "+f"(d[37]), "+f"(d[38]), "+f"(d[39]), "+f"(d[40]), "+f"(d[41]), "+f"(d[42]), "+f"(d[43]), "+f"(d[44]), "+f"(d[45]), "+f"(d[46]), "+f"(d[47]), "+f"(d[48]), "+f"(d[49]), "+f"(d[50]), "+f"(d[51]), "+f"(d[52]), "+f"(d[53]), "+f"(d[54]), "+f"(d[55]), "+f"(d[56]), "+f"(d[57]), "+f"(d[58]), "+f"(d[59]), "+f"(d[60]), "+f"(d[61]), "+f"(d[62]), "+f"(d[63]), "+f"(d[64]), "+f"(d[65]), "+f"(d[66]), "+f"(d[67]), "+f"(d[68]), "+f"(d[69]), "+f"(d[70]), "+f"(d[71]), "+f"(d[72]), "+f"(d[73]), "+f"(d[74]), "+f"(d[75]), "+f"(d[76]), "+f"(d[77]), "+f"(d[78]), "+f"(d[79]), "+f"(d[80]), "+f"(d[81]), "+f"(d[82]), "+f"(d[83]), "+f"(d[84]), "+f"(d[85]), "+f"(d[86]), "+f"(d[87]), "+f"(d[88]), "+f"(d[89]), "+f"(d[90]), "+f"(d[91]), "+f"(d[92]), "+f"(d[93]), "+f"(d[94]), "+f"(d[95]), "+f"(d[96]), "+f"(d[97]), "+f"(d[98]), "+f"(d[99]), "+f"(d[100]), "+f"(d[101]), "+f"(d[102]), "+f"(d[103]), "+f"(d[104]), "+f"(d[105]), "+f"(d[106]), "+f"(d[107]), "+f"(d[108]), "+f"(d[109]), "+f"(d[110]), "+f"(d[111]), "+f"(d[112]), "+f"(d[113]), "+f"(d[114]), "+f"(d[115]), "+f"(d[116]), "+f"(d[117]), "+f"(d[118]), "+f"(d[119]), "+f"(d[120]), "+f"(d[121]), "+f"(d[122]), "+f"(d[123]), "+f"(d[124]), "+f"(d[125]), "+f"(d[126]), "+f"(d[127])
    : "l"(da), "l"(db), "r"(sd));
}

__device__ __forceinline__ void wgmma_m64n128_ss(float (&d)[64], uint64_t da, uint64_t db, int sd) {
  asm volatile(
    "{\n.reg .pred p;\nsetp.ne.b32 p, %66, 0;\n"
    "wgmma.mma_async.sync.aligned.m64n128k16.f32.bf16.bf16 "
    "{%0, %1, %2, %3, %4, %5, %6, %7, %8, %9, %10, %11, %12, %13, %14, %15, %16, %17, %18, %19, %20, %21, %22, %23, %24, %25, %26, %27, %28, %29, %30, %31, %32, %33, %34, %35, %36, %37, %38, %39, %40, %41, %42, %43, %44, %45, %46, %47, %48, %49, %50, %51, %52, %53, %54, %55, %56, %57, %58, %59, %60, %61, %62, %63}, %64, %65, p, 1, 1, 0, 0;\n}\n"
    : "+f"(d[0]), "+f"(d[1]), "+f"(d[2]), "+f"(d[3]), "+f"(d[4]), "+f"(d[5]), "+f"(d[6]), "+f"(d[7]), "+f"(d[8]), "+f"(d[9]), "+f"(d[10]), "+f"(d[11]), "+f"(d[12]), "+f"(d[13]), "+f"(d[14]), "+f"(d[15]), "+f"(d[16]), "+f"(d[17]), "+f"(d[18]), "+f"(d[19]), "+f"(d[20]), "+f"(d[21]), "+f"(d[22]), "+f"(d[23]), "+f"(d[24]), "+f"(d[25]), "+f"(d[26]), "+f"(d[27]), "+f"(d[28]), "+f"(d[29]), "+f"(d[30]), "+f"(d[31]), "+f"(d[32]), "+f"(d[33]), "+f"(d[34]), "+f"(d[35]), "+f"(d[36]), "+f"(d[37]), "+f"(d[38]), "+f"(d[39]), "+f"(d[40]), "+f"(d[41]), "+f"(d[42]), "+f"(d[43]), "+f"(d[44]), "+f"(d[45]), "+f"(d[46]), "+f"(d[47]), "+f"(d[48]), "+f"(d[49]), "+f"(d[50]), "+f"(d[51]), "+f"(d[52]), "+f"(d[53]), "+f"(d[54]), "+f"(d[55]), "+f"(d[56]), "+f"(d[57]), "+f"(d[58]), "+f"(d[59]), "+f"(d[60]), "+f"(d[61]), "+f"(d[62]), "+f"(d[63])
    : "l"(da), "l"(db), "r"(sd));
}

__device__ __forceinline__ void wgmma_m64n128_ss_tb(float (&d)[64], uint64_t da, uint64_t db, int sd) {
  asm volatile(
    "{\n.reg .pred p;\nsetp.ne.b32 p, %66, 0;\n"
    "wgmma.mma_async.sync.aligned.m64n128k16.f32.bf16.bf16 "
    "{%0, %1, %2, %3, %4, %5, %6, %7, %8, %9, %10, %11, %12, %13, %14, %15, %16, %17, %18, %19, %20, %21, %22, %23, %24, %25, %26, %27, %28, %29, %30, %31, %32, %33, %34, %35, %36, %37, %38, %39, %40, %41, %42, %43, %44, %45, %46, %47, %48, %49, %50, %51, %52, %53, %54, %55, %56, %57, %58, %59, %60, %61, %62, %63}, %64, %65, p, 1, 1, 0, 1;\n}\n"
    : "+f"(d[0]), "+f"(d[1]), "+f"(d[2]), "+f"(d[3]), "+f"(d[4]), "+f"(d[5]), "+f"(d[6]), "+f"(d[7]), "+f"(d[8]), "+f"(d[9]), "+f"(d[10]), "+f"(d[11]), "+f"(d[12]), "+f"(d[13]), "+f"(d[14]), "+f"(d[15]), "+f"(d[16]), "+f"(d[17]), "+f"(d[18]), "+f"(d[19]), "+f"(d[20]), "+f"(d[21]), "+f"(d[22]), "+f"(d[23]), "+f"(d[24]), "+f"(d[25]), "+f"(d[26]), "+f"(d[27]), "+f"(d[28]), "+f"(d[29]), "+f"(d[30]), "+f"(d[31]), "+f"(d[32]), "+f"(d[33]), "+f"(d[34]), "+f"(d[35]), "+f"(d[36]), "+f"(d[37]), "+f"(d[38]), "+f"(d[39]), "+f"(d[40]), "+f"(d[41]), "+f"(d[42]), "+f"(d[43]), "+f"(d[44]), "+f"(d[45]), "+f"(d[46]), "+f"(d[47]), "+f"(d[48]), "+f"(d[49]), "+f"(d[50]), "+f"(d[51]), "+f"(d[52]), "+f"(d[53]), "+f"(d[54]), "+f"(d[55]), "+f"(d[56]), "+f"(d[57]), "+f"(d[58]), "+f"(d[59]), "+f"(d[60]), "+f"(d[61]), "+f"(d[62]), "+f"(d[63])
    : "l"(da), "l"(db), "r"(sd));
}

__device__ __forceinline__ void wgmma_m64n128_rs_tb(float* d, uint32_t a0, uint32_t a1, uint32_t a2, uint32_t a3, uint64_t db, int sd) {
  asm volatile(
    "{\n.reg .pred p;\nsetp.ne.b32 p, %69, 0;\n"
    "wgmma.mma_async.sync.aligned.m64n128k16.f32.bf16.bf16 "
    "{%0, %1, %2, %3, %4, %5, %6, %7, %8, %9, %10, %11, %12, %13, %14, %15, %16, %17, %18, %19, %20, %21, %22, %23, %24, %25, %26, %27, %28, %29, %30, %31, %32, %33, %34, %35, %36, %37, %38, %39, %40, %41, %42, %43, %44, %45, %46, %47, %48, %49, %50, %51, %52, %53, %54, %55, %56, %57, %58, %59, %60, %61, %62, %63}, {%64, %65, %66, %67}, %68, p, 1, 1, 1;\n}\n"
    : "+f"(d[0]), "+f"(d[1]), "+f"(d[2]), "+f"(d[3]), "+f"(d[4]), "+f"(d[5]), "+f"(d[6]), "+f"(d[7]), "+f"(d[8]), "+f"(d[9]), "+f"(d[10]), "+f"(d[11]), "+f"(d[12]), "+f"(d[13]), "+f"(d[14]), "+f"(d[15]), "+f"(d[16]), "+f"(d[17]), "+f"(d[18]), "+f"(d[19]), "+f"(d[20]), "+f"(d[21]), "+f"(d[22]), "+f"(d[23]), "+f"(d[24]), "+f"(d[25]), "+f"(d[26]), "+f"(d[27]), "+f"(d[28]), "+f"(d[29]), "+f"(d[30]), "+f"(d[31]), "+f"(d[32]), "+f"(d[33]), "+f"(d[34]), "+f"(d[35]), "+f"(d[36]), "+f"(d[37]), "+f"(d[38]), "+f"(d[39]), "+f"(d[40]), "+f"(d[41]), "+f"(d[42]), "+f"(d[43]), "+f"(d[44]), "+f"(d[45]), "+f"(d[46]), "+f"(d[47]), "+f"(d[48]), "+f"(d[49]), "+f"(d[50]), "+f"(d[51]), "+f"(d[52]), "+f"(d[53]), "+f"(d[54]), "+f"(d[55]), "+f"(d[56]), "+f"(d[57]), "+f"(d[58]), "+f"(d[59]), "+f"(d[60]), "+f"(d[61]), "+f"(d[62]), "+f"(d[63])
    : "r"(a0), "r"(a1), "r"(a2), "r"(a3), "l"(db), "r"(sd));
}

__device__ __forceinline__ void wgmma_m64n64_rs(float (&d)[32], const uint32_t* a, uint64_t db, int sd) {
  asm volatile(
    "{\n.reg .pred p;\nsetp.ne.b32 p, %37, 0;\n"
    "wgmma.mma_async.sync.aligned.m64n64k16.f32.bf16.bf16 "
    "{%0, %1, %2, %3, %4, %5, %6, %7, %8, %9, %10, %11, %12, %13, %14, %15, %16, %17, %18, %19, %20, %21, %22, %23, %24, %25, %26, %27, %28, %29, %30, %31}, {%32, %33, %34, %35}, %36, p, 1, 1, 0;\n}\n"
    : "+f"(d[0]), "+f"(d[1]), "+f"(d[2]), "+f"(d[3]), "+f"(d[4]), "+f"(d[5]), "+f"(d[6]), "+f"(d[7]), "+f"(d[8]), "+f"(d[9]), "+f"(d[10]), "+f"(d[11]), "+f"(d[12]), "+f"(d[13]), "+f"(d[14]), "+f"(d[15]), "+f"(d[16]), "+f"(d[17]), "+f"(d[18]), "+f"(d[19]), "+f"(d[20]), "+f"(d[21]), "+f"(d[22]), "+f"(d[23]), "+f"(d[24]), "+f"(d[25]), "+f"(d[26]), "+f"(d[27]), "+f"(d[28]), "+f"(d[29]), "+f"(d[30]), "+f"(d[31])
    : "r"(a[0]), "r"(a[1]), "r"(a[2]), "r"(a[3]), "l"(db), "r"(sd));
}

constexpr int G_STAGES = 4;
constexpr int G_A_BYTES = 128 * 64 * 2;
constexpr int G_B_BYTES = 256 * 64 * 2;
constexpr int G_STAGE_BYTES = G_A_BYTES + G_B_BYTES;
constexpr int G_STG_OFF = G_STAGES * G_STAGE_BYTES;
constexpr int BAR_OFF = G_STG_OFF + 32768 + 2048;
constexpr int SMEM_BYTES = BAR_OFF + 1024;
constexpr int B_GFULL = 0, B_GEMPTY = 32, B_OY2 = 64, B_PFULL = 224;
constexpr int B_KFULL = 80, B_KEMPTY = 96, B_VFULL = 112, B_VEMPTY = 128, B_QFULL = 144, B_QEMPTY = 160,
              B_QDONE = 184;
constexpr int B_CFULL = 192;
constexpr int B_OFREE = 256, B_OFULL = 272, B_OEMPTY = 320, B_OY = 368;
constexpr int B_SFULL = 392, B_SFREE = 424, B_PEND = 456, B_SCMD = 512;

#define PHASE_PROLOGUE                                                                \
  uint32_t tid, rt_zero;                                                              \
  asm volatile("mov.u32 %0, %%tid.x;" : "=r"(tid));                                   \
  asm volatile("mov.u32 %0, %%nctaid.y;" : "=r"(rt_zero));                            \
  asm volatile("" : "+r"(smem0));                                                     \
  rt_zero = __shfl_sync(0xffffffffu, rt_zero >> 8, 0);   \
  const uint32_t sbase = __shfl_sync(0xffffffffu, smem0, 0);                          \
  const uint32_t bar = sbase + BAR_OFF;                                               \
  const int wg = __shfl_sync(0xffffffffu, tid >> 7, 0);                               \
  const int warp = (tid >> 5) & 3, lane = tid & 31, wtid = tid & 127;                 \
  (void)rt_zero; (void)bar; (void)warp; (void)lane; (void)wtid;

enum { ST_END = 0, ST_BOX1, ST_BOX2, ST_BOX2Q, ST_BOX2L };
__device__ __forceinline__ void st_post(uint32_t bar, int wg, int wtid, uint32_t n, int kind, const void* dst,
                                        uint32_t src, int c0, int c1, int sig) {
  if (wtid == 0) {
    const uint32_t c = bar + B_SCMD + wg * 64 + (n & 1) * 32;
    const uint64_t d = reinterpret_cast<uint64_t>(dst);
    sts128(c, make_uint4(kind, src, c0, c1));
    sts128(c + 16, make_uint4((uint32_t)d, (uint32_t)(d >> 32), sig, 0));
  }
  fence_proxy_async();
  __syncwarp();
  mbar_arrive_if(bar + B_SFULL + wg * 16 + (n & 1) * 8, (wtid & 31) == 0);
}
__device__ __forceinline__ void st_wait(uint32_t bar, int wg, uint32_t n) {
  const uint32_t b = bar + B_SFREE + wg * 16 + (n & 1) * 8;
  if (!mbar_try(b, ~(n >> 1) & 1)) mbar_wait(b, ~(n >> 1) & 1);
}
__device__ __forceinline__ void note(uint32_t bar, uint32_t cnt) {
  asm volatile("red.release.cta.shared.add.u32 [%0], 1;" ::"r"(bar + B_PEND + 4 * cnt) : "memory");
}
__device__ __forceinline__ void store_agent(uint32_t bar, int wg) {
  mbar_arrive(bar + B_SFREE + wg * 16);
  mbar_arrive(bar + B_SFREE + wg * 16 + 8);
  for (uint32_t n = 0;; n++) {
    mbar_wait_sleep(bar + B_SFULL + wg * 16 + (n & 1) * 8, (n >> 1) & 1);
    const uint4 c = lds128(bar + B_SCMD + wg * 64 + (n & 1) * 32);
    const uint4 d = lds128(bar + B_SCMD + wg * 64 + (n & 1) * 32 + 16);
    if (c.x == ST_END) break;
    const CUtensorMap* dst = reinterpret_cast<const CUtensorMap*>((uint64_t)d.x | ((uint64_t)d.y << 32));
    tma_store_2d(dst, c.y, c.z, c.w);
    if (c.x >= ST_BOX2) tma_store_2d(dst, c.y + 8192, c.z + 64, c.w);
    tma_store_commit();
    tma_store_wait_read<0>();
    mbar_arrive(bar + B_SFREE + wg * 16 + (n & 1) * 8);
    if (c.x == ST_BOX2L) mbar_arrive(bar + B_OFREE + 8 * wg);
    if ((int)d.z >= 0) {
      tma_store_wait<0>();
      if (d.z == 0) { TD(6) }
      asm volatile("fence.proxy.async.global;" ::: "memory");
      if (c.x == ST_BOX2Q) mbar_arrive(bar + B_QDONE);
      else note(bar, d.z);
      if (c.x == ST_BOX2L) break;
    }
  }
  note(bar, CNT_DONE);
}

struct Maps {
  const bf16 *shift_k, *x, *gate_w, *ssm_k, *ssm_D;
  uint8_t id[128][4];
  CUtensorMap a[2];
  CUtensorMap b[3];
  CUtensorMap c[3];
  CUtensorMap bk, bv;
  CUtensorMap q, k, v, o;
  CUtensorMap oa, ob, oc, ox;
  CUtensorMap y, y2;
};

constexpr int P_SLOT = 67 * 128, P_V = 35 * 128, P_TAPS = 2 * P_SLOT;
__device__ __forceinline__ void ldsm4t(uint32_t (&r)[4], uint32_t a) {
  asm volatile("ldmatrix.sync.aligned.m8n8.x4.trans.shared.b16 {%0, %1, %2, %3}, [%4];"
               : "=r"(r[0]), "=r"(r[1]), "=r"(r[2]), "=r"(r[3])
               : "r"(a));
}
__device__ __forceinline__ uint32_t fma_bf2(uint32_t a, uint32_t b, uint32_t c) {
  uint32_t r;
  asm("fma.rn.bf16x2 %0, %1, %2, %3;" : "=r"(r) : "r"(a), "r"(b), "r"(c));
  return r;
}
__device__ __forceinline__ void prep_agent(const Maps& maps, uint32_t sbase, int w, int lane) {
  const uint32_t bar = sbase + BAR_OFF, pb = bar + B_PFULL + w * 16;
  const int d0 = (blockIdx.x >> 3) * 64, t0 = (blockIdx.x & 7) * 256 + w * 128;
  mbar_wait_sleep(bar + B_GFULL + 8 * (G_STAGES - 1), 0);
#pragma unroll 1
  for (int i = -1; i < 4; i++) {
    GA(82 + 2 * i)
    if (i >= 0) mbar_wait_sleep(pb + (i & 1) * 8, i >> 1);
    GA(83 + 2 * i)
    const uint32_t so = sbase + G_STG_OFF + w * (P_TAPS + 512) + (i & 1) * P_SLOT;
    if (i < 3 && elect_one()) {
      const uint32_t b = pb + (~i & 1) * 8, dst = so + (i & 1 ? -P_SLOT : P_SLOT);
      mbar_expect_tx(b, i < 0 ? P_SLOT + 512 : P_SLOT);
      const uint64_t pol = policy_evict_first();
      tma_load_2d_hint(dst, &maps.bk, b, d0, t0 + 32 * i + 29, pol);
      tma_load_2d_hint(dst + P_V, &maps.bv, b, d0, t0 + 32 * i + 32, pol);
      if (i < 0) bulk_load(sbase + G_STG_OFF + P_TAPS, maps.shift_k + d0 * 4, 512, b);
    }
    if (i < 0) continue;
    uint32_t ak[4];
#pragma unroll
    for (int r = 0; r < 4; r++) {
      const uint32_t a = so / 128 + r + 4 * (lane & 6) + (((((lane >> 2) ^ lane) & 6) + (lane & 1)) ^ 7);
      ak[r] = a * 128 + (a & 7) * 16;
    }
    bf16* dst = g_kvT + (size_t)(d0 + (lane >> 2)) * S_LEN + t0 + ((lane & 3) + 4 * i) * 8;
#pragma unroll 1
    for (int cg = 0; cg < 128; cg += 16) {
      uint32_t t01, t23, k[4][4], v[4];
      asm volatile("ld.shared.v2.u32 {%0, %1}, [%2];"
                   : "=r"(t01), "=r"(t23)
                   : "r"(sbase + G_STG_OFF + P_TAPS + cg * 4 + (lane >> 2) * 8));
#pragma unroll
      for (int r = 0; r < 4; r++) ldsm4t(k[r], ak[r] ^ cg);
      ldsm4t(v, (ak[3] ^ cg) + 4096);
      const uint32_t w0 = __byte_perm(t01, 0, 0x1010), w1 = __byte_perm(t01, 0, 0x3232);
      const uint32_t w2 = __byte_perm(t23, 0, 0x1010), w3 = __byte_perm(t23, 0, 0x3232);
#pragma unroll
      for (int j = 0; j < 4; j++)
        v[j] = mul_bf2(fma_bf2(k[3][j], w0, fma_bf2(k[2][j], w1, fma_bf2(k[1][j], w2, mul_bf2(k[0][j], w3)))), v[j]);
      const bool s1 = lane & 1, s2 = lane & 2;
      const uint32_t a0 = s1 ? v[1] : v[0], a1 = s1 ? v[0] : v[1], a2 = s1 ? v[3] : v[2], a3 = s1 ? v[2] : v[3];
      *reinterpret_cast<uint4*>(dst) = make_uint4(s2 ? a2 : a0, s2 ? a3 : a1, s2 ? a0 : a2, s2 ? a1 : a3);
      dst += 8 * S_LEN;
    }
    fence_proxy_async();
    __syncwarp();
  }
  GA(90)
  if (lane == 0) note(bar, CNT_PREP);
  __syncwarp();
  GA(91)
}

__device__ __forceinline__ void qkv_tile(const Maps& maps, int it, int& which, int& m_tile, int& n_tile) {
  const bool q = it == 0 || it >= 5;
  const int b = maps.id[blockIdx.x][it >= 5];
  which = q ? 0 : 2 - (it & 1);
  m_tile = b & 15;
  n_tile = (b >> 4) * 2 + ((0x19 >> it) & 1);
}

constexpr int G_NTILES = 6;
__device__ __forceinline__ void qkv_producer(const Maps& maps, uint32_t sbase, bool first) {
  const uint32_t bar = sbase + BAR_OFF;
  uint32_t stage = 0, phase = 0;
#pragma unroll 1
  for (int it = 0; it < (first ? 1 : G_NTILES); it++) {
    int which, m_tile, n_tile;
    qkv_tile(maps, it, which, m_tile, n_tile);
    const CUtensorMap* ma = &maps.a[which == 0 ? 0 : 1];
    const CUtensorMap* mb = &maps.b[which];
    const int nk = first ? G_STAGES : which == 0 ? 16 : 8;
#pragma unroll 1
    for (int kt = (it == 0 && !first) ? G_STAGES : 0; kt < nk; kt++) {
      if (!first) mbar_wait_sleep(bar + B_GEMPTY + 8 * stage, phase);
      const uint32_t fb = bar + B_GFULL + 8 * stage;
      const uint32_t sa = sbase + stage * G_STAGE_BYTES;
      mbar_expect_tx(fb, G_STAGE_BYTES);
      tma_load_2d(sa, ma, fb, kt * 64, m_tile * 128);
      tma_load_3d(sa + G_A_BYTES, mb, fb, 0, kt * 64, n_tile * 4);
      if (++stage == G_STAGES) { stage = 0; phase ^= 1; }
      {
        const int b = maps.id[blockIdx.x][1];
        if (it == 2 && kt == (b & 7)) {
          for (int i = 0; i < 2; i++)
            asm volatile("cp.async.bulk.prefetch.tensor.2d.L2.global.tile [%0, {%1, %2}];" ::"l"(&maps.a[0]),
                         "r"((b >> 4) * 128 + i * 64), "r"((b & 15) * 128)
                         : "memory");
        }
        if (it == 3 && kt == (b & 7))
          asm volatile("cp.async.bulk.prefetch.tensor.3d.L2.global.tile [%0, {%1, %2, %3}];" ::"l"(&maps.b[0]), "r"(0),
                       "r"((b & 15) * 64), "r"((b >> 4) * 8)
                       : "memory");
      }
    }
  }
}

__device__ __noinline__ void publisher(uint32_t bar, int lane, uint32_t nsrc) {
  uint32_t done = 0;
  CLK_DECL
#pragma unroll 1
  for (uint32_t spins = 0; done < nsrc && spins < (1u << 20); spins++) {
    CLK_SAMPLE
    uint32_t v = 0;
    if (lane < CNT_N)
      asm volatile("atom.acquire.cta.shared.exch.b32 %0, [%1], 0;" : "=r"(v) : "r"(bar + B_PEND + 4 * lane) : "memory");
    done += __shfl_sync(0xffffffffu, v, CNT_DONE);
    if (lane == CNT_DONE) v = 0;
    if (done == nsrc && lane < CNT_DONE) {
      uint32_t w;
      asm volatile("atom.acquire.cta.shared.exch.b32 %0, [%1], 0;" : "=r"(w) : "r"(bar + B_PEND + 4 * lane) : "memory");
      v += w;
    }
    if (v && lane == 0) { TD(0) }
    if (v) cnt_signal_release(lane, v);
    if (v && lane == 0) { TD(1) }
    if (!__any_sync(0xffffffffu, v != 0)) __nanosleep(200);
  }
  CLK_END
  __threadfence();
  __syncwarp();
}

__device__ __forceinline__ void gate_rows(const Maps& maps, uint32_t sbase, int w48, int w12, int lane) {
  const uint32_t buf = sbase + w12 * 16384, gb = sbase + BAR_OFF + 768 + w12 * 16;
  if (lane == 0) {
    mbar_init(gb, 1);
    mbar_init(gb + 8, 1);
    fence_barrier_init();
    for (int i = 0; i < 2; i++) {
      mbar_expect_tx(gb + 8 * i, 8192);
      bulk_load(buf + i * 8192, maps.x + (size_t)(w48 + 48 * i) * 4 * DM, 8192, gb + 8 * i);
    }
  }
  __syncwarp();
  uint4 wv[4];
#pragma unroll
  for (int i = 0; i < 4; i++) wv[i] = __ldg(reinterpret_cast<const uint4*>(maps.gate_w + (i * 32 + lane) * 8));
  int it = 0;
#pragma unroll 1
  for (int row = w48 * 4; row < S_LEN; row += 48 * 4, it++) {
    mbar_wait(gb + 8 * (it & 1), (it >> 1) & 1);
    uint4 xv[4][4];
#pragma unroll
    for (int r = 0; r < 4; r++)
#pragma unroll
      for (int i = 0; i < 4; i++) xv[r][i] = lds128(buf + (it & 1) * 8192 + r * 2048 + (i * 32 + lane) * 16);
    float d[2][4];
#pragma unroll
    for (int pr = 0; pr < 2; pr++) {
      d[pr][0] = d[pr][1] = d[pr][2] = d[pr][3] = 0.f;
      auto acc = [&](uint32_t a0, uint32_t a2, uint32_t b0, uint32_t b2, uint32_t w0, uint32_t w2) {
        asm volatile(
            "mma.sync.aligned.m16n8k16.row.col.f32.bf16.bf16.f32 {%0, %1, %2, %3}, {%4, %5, %6, %7}, {%8, %8}, "
            "{%0, %1, %2, %3};"
            : "+f"(d[pr][0]), "+f"(d[pr][1]), "+f"(d[pr][2]), "+f"(d[pr][3])
            : "r"(mul_bf2(a0, w0)), "r"(mul_bf2(b0, w0)), "r"(mul_bf2(a2, w2)), "r"(mul_bf2(b2, w2)), "r"(0x3f803f80u));
      };
#pragma unroll
      for (int i = 0; i < 4; i++) {
        acc(xv[2 * pr][i].x, xv[2 * pr][i].y, xv[2 * pr + 1][i].x, xv[2 * pr + 1][i].y, wv[i].x, wv[i].y);
        acc(xv[2 * pr][i].z, xv[2 * pr][i].w, xv[2 * pr + 1][i].z, xv[2 * pr + 1][i].w, wv[i].z, wv[i].w);
      }
    }
    float sum = (lane & 2) ? ((lane & 1) ? d[1][2] : d[1][0]) : ((lane & 1) ? d[0][2] : d[0][0]);
#pragma unroll
    for (int off = 16; off >= 4; off >>= 1) sum += __shfl_xor_sync(0xffffffffu, sum, off);
    if (lane < 4) g_gate[row + lane] = bf16_round(rcp(1.0f + __expf(-bf16_round(sum))));
    if (lane == 0 && row + 2 * 48 * 4 < S_LEN) {
      mbar_expect_tx(gb + 8 * (it & 1), 8192);
      bulk_load(buf + (it & 1) * 8192, maps.x + (size_t)(row + 2 * 48 * 4) * DM, 8192, gb + 8 * (it & 1));
    }
  }
}

constexpr float Q_SCALE = 0.08838834764831845f * 1.4426950408889634f;
__device__ __forceinline__ uint32_t qkv_consumer(const Maps& maps, uint32_t smem0, bool fused, float (&rest)[64]) {
  PHASE_PROLOGUE
  constexpr int NTILES = G_NTILES;
  float acc[128];
  uint32_t stage = 0, phase = 0;
  const uint32_t stg = sbase + G_STG_OFF + wg * 18432;
  const int st_row = warp * 16 + (lane & 7) + ((lane >> 3) & 1) * 8;
  const int st_cb = lane >> 4;
  uint32_t pend[64];
  const CUtensorMap* pend_map = nullptr;
  int pend_c0 = 0, pend_c1 = 0;
  uint32_t sn = 0;
  auto put_box = [&](uint32_t buf, const uint32_t* v) {
#pragma unroll
    for (int jp = 0; jp < 4; jp++) {
      const int chunk = jp * 2 + st_cb;
      const uint32_t addr = buf + st_row * 128 + ((chunk ^ (st_row & 7)) << 4);
      stmatrix_x4(addr, v[jp * 4], v[jp * 4 + 1], v[jp * 4 + 2], v[jp * 4 + 3]);
    }
  };
  GT(gti++)
#pragma unroll 1
  for (int it = 0; it <= NTILES; it++) {
    int which, m_tile, n_tile;
    qkv_tile(maps, it, which, m_tile, n_tile);
    const int nk = (which == 0 && it < NTILES) ? 16 : 8;
    uint32_t prev_stage = 0;
#pragma unroll 1
    for (int kt = 0; kt < nk; kt++) {
      if (it < NTILES) {
        mbar_wait((bar + B_GFULL) + 8 * stage, phase);
        GT(gti++)
        const uint64_t da0 = make_desc(sbase + stage * G_STAGE_BYTES + wg * 8192, 16, 1024, DESC_SW128);
        const uint64_t db0 = make_desc(sbase + stage * G_STAGE_BYTES + G_A_BYTES, 8192, 1024, DESC_SW128);
        wgmma_fence();
#pragma unroll
        for (int kk = 0; kk < 4; kk++) {
          wgmma_m64n256_ss_tb(acc, desc_add(da0, kk * 2), desc_add(db0, kk * 128), (kt | kk) != 0);
        }
        wgmma_commit();
      }
      const uint32_t when = it == 0 ? 0 : it == 5 ? 0x922 << wg : wg ? 0xAA : 0x55;
      if ((when >> kt) & 1) {
        const int c = __popc(when & ~(~0u << kt));
        st_wait(bar, wg, sn - 2);
        const uint32_t buf = stg + (c & 1) * 8192;
        switch (c) {
          case 0: put_box(buf, pend); break;
          case 1: put_box(buf, pend + 16); break;
          case 2: put_box(buf, pend + 32); break;
          default: put_box(buf, pend + 48); break;
        }
        st_post(bar, wg, wtid, sn, ST_BOX1, pend_map, buf, pend_c0 + c * 64, pend_c1, (c == 3 && it > 1) ? CNT_KV + (it > 3) : -1);
        sn++;
      }
      if (it < NTILES) {
        wgmma_wait<1>();
        mbar_arrive_if((bar + B_GEMPTY) + 8 * prev_stage, wtid == 32 && kt > 0);
        prev_stage = stage;
        if (++stage == G_STAGES) { stage = 0; phase ^= 1; }
      }
    }
    wgmma_wait<0>();
    fence_regs(acc);
    if (it == NTILES) break;
    GT(gti++)
    mbar_arrive_if((bar + B_GEMPTY) + 8 * prev_stage, wtid == 32);
    if (it == NTILES - 1 && fused) break;
    if (which == 0) {
#pragma unroll
      for (int j = 0; j < 128; j++) acc[j] *= Q_SCALE;
    }
#pragma unroll
    for (int j = 0; j < 64; j++) pend[j] = pack_bf16(acc[2 * j], acc[2 * j + 1]);
    pend_map = &maps.c[which];
    pend_c0 = n_tile * 256;
    pend_c1 = m_tile * 128 + wg * 64;
  }
  mbar_wait(bar + B_GEMPTY, 1);
#pragma unroll
  for (int j = 0; j < 32; j++) pend[j] = pack_bf16(acc[2 * j] * Q_SCALE, acc[2 * j + 1] * Q_SCALE);
  put_box(sbase + wg * 8192, pend);
  put_box(sbase + 16384 + wg * 8192, pend + 16);
  fence_proxy_async();
#pragma unroll
  for (int j = 0; j < 64; j++) rest[j] = acc[64 + j];
  GT(gti++)
  return sn;
}

constexpr int A_TILE = 128 * 128 * 2;
constexpr int A_Q_OFF = 0;
constexpr int A_K_OFF = 2 * A_TILE;
constexpr int A_V_OFF = 4 * A_TILE;
constexpr int A_O_OFF = 6 * A_TILE;
constexpr int A_ITEMS = NH * (S_LEN / 128);

constexpr uint32_t A_ORDER = 0x3120, A_STEPS = 34;
__device__ __forceinline__ int item_m(uint32_t it) { return it & 15; }
__device__ __forceinline__ int item_h(uint32_t it) { return it >> 4; }

constexpr int C_H0 = 16, C_U = C_H0 + 4096 + 112, C_SLOT = C_U + 4096;
constexpr int C_H1 = 2 * C_SLOT + 80;
constexpr int C_X_OFF = C_H1 + 4096 + 48;

__device__ __forceinline__ uint32_t item_of(const Maps& maps, uint32_t r) {
  const uint32_t b = maps.id[blockIdx.x & 127][1];
  return (b >> 4) * 64 + ((A_ORDER >> (4 * r)) & 3) * 16 + ((b ^ ((r & 1) * 15)) & 15);
}

constexpr uint32_t C_SIDE = 48;
__device__ __forceinline__ uint32_t conv_first(const Maps& maps) {
  const uint32_t b = maps.id[blockIdx.x & 127][1];
  return (b >> 4) * 128 + (b & 15);
}

__device__ __forceinline__ void conv_consumer(const Maps& maps, uint32_t smem0, uint32_t first, uint32_t step,
                                              uint32_t end) {
  PHASE_PROLOGUE
  const uint32_t full = bar + B_CFULL + wg * 16;
  const uint32_t ca = sbase + (wg ? A_V_OFF + A_TILE : A_Q_OFF);
  const int w4 = __shfl_sync(0xffffffffu, warp, 0);
  auto fetch = [&](uint32_t c, uint32_t slot) {
    if (w4 == 2 && c < end) {
      if (elect_one()) {
        const uint32_t sb = ca + slot * C_SLOT, fb = full + 8 * slot;
        const uint64_t pol = policy_evict_first();
        mbar_expect_tx(fb, 2 * 4096);
        bulk_load_hint(sb + C_H0, maps.ssm_k + (size_t)c * S_LEN, 4096, fb, pol);
        bulk_load_hint(sb + C_U, g_kvT + (size_t)c * S_LEN, 4096, fb, pol);
      }
    }
  };
  auto shift_h = [&](uint32_t so) {
    const uint32_t a = ca + so + C_H0 + wtid * 16;
#pragma unroll
    for (int i = 0; i < 2; i++) {
      uint32_t p;
      const uint4 v = lds128(a + i * 2048);
      asm volatile("ld.shared.u32 %0, [%1];" : "=r"(p) : "r"(a + i * 2048 - 4));
      sts128(ca + C_H1 + wtid * 16 + i * 2048, make_uint4(__byte_perm(p, v.x, 0x5432), __byte_perm(v.x, v.y, 0x5432),
                                                      __byte_perm(v.y, v.z, 0x5432), __byte_perm(v.z, v.w, 0x5432)));
    }
  };
  if (wtid == 96 && wg) { TD(15) }
  fetch(first, 0);
  if (wtid < 17)
    sts128(ca + (wtid >> 3) * C_SLOT + (wtid & 7 ? 4096 + (wtid & 7) * 16 : (wtid & 16) * 4), make_uint4(0, 0, 0, 0));
  fence_proxy_async();
  const uint32_t ha = ca + ((lane & 4) ? C_H1 : C_H0) + 4 * ((lane & 3) - (lane >> 3)) + w4 * 256;
  const uint32_t ua = ca + C_U + w4 * 256 + (lane >> 4) * 1024 + (lane & 15) * 16;
  const uint32_t xa = ca + C_X_OFF + lane * 8, xw = xa + w4 * 3072;
  uint32_t xg[3];
#pragma unroll
  for (int k = 0; k < 3; k++) {
    const int w = (w4 + k + 1) & 3;
    xg[k] = xa + (w * 12 + w4 - w - (w < w4 ? 1 : 0)) * 256;
  }
  const bool pp = step != 16;
  uint32_t h[2][16];
  const uint32_t hs = (lane & 4) ? 0 : C_SLOT;
  auto load_h = [&](uint32_t so, int a) {
#pragma unroll
    for (int i = 0; i < 16; i++)
      asm volatile("ld.shared.u32 %0, [%1];"
                   : "=r"(h[a & 1][i])
                   : "r"(ha + so + 1024 * a + 32 * (i >> 2) + (i & 1) * 128 + (~i & 2) * 8));
  };
  mbar_wait(full, 0);
  named_bar_sync(1 + wg, 128);
  shift_h(0);
  named_bar_sync(1 + wg, 128);
  fetch(first + step, 1);
  load_h(0, 0);
  load_h(0, 1);
  mbar_wait(bar + B_OFREE, 0);
  mbar_wait(bar + B_OFREE + 8, 0);
  uint32_t n = 0, ch = first;
  for (; ch < end; n++, ch += step) {
    CT(0)
    const uint32_t so = (n & 1) * C_SLOT, ho = (n & 1) * hs;
    uint32_t db = (uint32_t)make_desc(ca + so + C_U - 16, 16, 0, 0);
    asm volatile("" : "+r"(db));
    uint32_t dsk = __ldg(reinterpret_cast<const unsigned short*>(maps.ssm_D) + (ch | (lane & rt_zero)));
    float d[4][32], own[16];
    auto mma = [&](int a) {
      wgmma_fence();
#pragma unroll
      for (int c = a; c < 4; c++)
#pragma unroll
        for (int b = 0; b < 4; b++)
          wgmma_m64n64_rs(d[c], &h[a & 1][4 * b], (8ull << 32) | (db + 64 * (c - a) - 2 * b), (a | b) != 0);
      wgmma_commit();
    };
    auto put = [&](int c) {
      fence_regs(d[c]);
#pragma unroll
      for (int e = 0; e < 2; e++) {
        if (c == 0) asm volatile("mov.b32 %0, %1;" : "=f"(own[e]) : "f"(d[c][e]));
        else own[4 * c + e] += d[c][e];
        own[4 * c + 2 + e] = d[c][4 + e] + d[c][2 + e];
        if (c < 3) asm volatile("mov.b32 %0, %1;" : "=f"(own[4 * c + 4 + e]) : "f"(d[c][30 + e]));
      }
#pragma unroll
      for (int j = 1; j < 4; j++)
        asm volatile("{\n.reg .pred p;\nsetp.lt.s32 p, %3, 4;\n@p st.shared.v2.u32 [%0], {%1, %2};\n}\n" ::"r"(
                         xw + (3 * c + j - 1) * 256),
                     "r"(pack_bf16(d[c][8 * j] + d[c][8 * j - 2], d[c][8 * j + 1] + d[c][8 * j - 1])),
                     "r"(pack_bf16(d[c][8 * j + 4] + d[c][8 * j + 2], d[c][8 * j + 5] + d[c][8 * j + 3])),
                     "r"(c < 3 ? 0 : w4 + j)
                     : "memory");
    };
    named_bar_sync(pp ? 4 + wg : 1 + wg, pp ? 256 : 128);
    CT(1)
    mma(0);
    mma(1);
    wgmma_wait<1>();
    load_h(ho, 2);
    put(0);
    mma(2);
    CT(2)
    wgmma_wait<1>();
    load_h(ho, 3);
    put(1);
    mma(3);
    asm volatile("{\n.reg .pred p;\nsetp.ne.u32 p, %1, 0;\n@p bar.arrive %0, 256;\n}\n" ::"r"(5 - wg), "r"((uint32_t)pp) : "memory");
    CT(3)
    uint32_t sk[8];
    asm volatile("ldmatrix.sync.aligned.m8n8.x4.trans.shared.b16 {%0, %1, %2, %3}, [%4];"
                 : "=r"(sk[0]), "=r"(sk[1]), "=r"(sk[2]), "=r"(sk[3])
                 : "r"(ua + so));
    asm volatile("ldmatrix.sync.aligned.m8n8.x4.trans.shared.b16 {%0, %1, %2, %3}, [%4];"
                 : "=r"(sk[4]), "=r"(sk[5]), "=r"(sk[6]), "=r"(sk[7])
                 : "r"(ua + so + 2048));
    mbar_wait(full + 8 * (~n & 1), (((n + 1) >> 1) & 1) ^ (ch + step < end ? 0 : 1));
    named_bar_sync(1 + wg, 128);
    shift_h(C_SLOT - so);
    wgmma_wait<1>();
    put(2);
    uint32_t dep = 0;
#pragma unroll
    for (int i = 0; i < 8; i++) dep |= sk[i] = mul_bf2(sk[i], dsk | (dsk << 16));
    CT(4)
    wgmma_wait<0>();
    put(3);
    named_bar_sync((1 + wg) | (dep & rt_zero), 128);
    CT(5)
    fetch(ch + 2 * step, n & 1);
    if (wtid == 96 && n) note(bar, CNT_Y2 + (((ch - step) & 127) >= 112));
    uint2 q[12];
#pragma unroll
    for (int i = 0; i < 12; i++) {
      if (i >= 3) {
        asm volatile("ld.shared.v2.u32 {%0, %1}, [%2];" : "=r"(q[i].x), "=r"(q[i].y) : "r"(xg[i % 3] + (i / 3) * 768));
      } else {
        q[i] = make_uint2(0, 0);
        asm volatile("{\n.reg .pred p;\nsetp.gt.s32 p, %3, 2;\n@p ld.shared.v2.u32 {%0, %1}, [%2];\n}\n"
                     : "+r"(q[i].x), "+r"(q[i].y)
                     : "r"(xg[i]), "r"(w4 + i));
      }
    }
    load_h(hs - ho, 0);
    load_h(hs - ho, 1);
    CT(6)
    uint32_t* dst = reinterpret_cast<uint32_t*>(g_y2T + (size_t)ch * S_LEN) + 64 * w4 + (lane ^ 28);
#pragma unroll
    for (int f = 0; f < 4; f++) {
#pragma unroll
      for (int k = 0; k < 3; k++) {
        own[4 * f] += bf_lo(q[3 * f + k].x);
        own[4 * f + 1] += bf_hi(q[3 * f + k].x);
        own[4 * f + 2] += bf_lo(q[3 * f + k].y);
        own[4 * f + 3] += bf_hi(q[3 * f + k].y);
      }
#pragma unroll
      for (int i = 0; i < 2; i++) {
        dst[256 * f + 32 * i] = add_bf2(pack_bf16(own[4 * f + 2 * i], own[4 * f + 2 * i + 1]), sk[2 * f + i]);
      }
    }
    CT(7)
  }
  named_bar_sync(1 + wg, 128);
  if (wtid == 96 && wg) { TD(8) }
  if (wtid == 96) cnt_signal_release(CNT_Y2 + (((ch - step) & 127) >= 112), 1);
  if (wtid == 64) note(bar, CNT_DONE);
  if (wtid == 96 && wg) { TD(9) }
}

__device__ __forceinline__ void attn_producer(const Maps& maps, uint32_t sbase, bool after_qkv, bool to_out,
                                              bool dry) {
  const uint32_t bar = sbase + BAR_OFF;
  const uint32_t q_full = bar + B_QFULL, q_empty = bar + B_QEMPTY;
  const uint32_t k_full = bar + B_KFULL, k_empty = bar + B_KEMPTY, v_full = bar + B_VFULL, v_empty = bar + B_VEMPTY;
  int ndrained = after_qkv ? 0 : G_STAGES;
  auto wait = [&](uint32_t b, uint32_t par) {
    if (!dry) mbar_wait_sleep(b, par);
  };
  auto drained = [&](int upto) {
#pragma unroll 1
    for (; ndrained <= upto; ndrained++) wait(bar + B_GEMPTY + 8 * ndrained, 1);
  };
  uint32_t st = 0, ph = 1, vs = 0, vp = 1;
  int pend_j = -1, pend_h = 0;
  int round = -1, m = -1, h = 0;
  bool last = false;
#pragma unroll 1
  for (;; round++) {
    uint32_t nitem = 0;
    const int tpost = m >= 3 ? m - 1 : m;
#pragma unroll 1
    for (int t = m < 0 ? -1 : 0; t <= m; t++) {
      const int j = (t < m && (round & 1)) ? m - 1 - t : t;
      if (t >= 0) {
        drained(1 + st);
        wait(k_empty + 8 * st, ph);
        if (!dry) {
          mbar_expect_tx(k_full + 8 * st, A_TILE);
          tma_load_3d(sbase + A_K_OFF + st * A_TILE, &maps.k, k_full + 8 * st, 0, j * 128, h * 2);
        }
        if (++st == 2) { st = 0; ph ^= 1; }
      }
      if (pend_j >= 0) {
        drained(3);
        wait(v_empty + 8 * vs, vp);
        if (!dry) {
          mbar_expect_tx(v_full + 8 * vs, A_TILE);
          tma_load_3d(sbase + A_V_OFF + vs * A_TILE, &maps.v, v_full + 8 * vs, 0, pend_j * 128, pend_h * 2);
        }
        if (++vs == 2) { vs = 0; vp ^= 1; }
      }
      pend_j = j;
      pend_h = h;
      if (t == tpost && !last) {
        nitem = dry ? 1 : item_of(maps, round + 1);
        if (round == (dry ? 0 : 3) || blockIdx.x >= 128) {
          nitem = A_ITEMS;
          cnt_wait(CNT_PREP, dry ? 0 : 260);
          if (to_out) {
            cnt_wait(CNT_CTX, dry ? 0 : A_ITEMS);
            asm volatile("cp.async.bulk.prefetch.L2.global [%0], 4096;" ::"l"(maps.ssm_k + (size_t)conv_first(maps) * S_LEN));
            if (!dry)
              asm volatile("cp.async.bulk.prefetch.L2.global [%0], 4096;" ::"l"(g_kvT + (size_t)conv_first(maps) * S_LEN));
          }
        }
        const uint32_t qs = (round + 1) & 1;
        wait(q_empty + 8 * qs, (((round + 1) >> 1) & 1) ^ 1);
        if (round == 1 && after_qkv) wait(bar + B_QDONE, 0);
        if (round <= 0 && after_qkv) {
          if (!dry) { TD(2) }
          cnt_wait(CNT_KV + round + 1, dry ? 0 : 512);
          if (!dry) { TD(3) }
        }
        if (nitem >= A_ITEMS || (round < 0 && after_qkv && !dry)) {
          if (!dry) mbar_arrive(q_full + 8 * qs);
        } else {
          drained(qs);
          if (!dry) {
            mbar_expect_tx(q_full + 8 * qs, A_TILE);
            tma_load_3d_hint(sbase + A_Q_OFF + qs * A_TILE, &maps.q, q_full + 8 * qs, 0, item_m(nitem) * 128,
                             item_h(nitem) * 2, policy_evict_first());
          }
        }
      }
    }
    if (last) break;
    last = nitem >= A_ITEMS;
    m = last ? -1 : item_m(nitem);
    h = item_h(nitem);
  }
}

__device__ __forceinline__ uint32_t attn_consumer(const Maps& maps, uint32_t smem0, uint32_t sn,
                                                  float (&rest)[64], bool after_qkv) {
  PHASE_PROLOGUE
  const uint32_t q_full = bar + B_QFULL, q_empty = bar + B_QEMPTY;
  const uint32_t k_full = bar + B_KFULL, k_empty = bar + B_KEMPTY, v_full = bar + B_VFULL;
  float o[64], s[64];
  uint32_t p[32];
  float e[32];
  uint32_t dep = 0;
  constexpr int MIDJ = 5;
  float l0 = 0.f, l1 = 0.f, b0 = 0.f, b1 = 0.f;
  const int sched_own = 4 + wg, sched_other = 5 - wg;
  if (wg == 1) named_bar_arrive(4, 256);

  const uint32_t qd0 = (uint32_t)make_desc(sbase + A_Q_OFF + wg * 8192, 16, 0, 0);
  const uint32_t kd0 = (uint32_t)make_desc(sbase + A_K_OFF, 16, 0, 0);
  const uint32_t vd0 = (uint32_t)make_desc(sbase + A_V_OFF, 16384, 0, 0);
  constexpr uint64_t DHI = DESC_SW128 | ((uint64_t)(1024 >> 4) << 32);
  constexpr uint32_t DST = A_TILE >> 4;
  auto issue_qk = [&](uint32_t qd, uint32_t kd) {
#pragma unroll
    for (int kk = 0; kk < 8; kk++) {
      const uint32_t off = ((kk >> 2) * 16384 + (kk & 3) * 32) >> 4;
      wgmma_m64n128_ss(s, DHI | (qd + off), DHI | (kd + off), kk != 0);
    }
    wgmma_commit();
  };
  auto issue_pv = [&](uint32_t vd, bool accumulate, int nk) {
#pragma unroll
    for (int kk = 0; kk < 8; kk++) {
      if (kk < nk)
        wgmma_m64n128_rs_tb(o, p[4 * kk], p[4 * kk + 1], p[4 * kk + 2], p[4 * kk + 3], DHI | (vd + kk * 128),
                            accumulate || (kk != 0));
    }
    wgmma_commit();
  };
  auto exp_lo = [&](float& a0, float& a1) {
#pragma unroll
    for (int j = 0; j < 8; j++) {
      e[4 * j] = ex2(s[4 * j]);
      e[4 * j + 1] = ex2(s[4 * j + 1]);
      e[4 * j + 2] = ex2(s[4 * j + 2]);
      e[4 * j + 3] = ex2(s[4 * j + 3]);
      a0 += e[4 * j];
      a0 += e[4 * j + 1];
      a1 += e[4 * j + 2];
      a1 += e[4 * j + 3];
      if (j == MIDJ) dep = (__float_as_uint(a0) | __float_as_uint(a1)) & rt_zero;
    }
  };
  auto pack_lo = [&]() {
#pragma unroll
    for (int j = 0; j < 16; j++) p[j] = pack_bf16(e[2 * j], e[2 * j + 1]);
  };
  auto finish_p = [&](float& a0, float& a1) {
    pack_lo();
#pragma unroll
    for (int j = 8; j < 16; j++) {
      const float e0 = ex2(s[4 * j]), e1 = ex2(s[4 * j + 1]), e2 = ex2(s[4 * j + 2]), e3 = ex2(s[4 * j + 3]);
      a0 += e0;
      a0 += e1;
      a1 += e2;
      a1 += e3;
      p[2 * j] = pack_bf16(e0, e1);
      p[2 * j + 1] = pack_bf16(e2, e3);
      if (j == 8 + MIDJ) dep = __float_as_uint(a0) & rt_zero;
    }
  };
  auto quad_sum = [&](float t) {
    t += __shfl_xor_sync(0xffffffffu, t, 1);
    return t + __shfl_xor_sync(0xffffffffu, t, 2);
  };
  auto write_o = [&](float i0, float i1) {
    st_wait(bar, wg, sn - 1);
    const int st_row = warp * 16 + (lane & 7) + ((lane >> 3) & 1) * 8;
    const uint32_t so = sbase + A_O_OFF + wg * 16384 + st_row * 128;
#pragma unroll
    for (int j = 0; j < 16; j += 2)
      stmatrix_x4(so + (j >> 3) * 8192 + ((((j & 7) + (lane >> 4)) ^ (lane & 7)) << 4),
                  pack_bf16(o[4 * j] * i0, o[4 * j + 1] * i0), pack_bf16(o[4 * j + 2] * i1, o[4 * j + 3] * i1),
                  pack_bf16(o[4 * j + 4] * i0, o[4 * j + 5] * i0), pack_bf16(o[4 * j + 6] * i1, o[4 * j + 7] * i1));
  };
  auto store_o = [&](uint32_t r, int kind) {
    const uint32_t it = item_of(maps, r);
    st_post(bar, wg, wtid, sn, kind, (INPLACE & 1) || kind != ST_BOX2Q ? &maps.o : &maps.c[0], sbase + A_O_OFF + wg * 16384, item_h(it) * 128,
            item_m(it) * 128 + wg * 64, CNT_CTX + (r >> 1));
    sn++;
  };
  auto mask_half = [&](float* sh) {
    const int u = warp * 16 + (lane >> 2) - (lane & 3) * 2;
#pragma unroll
    for (int j = 0; j < 8; j++) {
      if (8 * j > u) sh[4 * j] = -INFINITY;
      if (8 * j + 1 > u) sh[4 * j + 1] = -INFINITY;
      if (8 * j - 8 > u) sh[4 * j + 2] = -INFINITY;
      if (8 * j - 7 > u) sh[4 * j + 3] = -INFINITY;
    }
  };
  ST(0)
  mbar_wait(q_full, 0);
  if (blockIdx.x >= 128) {
    mbar_arrive_if(bar + B_OFREE + 8 * wg, wtid == 0);
    return sn;
  }
  mbar_wait(k_full, 0);
  named_bar_sync(sched_own, 256);
  wgmma_fence();
  issue_qk(qd0, kd0);
  named_bar_arrive(sched_other, 256);
  fence_regs(rest);
#pragma unroll
  for (int i = 0; i < 64; i++) o[i] = rest[i] * Q_SCALE;
  fence_regs(o);
  wgmma_wait<0>();
  fence_regs(s);
  mbar_arrive_if(k_empty, wtid == 32);
  uint32_t g = 0;
  uint32_t rnd = 0;
  int rem = item_m(item_of(maps, 0));
  uint32_t first = 1;
  uint32_t fl = 0;
#define redo (fl & 1)
#define shifted (fl & 2)
  float d0 = 0.f, d1 = 0.f;
  float pi0 = 1.f, pi1 = 1.f;
  ST(1)
  for (;;) {
    if (shifted) {
#pragma unroll
      for (int j = 0; j < 16; j++) {
        s[4 * j] -= d0;
        s[4 * j + 1] -= d0;
        s[4 * j + 2] -= d1;
        s[4 * j + 3] -= d1;
      }
    }
    if (rem == 0 && !redo) {
      mbar_arrive_if(q_empty + 8 * (rnd & 1), wtid == 96);
      rnd++;
      if (wg == 0) mask_half(s);
      else mask_half(s + 32);
    }
    for (;;) {
      const bool kill = rem == 0 && wg == 0;
      const uint32_t kd = kd0 + ((g + 1) & 1) * DST, vd = vd0 + (g & 1) * DST;
      float a0 = 0.f, a1 = 0.f;
      exp_lo(a0, a1);
      fence_regs(e);
      const uint32_t kb = k_full + 8 * ((g + 1) & 1);
      const uint32_t kpar = ((((g + 1) >> 1) & 1) ^ (g == A_STEPS - 1 ? 1u : 0u)) | dep;
      if (!mbar_try(kb, kpar)) mbar_wait(kb, kpar | ((__float_as_uint(a0) | __float_as_uint(a1)) & rt_zero));
      wgmma_wait<0>();
      fence_regs(o);
      if (kill) {
        mbar_arrive_if(kb + (B_VEMPTY - B_KFULL), wtid == 64 && !redo && g > 0);
        fence_regs(e);
        pack_lo();
#pragma unroll
        for (int j = 16; j < 32; j++) asm volatile("mov.u32 %0, 0;" : "=r"(p[j]));
        goto check;
      }
#pragma unroll
      for (int i = 32; i < 64; i++) asm volatile("" : "+f"(s[i])::"memory");
      mbar_arrive_if(kb + (B_VEMPTY - B_KFULL), wtid == 64 && !redo && g > 0);
      finish_p(a0, a1);
      if (__any_sync(0xffffffffu, !(mbar_try(v_full + 8 * (g & 1), ((g >> 1) & 1) | dep) &
                                    mbar_try(q_full + 8 * (rnd & 1), ((rnd >> 1) & 1) | dep)) ||
                                      !(a0 + a1 < 1.0995116e12f) || !(fminf(a0, a1) > (first ? 9.094947e-13f : -1.f)))) {
      check:
        bool bad = !(a0 + a1 < 1.0995116e12f);
        if (first) bad |= !(fminf(quad_sum(a0), quad_sum(a1)) > 9.094947e-13f);
        if (!redo && __any_sync(0xffffffffu, bad)) {
          d0 = d1 = first ? -INFINITY : 0.f;
#pragma unroll
          for (int j = 0; j < 16; j++) {
            if (j < 8 || !kill) {
              d0 = fmaxf(d0, fmaxf(s[4 * j], s[4 * j + 1]));
              d1 = fmaxf(d1, fmaxf(s[4 * j + 2], s[4 * j + 3]));
            }
          }
#pragma unroll
          for (int x = 1; x <= 2; x++) {
            d0 = fmaxf(d0, __shfl_xor_sync(0xffffffffu, d0, x));
            d1 = fmaxf(d1, __shfl_xor_sync(0xffffffffu, d1, x));
          }
          b0 += d0;
          b1 += d1;
          if (!first) {
            const float al0 = ex2(-d0), al1 = ex2(-d1);
            l0 *= al0;
            l1 *= al1;
#pragma unroll
            for (int j = 0; j < 16; j++) {
              o[4 * j] *= al0;
              o[4 * j + 1] *= al0;
              o[4 * j + 2] *= al1;
              o[4 * j + 3] *= al1;
            }
          }
          fl = 3;
          break;
        }
        mbar_wait(v_full + 8 * (g & 1), (g >> 1) & 1);
        mbar_wait(q_full + 8 * (rnd & 1), (rnd >> 1) & 1);
      }
      named_bar_sync(sched_own, 256);
      if (g == A_STEPS - 1) {
        if (first) write_o(pi0, pi1);
        fence_regs(o);
        wgmma_fence();
        issue_pv(vd, !first, 8);
        named_bar_arrive(sched_other, 256);
        if (first) store_o(rnd - 2, ST_BOX2);
        pi0 = rcp(quad_sum(l0 + a0));
        pi1 = rcp(quad_sum(l1 + a1));
        goto done;
      }
      wgmma_fence();
      issue_qk(qd0 + (rnd & 1) * DST, kd);
      if (first) write_o(pi0, pi1);
      fence_regs(o);
      if (kill) {
        wgmma_fence();
        issue_pv(vd, !first, 4);
      } else {
        wgmma_fence();
        issue_pv(vd, !first, 8);
      }
      named_bar_arrive(sched_other, 256);
      fl &= 2;
      l0 += a0;
      l1 += a1;
      if (rem == 0 || first) {
        if (first && (g > 0 || after_qkv)) store_o(g ? rnd - (rem == 0 ? 2 : 1) : 2, g ? ST_BOX2 : ST_BOX2Q);
        first = rem == 0;
        if (first) {
          pi0 = rcp(quad_sum(l0));
          pi1 = rcp(quad_sum(l1));
          l0 = l1 = b0 = b1 = 0.f;
          fl = 0;
          rem = item_m(item_of(maps, rnd)) + 1;
        }
      }
      rem--;
      g++;
      wgmma_wait<1>();
      fence_regs(s);
      mbar_arrive_if(kb + (B_KEMPTY - B_KFULL), wtid == 32);
      ST(g + 1)
      if (rem == 0 || shifted) {
        d0 = b0;
        d1 = b1;
        break;
      }
    }
  }
done:
#undef redo
#undef shifted
  wgmma_wait<0>();
  fence_regs(o);
  write_o(pi0, pi1);
  store_o(3, ST_BOX2L);
  ST(35)
  return sn;
}

constexpr int O_STAGES = 5;
constexpr int O_STAGE_BYTES = 32768;
constexpr int O_Y_OFF = 5 * 32768;
constexpr int O_X_OFF = 6 * 32768 + 2048;
constexpr int O_NK = HDIM / 64;

__device__ __forceinline__ uint32_t out_stage(uint32_t st) { return ((0x43120u >> (4 * st)) & 7) * O_STAGE_BYTES; }

__device__ __forceinline__ void out_producer(const Maps& maps, uint32_t sbase, bool after_attn, bool dry) {
  const uint32_t bar = sbase + BAR_OFF;
  const uint32_t rank = blockIdx.x & 1;
  const int m_tile = maps.id[blockIdx.x][2] & 15, n_tile = maps.id[blockIdx.x][2] >> 4;
  uint32_t stage = 0, phase = 0;
  const int kx = dry ? 0 : 17 + (blockIdx.x >> 1) % 12;
#pragma unroll 1
  for (int ki = 0; ki < (dry ? 1 : O_NK); ki++) {
    const int kt = (ki & 14) * 4 + ((A_ORDER >> ((ki >> 4) * 4)) & 3) * 2 + (ki & 1);
    const uint32_t fb = bar + B_OFULL + 8 * stage, eb = bar + B_OEMPTY + 8 * stage;
    const uint32_t sa = sbase + out_stage(stage);
    if (ki < O_STAGES) {
      constexpr uint32_t LASTB = B_KEMPTY | ((B_QEMPTY + 8) << 8) | ((B_KEMPTY + 8) << 16) | (B_VEMPTY << 24);
      if (ki > 0 && after_attn) mbar_wait_sleep(bar + ((LASTB >> (8 * ki - 8)) & 255), ki == 2);
      mbar_arrive_cluster_if(eb, 0, !dry);
      mbar_arrive_cluster_if(eb, 1, !dry);
    }
    if (ki == (dry ? 0 : 16)) cnt_wait(CNT_CTX + 1, dry ? 0 : A_ITEMS);
    if (ki == kx) {
      if (after_attn && !dry) {
        mbar_wait_sleep(bar + B_OFREE, 0);
        mbar_wait_sleep(bar + B_OFREE + 8, 0);
      }
      if (!dry) {
        mbar_expect_tx(bar + B_OY, 32768);
        tma_load_4d(sbase + O_X_OFF, &maps.ox, bar + B_OY, n_tile * 128, m_tile);
        tma_load_4d(sbase + O_X_OFF + 16384, &maps.ox, bar + B_OY, n_tile * 128 + 64, m_tile);
      }
    }
    if (!dry) {
      mbar_wait_sleep(eb, phase);
      mbar_expect_tx(fb, O_STAGE_BYTES);
      tma_load_2d_mc(sa + 16384 + rank * 8192, &maps.ob, fb, n_tile * 128 + rank * 64, kt * 64, (uint16_t)3);
      tma_load_4d(sa, &maps.oa, fb, kt * 64, m_tile);
    }
    if (++stage == O_STAGES) { stage = 0; phase ^= 1; }
  }
  if (!dry) mbar_wait_sleep(bar + B_OY2, 0);
}

__device__ __forceinline__ void out_side(const Maps& maps, uint32_t smem0, const float (&gv)[4]) {
  PHASE_PROLOGUE
  const int m_tile = maps.id[blockIdx.x][2] & 15, n_tile = maps.id[blockIdx.x][2] >> 4;
  const int w4 = __shfl_sync(0xffffffffu, warp, 0);
  if (w4 == 0) {
    if (elect_one()) {
      mbar_expect_tx(bar + B_OY, 32768 - 4096);
      TD(10)
      GS(0)
      cnt_wait(CNT_Y2, DM - 128);
      GS(1)
      TD(7)
      for (const uint32_t t = clock(); (uint32_t)clock() - t < (blockIdx.x & 14) * 200;) __nanosleep(32);
      TD(11)
      GS(2)
      fence_proxy_async();
      tma_load_2d(sbase + O_Y_OFF, &maps.y, bar + B_OY, m_tile * 128, n_tile * 128);
      tma_load_2d(sbase + O_Y_OFF + 16384, &maps.y, bar + B_OY, m_tile * 128 + 64, n_tile * 128);
    }
  }
  mbar_wait_sleep(bar + B_OY, 0);
  const int st_row = warp * 16 + (lane & 7) + ((lane >> 3) & 1) * 8;
  const int mrow = (lane & 7) + ((lane >> 4) & 1) * 8;
  const int mchunk = warp * 2 + ((lane >> 3) & 1);
  const uint32_t xrow = sbase + O_X_OFF + st_row * 128;
  const uint32_t yrow = sbase + O_Y_OFF + mrow * 128 + ((mchunk ^ (lane & 7)) << 4);
  uint32_t y[7][4], x[7][4], om[4];
#pragma unroll
  for (int i = 0; i < 4; i++) om[i] = pack_bf16(1.0f - gv[i], 1.0f - gv[i]);
  auto xa = [&](int h, int i) { return xrow + h * 8192 + (i >> 2) * 16384 + ((((i & 3) * 2 + (lane >> 4)) ^ (lane & 7)) << 4); };
  auto load = [&](int r, int h, int i) {
    ldsm4t(y[r], yrow + h * 16384 + i * 2048);
    asm volatile("ldmatrix.sync.aligned.m8n8.x4.shared.b16 {%0, %1, %2, %3}, [%4];"
                 : "=r"(x[r][0]), "=r"(x[r][1]), "=r"(x[r][2]), "=r"(x[r][3])
                 : "r"(xa(h, i)));
  };
  auto store = [&](int r, int h, int i, uint32_t om0, uint32_t om1) {
    stmatrix_x4(xa(h, i), mul_bf2(om0, mul_bf2(x[r][0], y[r][0])), mul_bf2(om1, mul_bf2(x[r][1], y[r][1])),
                mul_bf2(om0, mul_bf2(x[r][2], y[r][2])), mul_bf2(om1, mul_bf2(x[r][3], y[r][3])));
  };
  if (wtid == 0) { TD(12) GS(3) }
#pragma unroll 1
  for (int h = 0; h < 2; h++) {
#pragma unroll
    for (int i = 0; i < 7; i++) load(i, h, i);
#pragma unroll
    for (int i = 0; i < 7; i++) store(i, h, i, h ? om[2] : om[0], h ? om[3] : om[1]);
  }
  if (wtid == 0) { TD(4) GS(4) }
  if (w4 == 0) {
    if (elect_one()) {
      mbar_expect_tx(bar + B_OY2, 4096);
      cnt_wait(CNT_Y2 + 1, 128);
      GS(5)
      for (int i = 0; i < 2; i++)
        tma_load_2d(sbase + O_Y_OFF + i * 16384 + 112 * 128, &maps.y2, bar + B_OY2, m_tile * 128 + i * 64,
                    n_tile * 128 + 112);
    }
  }
  mbar_wait_sleep(bar + B_OY2, 0);
#pragma unroll
  for (int h = 0; h < 2; h++) load(h, h, 7);
#pragma unroll
  for (int h = 0; h < 2; h++) store(h, h, 7, om[2 * h], om[2 * h + 1]);
  __syncwarp();
  mbar_arrive_if(bar + B_OY + 8, lane == 0);
  if (wtid == 0) { TD(13) GS(6) }
#pragma unroll
  for (int i = 0; i < 4; i++) {
    const int h = i >> 1, c = i & 1;
    named_bar_sync(6 + i, 256);
    if (elect_one()) {
      fence_proxy_async();
      tma_store_4d(&maps.oc, sbase + O_X_OFF + c * 16384 + h * 8192 + w4 * 2048, n_tile * 128 + c * 64, 2 * w4,
                   2 * m_tile + h);
      tma_store_commit();
    }
  }
}

__device__ __forceinline__ void out_gemm(const Maps& maps, uint32_t smem0) {
  PHASE_PROLOGUE
  const int m_tile = maps.id[blockIdx.x][2] & 15;
  float acc[2][64];
  undef_regs(acc[0]);
  undef_regs(acc[1]);
  uint32_t stage = 0, phase = 0, prev_stage = 0;
  GT(gti++)
  const float* gp = g_gate + m_tile * 128 + warp * 2 + (lane >> 2) * 8;
  const float gv[4] = {__ldcg(gp), __ldcg(gp + 1), __ldcg(gp + 64), __ldcg(gp + 65)};
  if (wg == 1) {
    out_side(maps, smem0, gv);
    return;
  }
  constexpr uint64_t DHI = DESC_SW128 | ((uint64_t)(1024 >> 4) << 32);
#pragma unroll 1
  for (int kt = 0; kt < O_NK - 1; kt++) {
    uint32_t da = (uint32_t)make_desc(sbase + out_stage(stage), 16, 0, 0);
    uint32_t db = (uint32_t)make_desc(sbase + out_stage(stage) + 16384, 8192, 0, 0);
    asm volatile("" : "+r"(da), "+r"(db));
    mbar_wait(bar + B_OFULL + 8 * stage, phase);
    GT(gti++)
    constexpr int OWAIT = 2;
#pragma unroll
    for (int kk = 0; kk < 4; kk++) {
      wgmma_wait<OWAIT>();
      if (kk == OWAIT)
        mbar_arrive_cluster_if(bar + B_OEMPTY + 8 * prev_stage, wtid >> 6,
                               (wtid & 63) == 32 && kt > 0 && kt - 1 + O_STAGES < O_NK);
      wgmma_fence();
      wgmma_m64n128_ss_tb(acc[0], DHI | (da + kk * 2), DHI | (db + kk * 128), (kt | kk) != 0);
      wgmma_m64n128_ss_tb(acc[1], DHI | (da + 512 + kk * 2), DHI | (db + kk * 128), (kt | kk) != 0);
      wgmma_commit();
    }
    prev_stage = stage;
    if (++stage == O_STAGES) { stage = 0; phase ^= 1; }
  }
  {
    const uint32_t da = (uint32_t)make_desc(sbase + out_stage((O_NK - 1) % O_STAGES), 16, 0, 0);
    const uint32_t db = (uint32_t)make_desc(sbase + out_stage((O_NK - 1) % O_STAGES) + 16384, 8192, 0, 0);
    mbar_wait(bar + B_OFULL + 8 * ((O_NK - 1) % O_STAGES), ((O_NK - 1) / O_STAGES) & 1);
    GT(gti++)
#pragma unroll
    for (int h = 0; h < 2; h++) {
      wgmma_fence();
#pragma unroll
      for (int kk = 0; kk < 4; kk++)
        wgmma_m64n128_ss_tb(acc[h], DHI | (da + h * 512 + kk * 2), DHI | (db + kk * 128), 1);
      wgmma_commit();
    }
  }
  if (tid == 0) { TD(14) }
  const int st_row = warp * 16 + (lane & 7) + ((lane >> 3) & 1) * 8;
  const uint32_t rowa = sbase + O_X_OFF + st_row * 128;
  auto oa = [&](int i) { return rowa + (i >> 3) * 8192 + (i & 4) * 4096 + ((((i & 3) * 2 + (lane >> 4)) ^ (st_row & 7)) << 4); };
  uint32_t b[16][4];
  mbar_wait(bar + B_OY + 8, 0);
#pragma unroll
  for (int i = 0; i < 16; i++)
    asm volatile("ldmatrix.sync.aligned.m8n8.x4.shared.b16 {%0, %1, %2, %3}, [%4];"
                 : "=r"(b[i][0]), "=r"(b[i][1]), "=r"(b[i][2]), "=r"(b[i][3])
                 : "r"(oa(i)));
  uint32_t gg[4];
#pragma unroll
  for (int i = 0; i < 4; i++) gg[i] = pack_bf16(gv[i], gv[i]);
#pragma unroll
  for (int i = 0; i < 16; i++) {
    const int h = i >> 3;
    if (i == 0) wgmma_wait<1>();
    if (i == 8) wgmma_wait<0>();
    if (i % 8 == 0) fence_regs(acc[h]);
    const float* a = acc[h] + 8 * (i & 7);
    const uint32_t gg0 = gg[2 * h], gg1 = gg[2 * h + 1];
    stmatrix_x4(oa(i), fma_bf2(gg0, pack_bf16(a[0], a[1]), b[i][0]), fma_bf2(gg1, pack_bf16(a[2], a[3]), b[i][1]),
                fma_bf2(gg0, pack_bf16(a[4], a[5]), b[i][2]), fma_bf2(gg1, pack_bf16(a[6], a[7]), b[i][3]));
    if (i % 4 == 3) named_bar_arrive(6 + i / 4, 256);
  }
  GT(gti++)
}

__device__ __noinline__ void leave_kernel(int mask) {
  if (!(mask & 4)) return;
  if (atomicAdd(g_cnt + CNT_DONE * 32, 1u) == 2 * gridDim.x - 1) {
    for (int i = 0; i < CNT_N; i++) g_cnt[i * 32] = 0;
  }
}

__device__ __noinline__ void side_jobs(const Maps& maps, uint32_t sbase) {
  const int w12 = __shfl_sync(0xffffffffu, threadIdx.x >> 5, 0);
  gate_rows(maps, sbase, (blockIdx.x - 128) * 12 + w12, w12, threadIdx.x & 31);
  fence_proxy_async();
  __syncthreads();
  if (threadIdx.x == 320) cnt_signal_release(CNT_PREP, 1);
}

__global__ void __launch_bounds__(384, 1) fused_kernel(int mask, const __grid_constant__ Maps maps) {
  extern __shared__ __align__(1024) uint8_t smem_raw[];
  {
    const uint32_t sbase = __shfl_sync(0xffffffffu, smem_u32(smem_raw), 0);
    const uint32_t bar = sbase + BAR_OFF;
    const int tid = threadIdx.x;
    const bool do_qkv = (mask & 1) && blockIdx.x < 128;
    TL(0, 0)
    if (__shfl_sync(0xffffffffu, tid >> 5, 0) == 1 && do_qkv) {
      if (elect_one()) {
        for (int i = 0; i < G_STAGES; i++) mbar_init(bar + B_GFULL + 8 * i, 1);
        fence_barrier_init();
        qkv_producer(maps, sbase, true);
      }
    }
    if (tid == 0) {
      for (int i = 0; i < G_STAGES; i++) {
        mbar_init(bar + B_GEMPTY + 8 * i, 2);
        mbar_init(bar + B_SFULL + 8 * i, 4);
        mbar_init(bar + B_SFREE + 8 * i, 1);
      }
      for (int i = 0; i < 2; i++) {
        mbar_init(bar + B_OFREE + 8 * i, 1);
        mbar_init(bar + B_QFULL + 8 * i, 1);
        mbar_init(bar + B_QEMPTY + 8 * i, 2);
        mbar_init(bar + B_KFULL + 8 * i, 1);
        mbar_init(bar + B_KEMPTY + 8 * i, 2);
        mbar_init(bar + B_VFULL + 8 * i, 1);
        mbar_init(bar + B_VEMPTY + 8 * i, 2);
      }
      for (int i = 0; i < O_STAGES; i++) {
        mbar_init(bar + B_OFULL + 8 * i, 1);
        mbar_init(bar + B_OEMPTY + 8 * i, 2);
      }
      mbar_init(bar + B_OY, 2);
      mbar_init(bar + B_OY2, 1);
      mbar_init(bar + B_OY + 8, 4);
      mbar_init(bar + B_QDONE, 2);
      for (int i = 0; i < 8; i++) mbar_init(bar + B_CFULL + 8 * i, 1);
      for (int i = 0; i < CNT_N; i++) asm volatile("st.shared.u32 [%0], 0;" ::"r"(bar + B_PEND + 4 * i) : "memory");
      fence_barrier_init();
    }
    __syncthreads();
    asm volatile("barrier.cluster.arrive.relaxed.aligned;" ::: "memory");
    if ((mask & 1) && blockIdx.x >= 128) side_jobs(maps, sbase);
  }
  uint32_t smem0 = smem_u32(smem_raw);
  PHASE_PROLOGUE
  const bool do_qkv = (mask & 1) && blockIdx.x < 128, do_out = (mask & 4) && blockIdx.x < 128;
  TL(0, 1)

  if (wg != 2) {
    reg_alloc<232>();
    uint32_t sn = 0;
    float o[64];
    if (do_qkv) {
      sn = qkv_consumer(maps, smem_u32(smem_raw), mask & 2, o);
    } else {
      undef_regs(o);
    }
    TL(0, 2) TL(1, 0) TL(1, 1)
    asm volatile("barrier.cluster.wait.acquire.aligned;" ::: "memory");
    if (mask & 2) {
      sn = attn_consumer(maps, smem_u32(smem_raw), sn, o, mask & 1);
      TL(2, 0)
      if ((mask & 4) && blockIdx.x < 128 && __shfl_sync(0xffffffffu, threadIdx.x, 0) < 128) {
        named_bar_arrive(3, 256);
      } else {
        named_bar_sync(3, 256);
        const uint32_t b2 = blockIdx.x * 2 + (threadIdx.x >> 7);
        const bool fused = mask & 4, mainc = blockIdx.x < 128;
        const uint32_t first = __shfl_sync(0xffffffffu, !fused ? b2 : mainc ? conv_first(maps) : (b2 - 255) * 128 - C_SIDE, 0);
        conv_consumer(maps, smem_u32(smem_raw), first, !fused ? 264 : mainc ? 16 : 1,
                      !fused ? DM : (first | 127) + 1 - (mainc ? C_SIDE : 0));
      }
      TL(1, 2) TL(2, 1) TL(2, 2)
    }
    TL(3, 0) TL(3, 1)
    if ((mask & 4) && blockIdx.x < 128) out_gemm(maps, smem_u32(smem_raw));
    if (!(mask & 2) || blockIdx.x >= 128) {
      uint32_t smem0 = smem_u32(smem_raw);
      PHASE_PROLOGUE
      st_wait(bar, wg, sn - 2);
      st_post(bar, wg, wtid, sn, ST_END, nullptr, 0, 0, 0, -1);
    }
    tma_store_wait_read<0>();
    TL2(3, 2)
  } else {
    reg_dealloc<40>();
    asm volatile("barrier.cluster.wait.acquire.aligned;" ::: "memory");
    const int w = __shfl_sync(0xffffffffu, tid >> 5, 0) - 8;
    if (w < 2) {
      if (do_qkv) prep_agent(maps, sbase, w, lane);
      if (elect_one()) store_agent(bar, w);
    } else {
      if (elect_one()) {
        const bool dry = w == 2;
        if (do_qkv && !dry) qkv_producer(maps, sbase, false);
        if (mask & 2) attn_producer(maps, sbase, do_qkv, do_out, dry);
        if (do_out) out_producer(maps, sbase, mask & 2, dry);
        if (dry) { TD(5) }
      }
      __syncwarp();
      if (w == 2) publisher(bar, tid & 31, !(mask & 2) ? 2 : do_out ? 3 : 4);
      if ((tid & 31) == 0) leave_kernel(mask);
    }
  }
}

typedef CUresult (*PFN_tmapEncode)(CUtensorMap*, CUtensorMapDataType, cuuint32_t, void*, const cuuint64_t*,
                                   const cuuint64_t*, const cuuint32_t*, const cuuint32_t*, CUtensorMapInterleave,
                                   CUtensorMapSwizzle, CUtensorMapL2promotion, CUtensorMapFloatOOBfill);
static PFN_tmapEncode s_encode = nullptr;

static void make_map_2d(CUtensorMap* m, const void* ptr, int rows, int cols, int box_rows) {
  cuuint64_t dims[2] = {(cuuint64_t)cols, (cuuint64_t)rows};
  cuuint64_t strides[1] = {(cuuint64_t)cols * 2};
  cuuint32_t box[2] = {64, (cuuint32_t)box_rows};
  cuuint32_t es[2] = {1, 1};
  s_encode(m, CU_TENSOR_MAP_DATA_TYPE_BFLOAT16, 2, const_cast<void*>(ptr), dims, strides, box, es,
           CU_TENSOR_MAP_INTERLEAVE_NONE, CU_TENSOR_MAP_SWIZZLE_128B, CU_TENSOR_MAP_L2_PROMOTION_L2_256B,
           CU_TENSOR_MAP_FLOAT_OOB_FILL_NONE);
}
static void make_map_3d(CUtensorMap* m, const void* ptr, int rows, int cols, int box_rows, int box_chunks) {
  cuuint64_t dims[3] = {64, (cuuint64_t)rows, (cuuint64_t)(cols / 64)};
  cuuint64_t strides[2] = {(cuuint64_t)cols * 2, 128};
  cuuint32_t box[3] = {64, (cuuint32_t)box_rows, (cuuint32_t)box_chunks};
  cuuint32_t es[3] = {1, 1, 1};
  s_encode(m, CU_TENSOR_MAP_DATA_TYPE_BFLOAT16, 3, const_cast<void*>(ptr), dims, strides, box, es,
           CU_TENSOR_MAP_INTERLEAVE_NONE, CU_TENSOR_MAP_SWIZZLE_128B, CU_TENSOR_MAP_L2_PROMOTION_L2_256B,
           CU_TENSOR_MAP_FLOAT_OOB_FILL_NONE);
}

static void make_map_4d(CUtensorMap* m, const void* ptr, int rows, int cols, int b2, int groups) {
  cuuint64_t dims[4] = {(cuuint64_t)cols, 8, 8, (cuuint64_t)(rows / 64)};
  cuuint64_t strides[3] = {(cuuint64_t)cols * 16, (cuuint64_t)cols * 2, (cuuint64_t)cols * 128};
  cuuint32_t box[4] = {64, 8, (cuuint32_t)b2, (cuuint32_t)groups};
  cuuint32_t es[4] = {1, 1, 1, 1};
  s_encode(m, CU_TENSOR_MAP_DATA_TYPE_BFLOAT16, 4, const_cast<void*>(ptr), dims, strides, box, es,
           CU_TENSOR_MAP_INTERLEAVE_NONE, CU_TENSOR_MAP_SWIZZLE_128B, CU_TENSOR_MAP_L2_PROMOTION_L2_256B,
           CU_TENSOR_MAP_FLOAT_OOB_FILL_NONE);
}

static cudaLaunchConfig_t fused_cfg(cudaLaunchAttribute* at) {
  cudaLaunchConfig_t cfg = {};
  cfg.gridDim = dim3(132);
  cfg.blockDim = dim3(384);
  cfg.dynamicSmemBytes = SMEM_BYTES;
  cfg.stream = cudaStreamPerThread;
  at[0].id = cudaLaunchAttributeClusterDimension;
  at[0].val.clusterDim.x = 2;
  at[0].val.clusterDim.y = 1;
  at[0].val.clusterDim.z = 1;
  cfg.attrs = at;
  cfg.numAttrs = 1;
  return cfg;
}

extern "C" void kernel_launch(void* const* d_in, const int* in_sizes, int n_in, void* d_out, int out_size) {
  const bf16* x = (const bf16*)d_in[0];
  const bf16* ckv = (const bf16*)d_in[1];
  const bf16* wq = (const bf16*)d_in[2];
  const bf16* wuk = (const bf16*)d_in[3];
  const bf16* wuv = (const bf16*)d_in[4];
  const bf16* wo = (const bf16*)d_in[5];
  const bf16* bk = (const bf16*)d_in[7];
  const bf16* bv = (const bf16*)d_in[8];
  const bf16* shift_k = (const bf16*)d_in[9];
  const bf16* ssm_k = (const bf16*)d_in[10];
  const bf16* ssm_D = (const bf16*)d_in[11];
  const bf16* gate_w = (const bf16*)d_in[12];
  bf16* out = (bf16*)d_out;

  static void *pq = nullptr, *pk = nullptr, *pv = nullptr, *pctx = nullptr, *pb = nullptr;
  static int max_clusters = 0;
  if (!s_encode) {
    void* fn = nullptr;
    cudaDriverEntryPointQueryResult qres;
    cudaGetDriverEntryPoint("cuTensorMapEncodeTiled", &fn, cudaEnableDefault, &qres);
    s_encode = (PFN_tmapEncode)fn;
    cudaGetSymbolAddress(&pq, g_q);
    cudaGetSymbolAddress(&pk, g_k);
    cudaGetSymbolAddress(&pv, g_v);
    cudaGetSymbolAddress(&pctx, g_ctx);
    cudaGetSymbolAddress(&pb, g_y2T);
    cudaFuncSetAttribute(fused_kernel, cudaFuncAttributeMaxDynamicSharedMemorySize, SMEM_BYTES);
    cudaLaunchAttribute at[1];
    cudaLaunchConfig_t cfg = fused_cfg(at);
    if (cudaOccupancyMaxActiveClusters(&max_clusters, fused_kernel, &cfg) != cudaSuccess) max_clusters = 0;
  }

  Maps all = {};
  make_map_2d(&all.a[0], x, S_LEN, DM, 128);
  make_map_2d(&all.a[1], ckv, S_LEN, DC, 128);
  make_map_3d(&all.b[0], wq, DM, HDIM, 64, 4);
  make_map_3d(&all.b[1], wuk, DC, HDIM, 64, 4);
  make_map_3d(&all.b[2], wuv, DC, HDIM, 64, 4);
  make_map_2d(&all.c[0], pq, S_LEN, HDIM, 64);
  make_map_2d(&all.c[1], pk, S_LEN, HDIM, 64);
  make_map_2d(&all.c[2], pv, S_LEN, HDIM, 64);
  make_map_3d(&all.q, pq, S_LEN, HDIM, 128, 2);
  make_map_3d(&all.k, pk, S_LEN, HDIM, 128, 2);
  make_map_3d(&all.v, pv, S_LEN, HDIM, 128, 2);
  make_map_2d(&all.o, pctx, S_LEN, HDIM, 64);
  all.ssm_k = ssm_k;
  all.ssm_D = ssm_D;
  make_map_4d(&all.oa, pctx, S_LEN, HDIM, 8, 2);
  make_map_4d(&all.ox, x, S_LEN, DM, 8, 2);
  make_map_2d(&all.ob, wo, HDIM, DM, 64);
  make_map_4d(&all.oc, out, S_LEN, DM, 2, 1);
  make_map_2d(&all.y, pb, DM, S_LEN, 112);
  make_map_2d(&all.y2, pb, DM, S_LEN, 16);

  make_map_2d(&all.bk, bk, S_LEN, DM, 35);
  make_map_2d(&all.bv, bv, S_LEN, DM, 32);
  for (int b = 0; b < 128; b++) {
    const int c = b >> 1, r = b & 1;
    const int G = c < 4 ? 0 : c < 36 ? (c - 4) % 8 : 1 + (c - 36) % 7;
    const int i = c < 4 ? 4 + c : c < 36 ? (c - 4) / 8 : 4 + (c - 36) / 7;
    all.id[b][0] = r + 2 * (i & 1) + 4 * (G & 3) + 16 * (i >> 1) + 64 * (G >> 2);
    all.id[b][1] = r + 2 * i + 16 * G;
    all.id[b][2] = r + 2 * G + 16 * i;
  }
  all.shift_k = shift_k;
  all.x = x;
  all.gate_w = gate_w;
  cudaLaunchAttribute at[1];
  cudaLaunchConfig_t cfg = fused_cfg(at);
  if (max_clusters >= 66) {
    cudaLaunchKernelEx(&cfg, fused_kernel, 7, all);
  } else {
    for (int m = 1; m <= 4; m <<= 1) cudaLaunchKernelEx(&cfg, fused_kernel, m, all);
  }
}
```

```cpp
#include <cuda_runtime.h>
#include <cuda_bf16.h>
#include <cuda.h>
#include <stdint.h>

typedef __nv_bfloat16 bf16;
#define INPLACE 3

constexpr int S_LEN = 2048;
constexpr int DM = 1024;
constexpr int NH = 32;
constexpr int HD = 128;
constexpr int DC = 512;
constexpr int HDIM = NH * HD;

__device__ __align__(1024) bf16 g_q[S_LEN * HDIM];
__device__ __align__(1024) bf16 g_k[S_LEN * HDIM];
__device__ __align__(1024) bf16 g_v[S_LEN * HDIM];
#define g_ctx g_q
__device__ __align__(1024) bf16 g_kvT[DM * S_LEN];
#define g_y2T g_kvT
__device__ __align__(1024) float g_gate[S_LEN];
enum { CNT_KV = 0, CNT_PREP = CNT_KV + 2, CNT_CTX, CNT_Y2 = CNT_CTX + 2, CNT_DONE = CNT_Y2 + 2, CNT_N };
__device__ unsigned int g_cnt[CNT_N * 32];

#define TL(k, i)
#define TL2(k, i)
#define TD(i)
#define CLK_DECL
#define CLK_SAMPLE
#define CLK_END
#define CT(i)
#define GT(i)
#define GS(i)
#define GA(i)
#define ST(i)

__device__ __forceinline__ uint32_t smem_u32(const void* p) { return (uint32_t)__cvta_generic_to_shared(p); }

__device__ __forceinline__ void mbar_init(uint32_t bar, uint32_t count) {
  asm volatile("mbarrier.init.shared::cta.b64 [%0], %1;" ::"r"(bar), "r"(count));
}
__device__ __forceinline__ void mbar_expect_tx(uint32_t bar, uint32_t bytes) {
  asm volatile("mbarrier.arrive.expect_tx.shared::cta.b64 _, [%0], %1;" ::"r"(bar), "r"(bytes) : "memory");
}
__device__ __forceinline__ void mbar_arrive(uint32_t bar) {
  asm volatile("mbarrier.arrive.shared::cta.b64 _, [%0];" ::"r"(bar) : "memory");
}
__device__ __forceinline__ void mbar_wait(uint32_t bar, uint32_t parity) {
  uint32_t done;
  uint32_t spins = 0;
  do {
    asm volatile(
        "{\n.reg .pred p;\n"
        "mbarrier.try_wait.parity.shared::cta.b64 p, [%1], %2;\n"
        "selp.u32 %0, 1, 0, p;\n}\n"
        : "=r"(done)
        : "r"(bar), "r"(parity)
        : "memory");
    if (++spins > (1u << 22)) break;
  } while (!done);
}
__device__ __forceinline__ bool mbar_try(uint32_t bar, uint32_t parity) {
  uint32_t done;
  asm volatile(
      "{\n.reg .pred p;\n"
      "mbarrier.try_wait.parity.shared::cta.b64 p, [%1], %2;\n"
      "selp.u32 %0, 1, 0, p;\n}\n"
      : "=r"(done)
      : "r"(bar), "r"(parity)
      : "memory");
  return done != 0;
}
__device__ __forceinline__ bool elect_one() {
  uint32_t pred;
  asm volatile("{\n.reg .pred p;\nelect.sync _|p, 0xffffffff;\nselp.u32 %0, 1, 0, p;\n}\n" : "=r"(pred));
  return pred != 0;
}
__device__ __forceinline__ void mbar_arrive_if(uint32_t bar, bool pred) {
  asm volatile(
      "{\n.reg .pred p;\nsetp.ne.b32 p, %1, 0;\n"
      "@p mbarrier.arrive.shared::cta.b64 _, [%0];\n}\n" ::"r"(bar),
      "r"((uint32_t)pred)
      : "memory");
}
__device__ __forceinline__ void mbar_wait_sleep(uint32_t bar, uint32_t parity) {
  uint32_t done;
  uint32_t spins = 0;
  do {
    asm volatile(
        "{\n.reg .pred p;\n"
        "mbarrier.try_wait.parity.shared::cta.b64 p, [%1], %2, %3;\n"
        "selp.u32 %0, 1, 0, p;\n}\n"
        : "=r"(done)
        : "r"(bar), "r"(parity), "r"(20000u)
        : "memory");
    if (++spins > (1u << 16)) break;
  } while (!done);
}
__device__ __forceinline__ void fence_barrier_init() {
  asm volatile("fence.mbarrier_init.release.cluster;" ::: "memory");
}
__device__ __forceinline__ void fence_proxy_async() {
  asm volatile("fence.proxy.async.shared::cta;" ::: "memory");
}
__device__ __forceinline__ void named_bar_sync(int id, int nthreads) {
  asm volatile("bar.sync %0, %1;" ::"r"(id), "r"(nthreads) : "memory");
}
__device__ __forceinline__ void named_bar_arrive(int id, int nthreads) {
  asm volatile("bar.arrive %0, %1;" ::"r"(id), "r"(nthreads) : "memory");
}
__device__ __forceinline__ void tma_load_2d(uint32_t dst, const CUtensorMap* m, uint32_t bar, int c0, int c1) {
  asm volatile(
      "cp.async.bulk.tensor.2d.shared::cluster.global.mbarrier::complete_tx::bytes [%0], [%1, {%3, %4}], [%2];" ::"r"(dst),
      "l"(reinterpret_cast<uint64_t>(m)), "r"(bar), "r"(c0), "r"(c1)
      : "memory");
}
__device__ __forceinline__ void tma_load_3d(uint32_t dst, const CUtensorMap* m, uint32_t bar, int c0, int c1, int c2) {
  asm volatile(
      "cp.async.bulk.tensor.3d.shared::cluster.global.mbarrier::complete_tx::bytes [%0], [%1, {%3, %4, %5}], [%2];" ::"r"(dst),
      "l"(reinterpret_cast<uint64_t>(m)), "r"(bar), "r"(c0), "r"(c1), "r"(c2)
      : "memory");
}
__device__ __forceinline__ void tma_store_2d(const CUtensorMap* m, uint32_t src, int c0, int c1) {
  asm volatile("cp.async.bulk.tensor.2d.global.shared::cta.bulk_group [%0, {%2, %3}], [%1];" ::"l"(
                   reinterpret_cast<uint64_t>(m)),
               "r"(src), "r"(c0), "r"(c1)
               : "memory");
}
__device__ __forceinline__ void tma_load_4d(uint32_t dst, const CUtensorMap* m, uint32_t bar, int c0, int tile) {
  asm volatile(
      "cp.async.bulk.tensor.4d.shared::cluster.global.mbarrier::complete_tx::bytes [%0], [%1, {%3, %4, %4, %5}], [%2];" ::"r"(dst),
      "l"(reinterpret_cast<uint64_t>(m)), "r"(bar), "r"(c0), "r"(0), "r"(2 * tile)
      : "memory");
}
__device__ __forceinline__ void tma_store_4d(const CUtensorMap* m, uint32_t src, int c0, int c2, int group) {
  asm volatile("cp.async.bulk.tensor.4d.global.shared::cta.bulk_group [%0, {%2, %3, %4, %5}], [%1];" ::"l"(
                   reinterpret_cast<uint64_t>(m)),
               "r"(src), "r"(c0), "r"(0), "r"(c2), "r"(group)
               : "memory");
}
__device__ __forceinline__ void bulk_load(uint32_t dst, const void* src, uint32_t bytes, uint32_t bar) {
  asm volatile("cp.async.bulk.shared::cluster.global.mbarrier::complete_tx::bytes [%0], [%1], %2, [%3];" ::"r"(dst),
               "l"(src), "r"(bytes), "r"(bar)
               : "memory");
}
__device__ __forceinline__ void tma_load_2d_mc(uint32_t dst, const CUtensorMap* m, uint32_t bar, int c0, int c1,
                                               uint16_t mask) {
  asm volatile(
      "cp.async.bulk.tensor.2d.shared::cluster.global.mbarrier::complete_tx::bytes.multicast::cluster [%0], [%1, {%3, "
      "%4}], [%2], %5;" ::"r"(dst),
      "l"(reinterpret_cast<uint64_t>(m)), "r"(bar), "r"(c0), "r"(c1), "h"(mask)
      : "memory");
}
__device__ __forceinline__ void mbar_arrive_cluster_if(uint32_t bar, uint32_t cta, bool pred) {
  asm volatile(
      "{\n.reg .b32 ra;\n.reg .pred p;\nsetp.ne.b32 p, %2, 0;\n"
      "mapa.shared::cluster.u32 ra, %0, %1;\n"
      "@p mbarrier.arrive.shared::cluster.b64 _, [ra];\n}\n" ::"r"(bar),
      "r"(cta), "r"((uint32_t)pred)
      : "memory");
}
__device__ __forceinline__ uint64_t policy_evict_first() {
  uint64_t pol;
  asm volatile("createpolicy.fractional.L2::evict_first.b64 %0, 1.0;" : "=l"(pol));
  return pol;
}
__device__ __forceinline__ void tma_load_2d_hint(uint32_t dst, const CUtensorMap* m, uint32_t bar, int c0, int c1,
                                                 uint64_t pol) {
  asm volatile(
      "cp.async.bulk.tensor.2d.shared::cluster.global.mbarrier::complete_tx::bytes.L2::cache_hint [%0], [%1, {%3, %4}], "
      "[%2], %5;" ::"r"(dst),
      "l"(reinterpret_cast<uint64_t>(m)), "r"(bar), "r"(c0), "r"(c1), "l"(pol)
      : "memory");
}
__device__ __forceinline__ void tma_load_3d_hint(uint32_t dst, const CUtensorMap* m, uint32_t bar, int c0, int c1,
                                                 int c2, uint64_t pol) {
  asm volatile(
      "cp.async.bulk.tensor.3d.shared::cluster.global.mbarrier::complete_tx::bytes.L2::cache_hint [%0], [%1, {%3, %4, "
      "%5}], [%2], %6;" ::"r"(dst),
      "l"(reinterpret_cast<uint64_t>(m)), "r"(bar), "r"(c0), "r"(c1), "r"(c2), "l"(pol)
      : "memory");
}
__device__ __forceinline__ void bulk_load_hint(uint32_t dst, const void* src, uint32_t bytes, uint32_t bar, uint64_t pol) {
  asm volatile(
      "cp.async.bulk.shared::cluster.global.mbarrier::complete_tx::bytes.L2::cache_hint [%0], [%1], %2, [%3], %4;" ::"r"(dst),
      "l"(src), "r"(bytes), "r"(bar), "l"(pol)
      : "memory");
}
__device__ __forceinline__ void cnt_signal_release(int which, uint32_t n) {
  asm volatile("red.release.gpu.global.add.u32 [%0], %1;" ::"l"(g_cnt + which * 32), "r"(n) : "memory");
}
__device__ __forceinline__ void cnt_wait(int which, uint32_t target) {
  uint32_t v, spins = 0;
  while (true) {
    asm volatile("ld.acquire.gpu.global.u32 %0, [%1];" : "=r"(v) : "l"(g_cnt + which * 32) : "memory");
    if (v >= target || ++spins > (1u << 18)) break;
    __nanosleep(64);
  }
  asm volatile("fence.proxy.async.global;" ::: "memory");
}
__device__ __forceinline__ void tma_store_commit() { asm volatile("cp.async.bulk.commit_group;" ::: "memory"); }
template <int N>
__device__ __forceinline__ void tma_store_wait_read() {
  asm volatile("cp.async.bulk.wait_group.read %0;" ::"n"(N) : "memory");
}
template <int N>
__device__ __forceinline__ void tma_store_wait() {
  asm volatile("cp.async.bulk.wait_group %0;" ::"n"(N) : "memory");
}
__device__ __forceinline__ void wgmma_fence() { asm volatile("wgmma.fence.sync.aligned;" ::: "memory"); }
__device__ __forceinline__ void wgmma_commit() { asm volatile("wgmma.commit_group.sync.aligned;" ::: "memory"); }
template <int N>
__device__ __forceinline__ void wgmma_wait() {
  asm volatile("wgmma.wait_group.sync.aligned %0;" ::"n"(N) : "memory");
}
template <int R>
__device__ __forceinline__ void reg_alloc() { asm volatile("setmaxnreg.inc.sync.aligned.u32 %0;" ::"n"(R)); }
template <int R>
__device__ __forceinline__ void reg_dealloc() { asm volatile("setmaxnreg.dec.sync.aligned.u32 %0;" ::"n"(R)); }

__device__ __forceinline__ void stmatrix_x4(uint32_t addr, uint32_t r0, uint32_t r1, uint32_t r2, uint32_t r3) {
  asm volatile("stmatrix.sync.aligned.m8n8.x4.shared.b16 [%0], {%1, %2, %3, %4};" ::"r"(addr), "r"(r0), "r"(r1),
               "r"(r2), "r"(r3)
               : "memory");
}
__device__ __forceinline__ uint32_t pack_bf16(float lo, float hi) {
  uint32_t r;
  asm("cvt.rn.bf16x2.f32 %0, %1, %2;" : "=r"(r) : "f"(hi), "f"(lo));
  return r;
}
__device__ __forceinline__ float bf16_round(float x) { return __bfloat162float(__float2bfloat16_rn(x)); }
__device__ __forceinline__ float bf_lo(uint32_t v) { return __uint_as_float(v << 16); }
__device__ __forceinline__ float bf_hi(uint32_t v) { return __uint_as_float(v & 0xffff0000u); }
__device__ __forceinline__ uint4 lds128(uint32_t a) {
  uint4 v;
  asm volatile("ld.shared.v4.u32 {%0, %1, %2, %3}, [%4];" : "=r"(v.x), "=r"(v.y), "=r"(v.z), "=r"(v.w) : "r"(a));
  return v;
}
__device__ __forceinline__ void sts128(uint32_t a, uint4 v) {
  asm volatile("st.shared.v4.u32 [%0], {%1, %2, %3, %4};" ::"r"(a), "r"(v.x), "r"(v.y), "r"(v.z), "r"(v.w) : "memory");
}
__device__ __forceinline__ uint32_t mul_bf2(uint32_t a, uint32_t b) {
  uint32_t r;
  asm("mul.rn.bf16x2 %0, %1, %2;" : "=r"(r) : "r"(a), "r"(b));
  return r;
}
__device__ __forceinline__ uint32_t add_bf2(uint32_t a, uint32_t b) {
  uint32_t r;
  asm("add.rn.bf16x2 %0, %1, %2;" : "=r"(r) : "r"(a), "r"(b));
  return r;
}
__device__ __forceinline__ float ex2(float x) {
  float y;
  asm("ex2.approx.ftz.f32 %0, %1;" : "=f"(y) : "f"(x));
  return y;
}
__device__ __forceinline__ float rcp(float x) {
  float y;
  asm("rcp.approx.ftz.f32 %0, %1;" : "=f"(y) : "f"(x));
  return y;
}
template <int N>
__device__ __forceinline__ void fence_regs(float (&r)[N]) {
#pragma unroll
  for (int i = 0; i < N; i++) asm volatile("" : "+f"(r[i])::"memory");
}

template <int N>
__device__ __forceinline__ void undef_regs(float (&r)[N]) {
#pragma unroll
  for (int i = 0; i < N; i++) asm volatile("" : "=f"(r[i]));
}
template <int N>
__device__ __forceinline__ void fence_regs_u(uint32_t (&r)[N]) {
#pragma unroll
  for (int i = 0; i < N; i++) asm volatile("" : "+r"(r[i])::"memory");
}

constexpr uint64_t DESC_SW128 = 1ull << 62;
__device__ __forceinline__ uint64_t make_desc(uint32_t addr, uint32_t lbo_bytes, uint32_t sbo_bytes, uint64_t swz) {
  return (uint64_t)((addr & 0x3FFFF) >> 4) | ((uint64_t)((lbo_bytes & 0x3FFFF) >> 4) << 16) |
         ((uint64_t)((sbo_bytes & 0x3FFFF) >> 4) << 32) | swz;
}

__device__ __forceinline__ uint64_t desc_add(uint64_t d, uint32_t off16) {
  return (d & 0xFFFFFFFF00000000ull) | (uint64_t)((uint32_t)d + off16);
}

__device__ __forceinline__ void wgmma_m64n256_ss_tb(float (&d)[128], uint64_t da, uint64_t db, int sd) {
  asm volatile(
    "{\n.reg .pred p;\nsetp.ne.b32 p, %130, 0;\n"
    "wgmma.mma_async.sync.aligned.m64n256k16.f32.bf16.bf16 "
    "{%0, %1, %2, %3, %4, %5, %6, %7, %8, %9, %10, %11, %12, %13, %14, %15, %16, %17, %18, %19, %20, %21, %22, %23, %24, %25, %26, %27, %28, %29, %30, %31, %32, %33, %34, %35, %36, %37, %38, %39, %40, %41, %42, %43, %44, %45, %46, %47, %48, %49, %50, %51, %52, %53, %54, %55, %56, %57, %58, %59, %60, %61, %62, %63, %64, %65, %66, %67, %68, %69, %70, %71, %72, %73, %74, %75, %76, %77, %78, %79, %80, %81, %82, %83, %84, %85, %86, %87, %88, %89, %90, %91, %92, %93, %94, %95, %96, %97, %98, %99, %100, %101, %102, %103, %104, %105, %106, %107, %108, %109, %110, %111, %112, %113, %114, %115, %116, %117, %118, %119, %120, %121, %122, %123, %124, %125, %126, %127}, %128, %129, p, 1, 1, 0, 1;\n}\n"
    : "+f"(d[0]), "+f"(d[1]), "+f"(d[2]), "+f"(d[3]), "+f"(d[4]), "+f"(d[5]), "+f"(d[6]), "+f"(d[7]), "+f"(d[8]), "+f"(d[9]), "+f"(d[10]), "+f"(d[11]), "+f"(d[12]), "+f"(d[13]), "+f"(d[14]), "+f"(d[15]), "+f"(d[16]), "+f"(d[17]), "+f"(d[18]), "+f"(d[19]), "+f"(d[20]), "+f"(d[21]), "+f"(d[22]), "+f"(d[23]), "+f"(d[24]), "+f"(d[25]), "+f"(d[26]), "+f"(d[27]), "+f"(d[28]), "+f"(d[29]), "+f"(d[30]), "+f"(d[31]), "+f"(d[32]), "+f"(d[33]), "+f"(d[34]), "+f"(d[35]), "+f"(d[36]), "+f"(d[37]), "+f"(d[38]), "+f"(d[39]), "+f"(d[40]), "+f"(d[41]), "+f"(d[42]), "+f"(d[43]), "+f"(d[44]), "+f"(d[45]), "+f"(d[46]), "+f"(d[47]), "+f"(d[48]), "+f"(d[49]), "+f"(d[50]), "+f"(d[51]), "+f"(d[52]), "+f"(d[53]), "+f"(d[54]), "+f"(d[55]), "+f"(d[56]), "+f"(d[57]), "+f"(d[58]), "+f"(d[59]), "+f"(d[60]), "+f"(d[61]), "+f"(d[62]), "+f"(d[63]), "+f"(d[64]), "+f"(d[65]), "+f"(d[66]), "+f"(d[67]), "+f"(d[68]), "+f"(d[69]), "+f"(d[70]), "+f"(d[71]), "+f"(d[72]), "+f"(d[73]), "+f"(d[74]), "+f"(d[75]), "+f"(d[76]), "+f"(d[77]), "+f"(d[78]), "+f"(d[79]), "+f"(d[80]), "+f"(d[81]), "+f"(d[82]), "+f"(d[83]), "+f"(d[84]), "+f"(d[85]), "+f"(d[86]), "+f"(d[87]), "+f"(d[88]), "+f"(d[89]), "+f"(d[90]), "+f"(d[91]), "+f"(d[92]), "+f"(d[93]), "+f"(d[94]), "+f"(d[95]), "+f"(d[96]), "+f"(d[97]), "+f"(d[98]), "+f"(d[99]), "+f"(d[100]), "+f"(d[101]), "+f"(d[102]), "+f"(d[103]), "+f"(d[104]), "+f"(d[105]), "+f"(d[106]), "+f"(d[107]), "+f"(d[108]), "+f"(d[109]), "+f"(d[110]), "+f"(d[111]), "+f"(d[112]), "+f"(d[113]), "+f"(d[114]), "+f"(d[115]), "+f"(d[116]), "+f"(d[117]), "+f"(d[118]), "+f"(d[119]), "+f"(d[120]), "+f"(d[121]), "+f"(d[122]), "+f"(d[123]), "+f"(d[124]), "+f"(d[125]), "+f"(d[126]), "+f"(d[127])
    : "l"(da), "l"(db), "r"(sd));
}

__device__ __forceinline__ void wgmma_m64n128_ss(float (&d)[64], uint64_t da, uint64_t db, int sd) {
  asm volatile(
    "{\n.reg .pred p;\nsetp.ne.b32 p, %66, 0;\n"
    "wgmma.mma_async.sync.aligned.m64n128k16.f32.bf16.bf16 "
    "{%0, %1, %2, %3, %4, %5, %6, %7, %8, %9, %10, %11, %12, %13, %14, %15, %16, %17, %18, %19, %20, %21, %22, %23, %24, %25, %26, %27, %28, %29, %30, %31, %32, %33, %34, %35, %36, %37, %38, %39, %40, %41, %42, %43, %44, %45, %46, %47, %48, %49, %50, %51, %52, %53, %54, %55, %56, %57, %58, %59, %60, %61, %62, %63}, %64, %65, p, 1, 1, 0, 0;\n}\n"
    : "+f"(d[0]), "+f"(d[1]), "+f"(d[2]), "+f"(d[3]), "+f"(d[4]), "+f"(d[5]), "+f"(d[6]), "+f"(d[7]), "+f"(d[8]), "+f"(d[9]), "+f"(d[10]), "+f"(d[11]), "+f"(d[12]), "+f"(d[13]), "+f"(d[14]), "+f"(d[15]), "+f"(d[16]), "+f"(d[17]), "+f"(d[18]), "+f"(d[19]), "+f"(d[20]), "+f"(d[21]), "+f"(d[22]), "+f"(d[23]), "+f"(d[24]), "+f"(d[25]), "+f"(d[26]), "+f"(d[27]), "+f"(d[28]), "+f"(d[29]), "+f"(d[30]), "+f"(d[31]), "+f"(d[32]), "+f"(d[33]), "+f"(d[34]), "+f"(d[35]), "+f"(d[36]), "+f"(d[37]), "+f"(d[38]), "+f"(d[39]), "+f"(d[40]), "+f"(d[41]), "+f"(d[42]), "+f"(d[43]), "+f"(d[44]), "+f"(d[45]), "+f"(d[46]), "+f"(d[47]), "+f"(d[48]), "+f"(d[49]), "+f"(d[50]), "+f"(d[51]), "+f"(d[52]), "+f"(d[53]), "+f"(d[54]), "+f"(d[55]), "+f"(d[56]), "+f"(d[57]), "+f"(d[58]), "+f"(d[59]), "+f"(d[60]), "+f"(d[61]), "+f"(d[62]), "+f"(d[63])
    : "l"(da), "l"(db), "r"(sd));
}

__device__ __forceinline__ void wgmma_m64n128_ss_tb(float (&d)[64], uint64_t da, uint64_t db, int sd) {
  asm volatile(
    "{\n.reg .pred p;\nsetp.ne.b32 p, %66, 0;\n"
    "wgmma.mma_async.sync.aligned.m64n128k16.f32.bf16.bf16 "
    "{%0, %1, %2, %3, %4, %5, %6, %7, %8, %9, %10, %11, %12, %13, %14, %15, %16, %17, %18, %19, %20, %21, %22, %23, %24, %25, %26, %27, %28, %29, %30, %31, %32, %33, %34, %35, %36, %37, %38, %39, %40, %41, %42, %43, %44, %45, %46, %47, %48, %49, %50, %51, %52, %53, %54, %55, %56, %57, %58, %59, %60, %61, %62, %63}, %64, %65, p, 1, 1, 0, 1;\n}\n"
    : "+f"(d[0]), "+f"(d[1]), "+f"(d[2]), "+f"(d[3]), "+f"(d[4]), "+f"(d[5]), "+f"(d[6]), "+f"(d[7]), "+f"(d[8]), "+f"(d[9]), "+f"(d[10]), "+f"(d[11]), "+f"(d[12]), "+f"(d[13]), "+f"(d[14]), "+f"(d[15]), "+f"(d[16]), "+f"(d[17]), "+f"(d[18]), "+f"(d[19]), "+f"(d[20]), "+f"(d[21]), "+f"(d[22]), "+f"(d[23]), "+f"(d[24]), "+f"(d[25]), "+f"(d[26]), "+f"(d[27]), "+f"(d[28]), "+f"(d[29]), "+f"(d[30]), "+f"(d[31]), "+f"(d[32]), "+f"(d[33]), "+f"(d[34]), "+f"(d[35]), "+f"(d[36]), "+f"(d[37]), "+f"(d[38]), "+f"(d[39]), "+f"(d[40]), "+f"(d[41]), "+f"(d[42]), "+f"(d[43]), "+f"(d[44]), "+f"(d[45]), "+f"(d[46]), "+f"(d[47]), "+f"(d[48]), "+f"(d[49]), "+f"(d[50]), "+f"(d[51]), "+f"(d[52]), "+f"(d[53]), "+f"(d[54]), "+f"(d[55]), "+f"(d[56]), "+f"(d[57]), "+f"(d[58]), "+f"(d[59]), "+f"(d[60]), "+f"(d[61]), "+f"(d[62]), "+f"(d[63])
    : "l"(da), "l"(db), "r"(sd));
}

__device__ __forceinline__ void wgmma_m64n128_rs_tb(float* d, uint32_t a0, uint32_t a1, uint32_t a2, uint32_t a3, uint64_t db, int sd) {
  asm volatile(
    "{\n.reg .pred p;\nsetp.ne.b32 p, %69, 0;\n"
    "wgmma.mma_async.sync.aligned.m64n128k16.f32.bf16.bf16 "
    "{%0, %1, %2, %3, %4, %5, %6, %7, %8, %9, %10, %11, %12, %13, %14, %15, %16, %17, %18, %19, %20, %21, %22, %23, %24, %25, %26, %27, %28, %29, %30, %31, %32, %33, %34, %35, %36, %37, %38, %39, %40, %41, %42, %43, %44, %45, %46, %47, %48, %49, %50, %51, %52, %53, %54, %55, %56, %57, %58, %59, %60, %61, %62, %63}, {%64, %65, %66, %67}, %68, p, 1, 1, 1;\n}\n"
    : "+f"(d[0]), "+f"(d[1]), "+f"(d[2]), "+f"(d[3]), "+f"(d[4]), "+f"(d[5]), "+f"(d[6]), "+f"(d[7]), "+f"(d[8]), "+f"(d[9]), "+f"(d[10]), "+f"(d[11]), "+f"(d[12]), "+f"(d[13]), "+f"(d[14]), "+f"(d[15]), "+f"(d[16]), "+f"(d[17]), "+f"(d[18]), "+f"(d[19]), "+f"(d[20]), "+f"(d[21]), "+f"(d[22]), "+f"(d[23]), "+f"(d[24]), "+f"(d[25]), "+f"(d[26]), "+f"(d[27]), "+f"(d[28]), "+f"(d[29]), "+f"(d[30]), "+f"(d[31]), "+f"(d[32]), "+f"(d[33]), "+f"(d[34]), "+f"(d[35]), "+f"(d[36]), "+f"(d[37]), "+f"(d[38]), "+f"(d[39]), "+f"(d[40]), "+f"(d[41]), "+f"(d[42]), "+f"(d[43]), "+f"(d[44]), "+f"(d[45]), "+f"(d[46]), "+f"(d[47]), "+f"(d[48]), "+f"(d[49]), "+f"(d[50]), "+f"(d[51]), "+f"(d[52]), "+f"(d[53]), "+f"(d[54]), "+f"(d[55]), "+f"(d[56]), "+f"(d[57]), "+f"(d[58]), "+f"(d[59]), "+f"(d[60]), "+f"(d[61]), "+f"(d[62]), "+f"(d[63])
    : "r"(a0), "r"(a1), "r"(a2), "r"(a3), "l"(db), "r"(sd));
}

__device__ __forceinline__ void wgmma_m64n64_rs(float (&d)[32], const uint32_t* a, uint64_t db, int sd) {
  asm volatile(
    "{\n.reg .pred p;\nsetp.ne.b32 p, %37, 0;\n"
    "wgmma.mma_async.sync.aligned.m64n64k16.f32.bf16.bf16 "
    "{%0, %1, %2, %3, %4, %5, %6, %7, %8, %9, %10, %11, %12, %13, %14, %15, %16, %17, %18, %19, %20, %21, %22, %23, %24, %25, %26, %27, %28, %29, %30, %31}, {%32, %33, %34, %35}, %36, p, 1, 1, 0;\n}\n"
    : "+f"(d[0]), "+f"(d[1]), "+f"(d[2]), "+f"(d[3]), "+f"(d[4]), "+f"(d[5]), "+f"(d[6]), "+f"(d[7]), "+f"(d[8]), "+f"(d[9]), "+f"(d[10]), "+f"(d[11]), "+f"(d[12]), "+f"(d[13]), "+f"(d[14]), "+f"(d[15]), "+f"(d[16]), "+f"(d[17]), "+f"(d[18]), "+f"(d[19]), "+f"(d[20]), "+f"(d[21]), "+f"(d[22]), "+f"(d[23]), "+f"(d[24]), "+f"(d[25]), "+f"(d[26]), "+f"(d[27]), "+f"(d[28]), "+f"(d[29]), "+f"(d[30]), "+f"(d[31])
    : "r"(a[0]), "r"(a[1]), "r"(a[2]), "r"(a[3]), "l"(db), "r"(sd));
}

constexpr int G_STAGES = 4;
constexpr int G_A_BYTES = 128 * 64 * 2;
constexpr int G_B_BYTES = 256 * 64 * 2;
constexpr int G_STAGE_BYTES = G_A_BYTES + G_B_BYTES;
constexpr int G_STG_OFF = G_STAGES * G_STAGE_BYTES;
constexpr int BAR_OFF = G_STG_OFF + 32768 + 2048;
constexpr int SMEM_BYTES = BAR_OFF + 1024;
constexpr int B_GFULL = 0, B_GEMPTY = 32, B_OY2 = 64, B_PFULL = 224;
constexpr int B_KFULL = 80, B_KEMPTY = 96, B_VFULL = 112, B_VEMPTY = 128, B_QFULL = 144, B_QEMPTY = 160,
              B_QDONE = 184;
constexpr int B_CFULL = 192;
constexpr int B_OFREE = 256, B_OFULL = 272, B_OEMPTY = 320, B_OY = 368;
constexpr int B_SFULL = 392, B_SFREE = 424, B_PEND = 456, B_SCMD = 512;

#define PHASE_PROLOGUE                                                                \
  uint32_t tid, rt_zero;                                                              \
  asm volatile("mov.u32 %0, %%tid.x;" : "=r"(tid));                                   \
  asm volatile("mov.u32 %0, %%nctaid.y;" : "=r"(rt_zero));                            \
  asm volatile("" : "+r"(smem0));                                                     \
  rt_zero = __shfl_sync(0xffffffffu, rt_zero >> 8, 0);   \
  const uint32_t sbase = __shfl_sync(0xffffffffu, smem0, 0);                          \
  const uint32_t bar = sbase + BAR_OFF;                                               \
  const int wg = __shfl_sync(0xffffffffu, tid >> 7, 0);                               \
  const int warp = (tid >> 5) & 3, lane = tid & 31, wtid = tid & 127;                 \
  (void)rt_zero; (void)bar; (void)warp; (void)lane; (void)wtid;

enum { ST_END = 0, ST_BOX1, ST_BOX2, ST_BOX2Q, ST_BOX2L };
__device__ __forceinline__ void st_post(uint32_t bar, int wg, int wtid, uint32_t n, int kind, const void* dst,
                                        uint32_t src, int c0, int c1, int sig) {
  if (wtid == 0) {
    const uint32_t c = bar + B_SCMD + wg * 64 + (n & 1) * 32;
    const uint64_t d = reinterpret_cast<uint64_t>(dst);
    sts128(c, make_uint4(kind, src, c0, c1));
    sts128(c + 16, make_uint4((uint32_t)d, (uint32_t)(d >> 32), sig, 0));
  }
  fence_proxy_async();
  __syncwarp();
  mbar_arrive_if(bar + B_SFULL + wg * 16 + (n & 1) * 8, (wtid & 31) == 0);
}
__device__ __forceinline__ void st_wait(uint32_t bar, int wg, uint32_t n) {
  const uint32_t b = bar + B_SFREE + wg * 16 + (n & 1) * 8;
  if (!mbar_try(b, ~(n >> 1) & 1)) mbar_wait(b, ~(n >> 1) & 1);
}
__device__ __forceinline__ void note(uint32_t bar, uint32_t cnt) {
  asm volatile("red.release.cta.shared.add.u32 [%0], 1;" ::"r"(bar + B_PEND + 4 * cnt) : "memory");
}
__device__ __forceinline__ void store_agent(uint32_t bar, int wg) {
  mbar_arrive(bar + B_SFREE + wg * 16);
  mbar_arrive(bar + B_SFREE + wg * 16 + 8);
  for (uint32_t n = 0;; n++) {
    mbar_wait_sleep(bar + B_SFULL + wg * 16 + (n & 1) * 8, (n >> 1) & 1);
    const uint4 c = lds128(bar + B_SCMD + wg * 64 + (n & 1) * 32);
    const uint4 d = lds128(bar + B_SCMD + wg * 64 + (n & 1) * 32 + 16);
    if (c.x == ST_END) break;
    const CUtensorMap* dst = reinterpret_cast<const CUtensorMap*>((uint64_t)d.x | ((uint64_t)d.y << 32));
    tma_store_2d(dst, c.y, c.z, c.w);
    if (c.x >= ST_BOX2) tma_store_2d(dst, c.y + 8192, c.z + 64, c.w);
    tma_store_commit();
    tma_store_wait_read<0>();
    mbar_arrive(bar + B_SFREE + wg * 16 + (n & 1) * 8);
    if (c.x == ST_BOX2L) mbar_arrive(bar + B_OFREE + 8 * wg);
    if ((int)d.z >= 0) {
      tma_store_wait<0>();
      if (d.z == 0) { TD(6) }
      asm volatile("fence.proxy.async.global;" ::: "memory");
      if (c.x == ST_BOX2Q) mbar_arrive(bar + B_QDONE);
      else note(bar, d.z);
      if (c.x == ST_BOX2L) break;
    }
  }
  note(bar, CNT_DONE);
}

struct Maps {
  const bf16 *shift_k, *x, *gate_w, *ssm_k, *ssm_D;
  uint8_t id[128][4];
  CUtensorMap a[2];
  CUtensorMap b[3];
  CUtensorMap c[3];
  CUtensorMap bk, bv;
  CUtensorMap q, k, v, o;
  CUtensorMap oa, ob, oc, ox;
  CUtensorMap y, y2;
};

constexpr int P_SLOT = 67 * 128, P_V = 35 * 128, P_TAPS = 2 * P_SLOT;
__device__ __forceinline__ void ldsm4t(uint32_t (&r)[4], uint32_t a) {
  asm volatile("ldmatrix.sync.aligned.m8n8.x4.trans.shared.b16 {%0, %1, %2, %3}, [%4];"
               : "=r"(r[0]), "=r"(r[1]), "=r"(r[2]), "=r"(r[3])
               : "r"(a));
}
__device__ __forceinline__ uint32_t fma_bf2(uint32_t a, uint32_t b, uint32_t c) {
  uint32_t r;
  asm("fma.rn.bf16x2 %0, %1, %2, %3;" : "=r"(r) : "r"(a), "r"(b), "r"(c));
  return r;
}
__device__ __forceinline__ void prep_agent(const Maps& maps, uint32_t sbase, int w, int lane) {
  const uint32_t bar = sbase + BAR_OFF, pb = bar + B_PFULL + w * 16;
  const int d0 = (blockIdx.x >> 3) * 64, t0 = (blockIdx.x & 7) * 256 + w * 128;
  mbar_wait_sleep(bar + B_GFULL + 8 * (G_STAGES - 1), 0);
#pragma unroll 1
  for (int i = -1; i < 4; i++) {
    GA(82 + 2 * i)
    if (i >= 0) mbar_wait_sleep(pb + (i & 1) * 8, i >> 1);
    GA(83 + 2 * i)
    const uint32_t so = sbase + G_STG_OFF + w * (P_TAPS + 512) + (i & 1) * P_SLOT;
    if (i < 3 && elect_one()) {
      const uint32_t b = pb + (~i & 1) * 8, dst = so + (i & 1 ? -P_SLOT : P_SLOT);
      mbar_expect_tx(b, i < 0 ? P_SLOT + 512 : P_SLOT);
      const uint64_t pol = policy_evict_first();
      tma_load_2d_hint(dst, &maps.bk, b, d0, t0 + 32 * i + 29, pol);
      tma_load_2d_hint(dst + P_V, &maps.bv, b, d0, t0 + 32 * i + 32, pol);
      if (i < 0) bulk_load(sbase + G_STG_OFF + P_TAPS, maps.shift_k + d0 * 4, 512, b);
    }
    if (i < 0) continue;
    uint32_t ak[4];
#pragma unroll
    for (int r = 0; r < 4; r++) {
      const uint32_t a = so / 128 + r + 4 * (lane & 6) + (((((lane >> 2) ^ lane) & 6) + (lane & 1)) ^ 7);
      ak[r] = a * 128 + (a & 7) * 16;
    }
    bf16* dst = g_kvT + (size_t)(d0 + (lane >> 2)) * S_LEN + t0 + ((lane & 3) + 4 * i) * 8;
#pragma unroll 1
    for (int cg = 0; cg < 128; cg += 16) {
      uint32_t t01, t23, k[4][4], v[4];
      asm volatile("ld.shared.v2.u32 {%0, %1}, [%2];"
                   : "=r"(t01), "=r"(t23)
                   : "r"(sbase + G_STG_OFF + P_TAPS + cg * 4 + (lane >> 2) * 8));
#pragma unroll
      for (int r = 0; r < 4; r++) ldsm4t(k[r], ak[r] ^ cg);
      ldsm4t(v, (ak[3] ^ cg) + 4096);
      const uint32_t w0 = __byte_perm(t01, 0, 0x1010), w1 = __byte_perm(t01, 0, 0x3232);
      const uint32_t w2 = __byte_perm(t23, 0, 0x1010), w3 = __byte_perm(t23, 0, 0x3232);
#pragma unroll
      for (int j = 0; j < 4; j++)
        v[j] = mul_bf2(fma_bf2(k[3][j], w0, fma_bf2(k[2][j], w1, fma_bf2(k[1][j], w2, mul_bf2(k[0][j], w3)))), v[j]);
      const bool s1 = lane & 1, s2 = lane & 2;
      const uint32_t a0 = s1 ? v[1] : v[0], a1 = s1 ? v[0] : v[1], a2 = s1 ? v[3] : v[2], a3 = s1 ? v[2] : v[3];
      *reinterpret_cast<uint4*>(dst) = make_uint4(s2 ? a2 : a0, s2 ? a3 : a1, s2 ? a0 : a2, s2 ? a1 : a3);
      dst += 8 * S_LEN;
    }
    fence_proxy_async();
    __syncwarp();
  }
  GA(90)
  if (lane == 0) note(bar, CNT_PREP);
  __syncwarp();
  GA(91)
}

__device__ __forceinline__ void qkv_tile(const Maps& maps, int it, int& which, int& m_tile, int& n_tile) {
  const bool q = it == 0 || it >= 5;
  const int b = maps.id[blockIdx.x][it >= 5];
  which = q ? 0 : 2 - (it & 1);
  m_tile = b & 15;
  n_tile = (b >> 4) * 2 + ((0x19 >> it) & 1);
}

constexpr int G_NTILES = 6;
__device__ __forceinline__ void qkv_producer(const Maps& maps, uint32_t sbase, bool first) {
  const uint32_t bar = sbase + BAR_OFF;
  uint32_t stage = 0, phase = 0;
#pragma unroll 1
  for (int it = 0; it < (first ? 1 : G_NTILES); it++) {
    int which, m_tile, n_tile;
    qkv_tile(maps, it, which, m_tile, n_tile);
    const CUtensorMap* ma = &maps.a[which == 0 ? 0 : 1];
    const CUtensorMap* mb = &maps.b[which];
    const int nk = first ? G_STAGES : which == 0 ? 16 : 8;
#pragma unroll 1
    for (int kt = (it == 0 && !first) ? G_STAGES : 0; kt < nk; kt++) {
      if (!first) mbar_wait_sleep(bar + B_GEMPTY + 8 * stage, phase);
      const uint32_t fb = bar + B_GFULL + 8 * stage;
      const uint32_t sa = sbase + stage * G_STAGE_BYTES;
      mbar_expect_tx(fb, G_STAGE_BYTES);
      tma_load_2d(sa, ma, fb, kt * 64, m_tile * 128);
      tma_load_3d(sa + G_A_BYTES, mb, fb, 0, kt * 64, n_tile * 4);
      if (++stage == G_STAGES) { stage = 0; phase ^= 1; }
      {
        const int b = maps.id[blockIdx.x][1];
        if (it == 2 && kt == (b & 7))
          asm volatile("cp.async.bulk.prefetch.tensor.3d.L2.global.tile [%0, {%1, %2, %3}];" ::"l"(&maps.b[1 + (b >> 6)]),
                       "r"(0), "r"(((b >> 3) & 7) * 64), "r"((b & 7) * 8 + 4)
                       : "memory");
        if (it == 3 && kt == (b & 7))
          asm volatile("cp.async.bulk.prefetch.tensor.3d.L2.global.tile [%0, {%1, %2, %3}];" ::"l"(&maps.b[0]), "r"(0),
                       "r"((b & 15) * 64), "r"((b >> 4) * 8)
                       : "memory");
      }
    }
  }
}

__device__ __noinline__ void publisher(uint32_t bar, int lane, uint32_t nsrc) {
  uint32_t done = 0;
  CLK_DECL
#pragma unroll 1
  for (uint32_t spins = 0; done < nsrc && spins < (1u << 20); spins++) {
    CLK_SAMPLE
    uint32_t v = 0;
    if (lane < CNT_N)
      asm volatile("atom.acquire.cta.shared.exch.b32 %0, [%1], 0;" : "=r"(v) : "r"(bar + B_PEND + 4 * lane) : "memory");
    done += __shfl_sync(0xffffffffu, v, CNT_DONE);
    if (lane == CNT_DONE) v = 0;
    if (done == nsrc && lane < CNT_DONE) {
      uint32_t w;
      asm volatile("atom.acquire.cta.shared.exch.b32 %0, [%1], 0;" : "=r"(w) : "r"(bar + B_PEND + 4 * lane) : "memory");
      v += w;
    }
    if (v && lane == 0) { TD(0) }
    if (v) cnt_signal_release(lane, v);
    if (v && lane == 0) { TD(1) }
    if (!__any_sync(0xffffffffu, v != 0)) __nanosleep(200);
  }
  CLK_END
  __threadfence();
  __syncwarp();
}

__device__ __forceinline__ void gate_rows(const Maps& maps, uint32_t sbase, int w48, int w12, int lane) {
  const uint32_t buf = sbase + w12 * 16384, gb = sbase + BAR_OFF + 768 + w12 * 16;
  if (lane == 0) {
    mbar_init(gb, 1);
    mbar_init(gb + 8, 1);
    fence_barrier_init();
    for (int i = 0; i < 2; i++) {
      mbar_expect_tx(gb + 8 * i, 8192);
      bulk_load(buf + i * 8192, maps.x + (size_t)(w48 + 48 * i) * 4 * DM, 8192, gb + 8 * i);
    }
  }
  __syncwarp();
  uint4 wv[4];
#pragma unroll
  for (int i = 0; i < 4; i++) wv[i] = __ldg(reinterpret_cast<const uint4*>(maps.gate_w + (i * 32 + lane) * 8));
  int it = 0;
#pragma unroll 1
  for (int row = w48 * 4; row < S_LEN; row += 48 * 4, it++) {
    mbar_wait(gb + 8 * (it & 1), (it >> 1) & 1);
    uint4 xv[4][4];
#pragma unroll
    for (int r = 0; r < 4; r++)
#pragma unroll
      for (int i = 0; i < 4; i++) xv[r][i] = lds128(buf + (it & 1) * 8192 + r * 2048 + (i * 32 + lane) * 16);
    float d[2][4];
#pragma unroll
    for (int pr = 0; pr < 2; pr++) {
      d[pr][0] = d[pr][1] = d[pr][2] = d[pr][3] = 0.f;
      auto acc = [&](uint32_t a0, uint32_t a2, uint32_t b0, uint32_t b2, uint32_t w0, uint32_t w2) {
        asm volatile(
            "mma.sync.aligned.m16n8k16.row.col.f32.bf16.bf16.f32 {%0, %1, %2, %3}, {%4, %5, %6, %7}, {%8, %8}, "
            "{%0, %1, %2, %3};"
            : "+f"(d[pr][0]), "+f"(d[pr][1]), "+f"(d[pr][2]), "+f"(d[pr][3])
            : "r"(mul_bf2(a0, w0)), "r"(mul_bf2(b0, w0)), "r"(mul_bf2(a2, w2)), "r"(mul_bf2(b2, w2)), "r"(0x3f803f80u));
      };
#pragma unroll
      for (int i = 0; i < 4; i++) {
        acc(xv[2 * pr][i].x, xv[2 * pr][i].y, xv[2 * pr + 1][i].x, xv[2 * pr + 1][i].y, wv[i].x, wv[i].y);
        acc(xv[2 * pr][i].z, xv[2 * pr][i].w, xv[2 * pr + 1][i].z, xv[2 * pr + 1][i].w, wv[i].z, wv[i].w);
      }
    }
    float sum = (lane & 2) ? ((lane & 1) ? d[1][2] : d[1][0]) : ((lane & 1) ? d[0][2] : d[0][0]);
#pragma unroll
    for (int off = 16; off >= 4; off >>= 1) sum += __shfl_xor_sync(0xffffffffu, sum, off);
    if (lane < 4) g_gate[row + lane] = bf16_round(rcp(1.0f + __expf(-bf16_round(sum))));
    if (lane == 0 && row + 2 * 48 * 4 < S_LEN) {
      mbar_expect_tx(gb + 8 * (it & 1), 8192);
      bulk_load(buf + (it & 1) * 8192, maps.x + (size_t)(row + 2 * 48 * 4) * DM, 8192, gb + 8 * (it & 1));
    }
  }
}

constexpr float Q_SCALE = 0.08838834764831845f * 1.4426950408889634f;
__device__ __forceinline__ uint32_t qkv_consumer(const Maps& maps, uint32_t smem0, bool fused, float (&rest)[64]) {
  PHASE_PROLOGUE
  constexpr int NTILES = G_NTILES;
  float acc[128];
  uint32_t stage = 0, phase = 0;
  const uint32_t stg = sbase + G_STG_OFF + wg * 18432;
  const int st_row = warp * 16 + (lane & 7) + ((lane >> 3) & 1) * 8;
  const int st_cb = lane >> 4;
  uint32_t pend[64];
  const CUtensorMap* pend_map = nullptr;
  int pend_c0 = 0, pend_c1 = 0;
  uint32_t sn = 0;
  auto put_box = [&](uint32_t buf, const uint32_t* v) {
#pragma unroll
    for (int jp = 0; jp < 4; jp++) {
      const int chunk = jp * 2 + st_cb;
      const uint32_t addr = buf + st_row * 128 + ((chunk ^ (st_row & 7)) << 4);
      stmatrix_x4(addr, v[jp * 4], v[jp * 4 + 1], v[jp * 4 + 2], v[jp * 4 + 3]);
    }
  };
  GT(gti++)
#pragma unroll 1
  for (int it = 0; it <= NTILES; it++) {
    int which, m_tile, n_tile;
    qkv_tile(maps, it, which, m_tile, n_tile);
    const int nk = (which == 0 && it < NTILES) ? 16 : 8;
    uint32_t prev_stage = 0;
#pragma unroll 1
    for (int kt = 0; kt < nk; kt++) {
      if (it < NTILES) {
        mbar_wait((bar + B_GFULL) + 8 * stage, phase);
        GT(gti++)
        const uint64_t da0 = make_desc(sbase + stage * G_STAGE_BYTES + wg * 8192, 16, 1024, DESC_SW128);
        const uint64_t db0 = make_desc(sbase + stage * G_STAGE_BYTES + G_A_BYTES, 8192, 1024, DESC_SW128);
        wgmma_fence();
#pragma unroll
        for (int kk = 0; kk < 4; kk++) {
          wgmma_m64n256_ss_tb(acc, desc_add(da0, kk * 2), desc_add(db0, kk * 128), (kt | kk) != 0);
        }
        wgmma_commit();
      }
      const uint32_t when = it == 0 ? 0 : it == 5 ? 0x922 << wg : wg ? 0xAA : 0x55;
      if ((when >> kt) & 1) {
        const int c = __popc(when & ~(~0u << kt));
        st_wait(bar, wg, sn - 2);
        const uint32_t buf = stg + (c & 1) * 8192;
        switch (c) {
          case 0: put_box(buf, pend); break;
          case 1: put_box(buf, pend + 16); break;
          case 2: put_box(buf, pend + 32); break;
          default: put_box(buf, pend + 48); break;
        }
        st_post(bar, wg, wtid, sn, ST_BOX1, pend_map, buf, pend_c0 + c * 64, pend_c1, (c == 3 && it > 1) ? CNT_KV + (it > 3) : -1);
        sn++;
      }
      if (it < NTILES) {
        wgmma_wait<1>();
        mbar_arrive_if((bar + B_GEMPTY) + 8 * prev_stage, wtid == 32 && kt > 0);
        prev_stage = stage;
        if (++stage == G_STAGES) { stage = 0; phase ^= 1; }
      }
    }
    wgmma_wait<0>();
    fence_regs(acc);
    if (it == NTILES) break;
    GT(gti++)
    mbar_arrive_if((bar + B_GEMPTY) + 8 * prev_stage, wtid == 32);
    if (it == NTILES - 1 && fused) break;
    if (which == 0) {
#pragma unroll
      for (int j = 0; j < 128; j++) acc[j] *= Q_SCALE;
    }
#pragma unroll
    for (int j = 0; j < 64; j++) pend[j] = pack_bf16(acc[2 * j], acc[2 * j + 1]);
    pend_map = &maps.c[which];
    pend_c0 = n_tile * 256;
    pend_c1 = m_tile * 128 + wg * 64;
  }
  mbar_wait(bar + B_GEMPTY, 1);
#pragma unroll
  for (int j = 0; j < 32; j++) pend[j] = pack_bf16(acc[2 * j] * Q_SCALE, acc[2 * j + 1] * Q_SCALE);
  put_box(sbase + wg * 8192, pend);
  put_box(sbase + 16384 + wg * 8192, pend + 16);
  fence_proxy_async();
#pragma unroll
  for (int j = 0; j < 64; j++) rest[j] = acc[64 + j];
  GT(gti++)
  return sn;
}

constexpr int A_TILE = 128 * 128 * 2;
constexpr int A_Q_OFF = 0;
constexpr int A_K_OFF = 2 * A_TILE;
constexpr int A_V_OFF = 4 * A_TILE;
constexpr int A_O_OFF = 6 * A_TILE;
constexpr int A_ITEMS = NH * (S_LEN / 128);

constexpr uint32_t A_ORDER = 0x3120, A_STEPS = 34;
__device__ __forceinline__ int item_m(uint32_t it) { return it & 15; }
__device__ __forceinline__ int item_h(uint32_t it) { return it >> 4; }

constexpr int C_H0 = 16, C_U = C_H0 + 4096 + 112, C_SLOT = C_U + 4096;
constexpr int C_H1 = 2 * C_SLOT + 80;
constexpr int C_X_OFF = C_H1 + 4096 + 48;

__device__ __forceinline__ uint32_t item_of(const Maps& maps, uint32_t r) {
  const uint32_t b = maps.id[blockIdx.x & 127][1];
  return (b >> 4) * 64 + ((A_ORDER >> (4 * r)) & 3) * 16 + ((b ^ ((r & 1) * 15)) & 15);
}

constexpr uint32_t C_SIDE = 48;
__device__ __forceinline__ uint32_t conv_first(const Maps& maps) {
  const uint32_t b = maps.id[blockIdx.x & 127][1];
  return (b >> 4) * 128 + (b & 15);
}

__device__ __forceinline__ void conv_consumer(const Maps& maps, uint32_t smem0, uint32_t first, uint32_t step,
                                              uint32_t end) {
  PHASE_PROLOGUE
  const uint32_t full = bar + B_CFULL + wg * 16;
  const uint32_t ca = sbase + (wg ? A_V_OFF + A_TILE : A_Q_OFF);
  const int w4 = __shfl_sync(0xffffffffu, warp, 0);
  auto fetch = [&](uint32_t c, uint32_t slot) {
    if (w4 == 2 && c < end) {
      if (elect_one()) {
        const uint32_t sb = ca + slot * C_SLOT, fb = full + 8 * slot;
        const uint64_t pol = policy_evict_first();
        mbar_expect_tx(fb, 2 * 4096);
        bulk_load_hint(sb + C_H0, maps.ssm_k + (size_t)c * S_LEN, 4096, fb, pol);
        bulk_load_hint(sb + C_U, g_kvT + (size_t)c * S_LEN, 4096, fb, pol);
      }
    }
  };
  auto shift_h = [&](uint32_t so) {
    const uint32_t a = ca + so + C_H0 + wtid * 16;
#pragma unroll
    for (int i = 0; i < 2; i++) {
      uint32_t p;
      const uint4 v = lds128(a + i * 2048);
      asm volatile("ld.shared.u32 %0, [%1];" : "=r"(p) : "r"(a + i * 2048 - 4));
      sts128(ca + C_H1 + wtid * 16 + i * 2048, make_uint4(__byte_perm(p, v.x, 0x5432), __byte_perm(v.x, v.y, 0x5432),
                                                      __byte_perm(v.y, v.z, 0x5432), __byte_perm(v.z, v.w, 0x5432)));
    }
  };
  if (wtid == 96 && wg) { TD(15) }
  fetch(first, 0);
  if (wtid < 17)
    sts128(ca + (wtid >> 3) * C_SLOT + (wtid & 7 ? 4096 + (wtid & 7) * 16 : (wtid & 16) * 4), make_uint4(0, 0, 0, 0));
  fence_proxy_async();
  const uint32_t ha = ca + ((lane & 4) ? C_H1 : C_H0) + 4 * ((lane & 3) - (lane >> 3)) + w4 * 256;
  const uint32_t ua = ca + C_U + w4 * 256 + (lane >> 4) * 1024 + (lane & 15) * 16;
  const uint32_t xa = ca + C_X_OFF + lane * 8, xw = xa + w4 * 3072;
  uint32_t xg[3];
#pragma unroll
  for (int k = 0; k < 3; k++) {
    const int w = (w4 + k + 1) & 3;
    xg[k] = xa + (w * 12 + w4 - w - (w < w4 ? 1 : 0)) * 256;
  }
  const bool pp = step != 16;
  uint32_t h[2][16];
  const uint32_t hs = (lane & 4) ? 0 : C_SLOT;
  auto load_h = [&](uint32_t so, int a) {
#pragma unroll
    for (int i = 0; i < 16; i++)
      asm volatile("ld.shared.u32 %0, [%1];"
                   : "=r"(h[a & 1][i])
                   : "r"(ha + so + 1024 * a + 32 * (i >> 2) + (i & 1) * 128 + (~i & 2) * 8));
  };
  mbar_wait(full, 0);
  named_bar_sync(1 + wg, 128);
  shift_h(0);
  named_bar_sync(1 + wg, 128);
  fetch(first + step, 1);
  load_h(0, 0);
  load_h(0, 1);
  mbar_wait(bar + B_OFREE, 0);
  mbar_wait(bar + B_OFREE + 8, 0);
  uint32_t n = 0, ch = first;
  for (; ch < end; n++, ch += step) {
    CT(0)
    const uint32_t so = (n & 1) * C_SLOT, ho = (n & 1) * hs;
    uint32_t db = (uint32_t)make_desc(ca + so + C_U - 16, 16, 0, 0);
    asm volatile("" : "+r"(db));
    uint32_t dsk = __ldg(reinterpret_cast<const unsigned short*>(maps.ssm_D) + (ch | (lane & rt_zero)));
    float d[4][32], own[16];
    auto mma = [&](int a) {
      wgmma_fence();
#pragma unroll
      for (int c = a; c < 4; c++)
#pragma unroll
        for (int b = 0; b < 4; b++)
          wgmma_m64n64_rs(d[c], &h[a & 1][4 * b], (8ull << 32) | (db + 64 * (c - a) - 2 * b), (a | b) != 0);
      wgmma_commit();
    };
    auto put = [&](int c) {
      fence_regs(d[c]);
#pragma unroll
      for (int e = 0; e < 2; e++) {
        if (c == 0) asm volatile("mov.b32 %0, %1;" : "=f"(own[e]) : "f"(d[c][e]));
        else own[4 * c + e] += d[c][e];
        own[4 * c + 2 + e] = d[c][4 + e] + d[c][2 + e];
        if (c < 3) asm volatile("mov.b32 %0, %1;" : "=f"(own[4 * c + 4 + e]) : "f"(d[c][30 + e]));
      }
#pragma unroll
      for (int j = 1; j < 4; j++)
        asm volatile("{\n.reg .pred p;\nsetp.lt.s32 p, %3, 4;\n@p st.shared.v2.u32 [%0], {%1, %2};\n}\n" ::"r"(
                         xw + (3 * c + j - 1) * 256),
                     "r"(pack_bf16(d[c][8 * j] + d[c][8 * j - 2], d[c][8 * j + 1] + d[c][8 * j - 1])),
                     "r"(pack_bf16(d[c][8 * j + 4] + d[c][8 * j + 2], d[c][8 * j + 5] + d[c][8 * j + 3])),
                     "r"(c < 3 ? 0 : w4 + j)
                     : "memory");
    };
    named_bar_sync(pp ? 4 + wg : 1 + wg, pp ? 256 : 128);
    CT(1)
    mma(0);
    mma(1);
    wgmma_wait<1>();
    load_h(ho, 2);
    put(0);
    mma(2);
    CT(2)
    wgmma_wait<1>();
    load_h(ho, 3);
    put(1);
    mma(3);
    asm volatile("{\n.reg .pred p;\nsetp.ne.u32 p, %1, 0;\n@p bar.arrive %0, 256;\n}\n" ::"r"(5 - wg), "r"((uint32_t)pp) : "memory");
    CT(3)
    uint32_t sk[8];
    asm volatile("ldmatrix.sync.aligned.m8n8.x4.trans.shared.b16 {%0, %1, %2, %3}, [%4];"
                 : "=r"(sk[0]), "=r"(sk[1]), "=r"(sk[2]), "=r"(sk[3])
                 : "r"(ua + so));
    asm volatile("ldmatrix.sync.aligned.m8n8.x4.trans.shared.b16 {%0, %1, %2, %3}, [%4];"
                 : "=r"(sk[4]), "=r"(sk[5]), "=r"(sk[6]), "=r"(sk[7])
                 : "r"(ua + so + 2048));
    mbar_wait(full + 8 * (~n & 1), (((n + 1) >> 1) & 1) ^ (ch + step < end ? 0 : 1));
    named_bar_sync(1 + wg, 128);
    shift_h(C_SLOT - so);
    wgmma_wait<1>();
    put(2);
    uint32_t dep = 0;
#pragma unroll
    for (int i = 0; i < 8; i++) dep |= sk[i] = mul_bf2(sk[i], dsk | (dsk << 16));
    CT(4)
    wgmma_wait<0>();
    put(3);
    named_bar_sync((1 + wg) | (dep & rt_zero), 128);
    CT(5)
    fetch(ch + 2 * step, n & 1);
    if (wtid == 96 && n) note(bar, CNT_Y2 + (((ch - step) & 127) >= 112));
    uint2 q[12];
#pragma unroll
    for (int i = 0; i < 12; i++) {
      if (i >= 3) {
        asm volatile("ld.shared.v2.u32 {%0, %1}, [%2];" : "=r"(q[i].x), "=r"(q[i].y) : "r"(xg[i % 3] + (i / 3) * 768));
      } else {
        q[i] = make_uint2(0, 0);
        asm volatile("{\n.reg .pred p;\nsetp.gt.s32 p, %3, 2;\n@p ld.shared.v2.u32 {%0, %1}, [%2];\n}\n"
                     : "+r"(q[i].x), "+r"(q[i].y)
                     : "r"(xg[i]), "r"(w4 + i));
      }
    }
    load_h(hs - ho, 0);
    load_h(hs - ho, 1);
    CT(6)
    uint32_t* dst = reinterpret_cast<uint32_t*>(g_y2T + (size_t)ch * S_LEN) + 64 * w4 + (lane ^ 28);
#pragma unroll
    for (int f = 0; f < 4; f++) {
#pragma unroll
      for (int k = 0; k < 3; k++) {
        own[4 * f] += bf_lo(q[3 * f + k].x);
        own[4 * f + 1] += bf_hi(q[3 * f + k].x);
        own[4 * f + 2] += bf_lo(q[3 * f + k].y);
        own[4 * f + 3] += bf_hi(q[3 * f + k].y);
      }
#pragma unroll
      for (int i = 0; i < 2; i++) {
        dst[256 * f + 32 * i] = add_bf2(pack_bf16(own[4 * f + 2 * i], own[4 * f + 2 * i + 1]), sk[2 * f + i]);
      }
    }
    CT(7)
  }
  named_bar_sync(1 + wg, 128);
  if (wtid == 96 && wg) { TD(8) }
  if (wtid == 96) cnt_signal_release(CNT_Y2 + (((ch - step) & 127) >= 112), 1);
  if (wtid == 64) note(bar, CNT_DONE);
  if (wtid == 96 && wg) { TD(9) }
}

__device__ __forceinline__ void attn_producer(const Maps& maps, uint32_t sbase, bool after_qkv, bool to_out,
                                              bool dry) {
  const uint32_t bar = sbase + BAR_OFF;
  const uint32_t q_full = bar + B_QFULL, q_empty = bar + B_QEMPTY;
  const uint32_t k_full = bar + B_KFULL, k_empty = bar + B_KEMPTY, v_full = bar + B_VFULL, v_empty = bar + B_VEMPTY;
  int ndrained = after_qkv ? 0 : G_STAGES;
  auto wait = [&](uint32_t b, uint32_t par) {
    if (!dry) mbar_wait_sleep(b, par);
  };
  auto drained = [&](int upto) {
#pragma unroll 1
    for (; ndrained <= upto; ndrained++) wait(bar + B_GEMPTY + 8 * ndrained, 1);
  };
  uint32_t st = 0, ph = 1, vs = 0, vp = 1;
  int pend_j = -1, pend_h = 0;
  int round = -1, m = -1, h = 0;
  bool last = false;
#pragma unroll 1
  for (;; round++) {
    uint32_t nitem = 0;
    const int tpost = m >= 3 ? m - 1 : m;
#pragma unroll 1
    for (int t = m < 0 ? -1 : 0; t <= m; t++) {
      const int j = (t < m && (round & 1)) ? m - 1 - t : t;
      if (t >= 0) {
        drained(1 + st);
        wait(k_empty + 8 * st, ph);
        if (!dry) {
          mbar_expect_tx(k_full + 8 * st, A_TILE);
          tma_load_3d(sbase + A_K_OFF + st * A_TILE, &maps.k, k_full + 8 * st, 0, j * 128, h * 2);
        }
        if (++st == 2) { st = 0; ph ^= 1; }
      }
      if (pend_j >= 0) {
        drained(3);
        wait(v_empty + 8 * vs, vp);
        if (!dry) {
          mbar_expect_tx(v_full + 8 * vs, A_TILE);
          tma_load_3d(sbase + A_V_OFF + vs * A_TILE, &maps.v, v_full + 8 * vs, 0, pend_j * 128, pend_h * 2);
        }
        if (++vs == 2) { vs = 0; vp ^= 1; }
      }
      pend_j = j;
      pend_h = h;
      if (t == tpost && !last) {
        nitem = dry ? 1 : item_of(maps, round + 1);
        if (round == (dry ? 0 : 3) || blockIdx.x >= 128) {
          nitem = A_ITEMS;
          cnt_wait(CNT_PREP, dry ? 0 : 260);
          if (to_out) {
            cnt_wait(CNT_CTX, dry ? 0 : A_ITEMS);
            asm volatile("cp.async.bulk.prefetch.L2.global [%0], 4096;" ::"l"(maps.ssm_k + (size_t)conv_first(maps) * S_LEN));
            if (!dry)
              asm volatile("cp.async.bulk.prefetch.L2.global [%0], 4096;" ::"l"(g_kvT + (size_t)conv_first(maps) * S_LEN));
          }
        }
        const uint32_t qs = (round + 1) & 1;
        wait(q_empty + 8 * qs, (((round + 1) >> 1) & 1) ^ 1);
        if (round == 1 && after_qkv) wait(bar + B_QDONE, 0);
        if (round <= 0 && after_qkv) {
          if (!dry) { TD(2) }
          cnt_wait(CNT_KV + round + 1, dry ? 0 : 512);
          if (!dry) { TD(3) }
        }
        if (nitem >= A_ITEMS || (round < 0 && after_qkv && !dry)) {
          if (!dry) mbar_arrive(q_full + 8 * qs);
        } else {
          drained(qs);
          if (!dry) {
            mbar_expect_tx(q_full + 8 * qs, A_TILE);
            tma_load_3d_hint(sbase + A_Q_OFF + qs * A_TILE, &maps.q, q_full + 8 * qs, 0, item_m(nitem) * 128,
                             item_h(nitem) * 2, policy_evict_first());
          }
        }
      }
    }
    if (last) break;
    last = nitem >= A_ITEMS;
    m = last ? -1 : item_m(nitem);
    h = item_h(nitem);
  }
}

__device__ __forceinline__ uint32_t attn_consumer(const Maps& maps, uint32_t smem0, uint32_t sn,
                                                  float (&rest)[64], bool after_qkv) {
  PHASE_PROLOGUE
  const uint32_t q_full = bar + B_QFULL, q_empty = bar + B_QEMPTY;
  const uint32_t k_full = bar + B_KFULL, k_empty = bar + B_KEMPTY, v_full = bar + B_VFULL;
  float o[64], s[64];
  uint32_t p[32];
  float e[32];
  uint32_t dep = 0;
  constexpr int MIDJ = 5;
  float l0 = 0.f, l1 = 0.f, b0 = 0.f, b1 = 0.f;
  const int sched_own = 4 + wg, sched_other = 5 - wg;
  if (wg == 1) named_bar_arrive(4, 256);

  const uint32_t qd0 = (uint32_t)make_desc(sbase + A_Q_OFF + wg * 8192, 16, 0, 0);
  const uint32_t kd0 = (uint32_t)make_desc(sbase + A_K_OFF, 16, 0, 0);
  const uint32_t vd0 = (uint32_t)make_desc(sbase + A_V_OFF, 16384, 0, 0);
  constexpr uint64_t DHI = DESC_SW128 | ((uint64_t)(1024 >> 4) << 32);
  constexpr uint32_t DST = A_TILE >> 4;
  auto issue_qk = [&](uint32_t qd, uint32_t kd) {
#pragma unroll
    for (int kk = 0; kk < 8; kk++) {
      const uint32_t off = ((kk >> 2) * 16384 + (kk & 3) * 32) >> 4;
      wgmma_m64n128_ss(s, DHI | (qd + off), DHI | (kd + off), kk != 0);
    }
    wgmma_commit();
  };
  auto issue_pv = [&](uint32_t vd, bool accumulate, int nk) {
#pragma unroll
    for (int kk = 0; kk < 8; kk++) {
      if (kk < nk)
        wgmma_m64n128_rs_tb(o, p[4 * kk], p[4 * kk + 1], p[4 * kk + 2], p[4 * kk + 3], DHI | (vd + kk * 128),
                            accumulate || (kk != 0));
    }
    wgmma_commit();
  };
  auto exp_lo = [&](float& a0, float& a1) {
#pragma unroll
    for (int j = 0; j < 8; j++) {
      e[4 * j] = ex2(s[4 * j]);
      e[4 * j + 1] = ex2(s[4 * j + 1]);
      e[4 * j + 2] = ex2(s[4 * j + 2]);
      e[4 * j + 3] = ex2(s[4 * j + 3]);
      a0 += e[4 * j];
      a0 += e[4 * j + 1];
      a1 += e[4 * j + 2];
      a1 += e[4 * j + 3];
      if (j == MIDJ) dep = (__float_as_uint(a0) | __float_as_uint(a1)) & rt_zero;
    }
  };
  auto pack_lo = [&]() {
#pragma unroll
    for (int j = 0; j < 16; j++) p[j] = pack_bf16(e[2 * j], e[2 * j + 1]);
  };
  auto finish_p = [&](float& a0, float& a1) {
    pack_lo();
#pragma unroll
    for (int j = 8; j < 16; j++) {
      const float e0 = ex2(s[4 * j]), e1 = ex2(s[4 * j + 1]), e2 = ex2(s[4 * j + 2]), e3 = ex2(s[4 * j + 3]);
      a0 += e0;
      a0 += e1;
      a1 += e2;
      a1 += e3;
      p[2 * j] = pack_bf16(e0, e1);
      p[2 * j + 1] = pack_bf16(e2, e3);
      if (j == 8 + MIDJ) dep = __float_as_uint(a0) & rt_zero;
    }
  };
  auto quad_sum = [&](float t) {
    t += __shfl_xor_sync(0xffffffffu, t, 1);
    return t + __shfl_xor_sync(0xffffffffu, t, 2);
  };
  auto write_o = [&](float i0, float i1) {
    st_wait(bar, wg, sn - 1);
    const int st_row = warp * 16 + (lane & 7) + ((lane >> 3) & 1) * 8;
    const uint32_t so = sbase + A_O_OFF + wg * 16384 + st_row * 128;
#pragma unroll
    for (int j = 0; j < 16; j += 2)
      stmatrix_x4(so + (j >> 3) * 8192 + ((((j & 7) + (lane >> 4)) ^ (lane & 7)) << 4),
                  pack_bf16(o[4 * j] * i0, o[4 * j + 1] * i0), pack_bf16(o[4 * j + 2] * i1, o[4 * j + 3] * i1),
                  pack_bf16(o[4 * j + 4] * i0, o[4 * j + 5] * i0), pack_bf16(o[4 * j + 6] * i1, o[4 * j + 7] * i1));
  };
  auto store_o = [&](uint32_t r, int kind) {
    const uint32_t it = item_of(maps, r);
    st_post(bar, wg, wtid, sn, kind, (INPLACE & 1) || kind != ST_BOX2Q ? &maps.o : &maps.c[0], sbase + A_O_OFF + wg * 16384, item_h(it) * 128,
            item_m(it) * 128 + wg * 64, CNT_CTX + (r >> 1));
    sn++;
  };
  auto mask_half = [&](float* sh) {
    const int u = warp * 16 + (lane >> 2) - (lane & 3) * 2;
#pragma unroll
    for (int j = 0; j < 8; j++) {
      if (8 * j > u) sh[4 * j] = -INFINITY;
      if (8 * j + 1 > u) sh[4 * j + 1] = -INFINITY;
      if (8 * j - 8 > u) sh[4 * j + 2] = -INFINITY;
      if (8 * j - 7 > u) sh[4 * j + 3] = -INFINITY;
    }
  };
  ST(0)
  mbar_wait(q_full, 0);
  if (blockIdx.x >= 128) {
    mbar_arrive_if(bar + B_OFREE + 8 * wg, wtid == 0);
    return sn;
  }
  mbar_wait(k_full, 0);
  named_bar_sync(sched_own, 256);
  wgmma_fence();
  issue_qk(qd0, kd0);
  named_bar_arrive(sched_other, 256);
  fence_regs(rest);
#pragma unroll
  for (int i = 0; i < 64; i++) o[i] = rest[i] * Q_SCALE;
  fence_regs(o);
  wgmma_wait<0>();
  fence_regs(s);
  mbar_arrive_if(k_empty, wtid == 32);
  uint32_t g = 0;
  uint32_t rnd = 0;
  int rem = item_m(item_of(maps, 0));
  uint32_t first = 1;
  uint32_t fl = 0;
#define redo (fl & 1)
#define shifted (fl & 2)
  float d0 = 0.f, d1 = 0.f;
  float pi0 = 1.f, pi1 = 1.f;
  ST(1)
  for (;;) {
    if (shifted) {
#pragma unroll
      for (int j = 0; j < 16; j++) {
        s[4 * j] -= d0;
        s[4 * j + 1] -= d0;
        s[4 * j + 2] -= d1;
        s[4 * j + 3] -= d1;
      }
    }
    if (rem == 0 && !redo) {
      mbar_arrive_if(q_empty + 8 * (rnd & 1), wtid == 96);
      rnd++;
      if (wg == 0) mask_half(s);
      else mask_half(s + 32);
    }
    for (;;) {
      const bool kill = rem == 0 && wg == 0;
      const uint32_t kd = kd0 + ((g + 1) & 1) * DST, vd = vd0 + (g & 1) * DST;
      float a0 = 0.f, a1 = 0.f;
      exp_lo(a0, a1);
      fence_regs(e);
      const uint32_t kb = k_full + 8 * ((g + 1) & 1);
      const uint32_t kpar = ((((g + 1) >> 1) & 1) ^ (g == A_STEPS - 1 ? 1u : 0u)) | dep;
      if (!mbar_try(kb, kpar)) mbar_wait(kb, kpar | ((__float_as_uint(a0) | __float_as_uint(a1)) & rt_zero));
      wgmma_wait<0>();
      fence_regs(o);
      if (kill) {
        mbar_arrive_if(kb + (B_VEMPTY - B_KFULL), wtid == 64 && !redo && g > 0);
        fence_regs(e);
        pack_lo();
#pragma unroll
        for (int j = 16; j < 32; j++) asm volatile("mov.u32 %0, 0;" : "=r"(p[j]));
        goto check;
      }
#pragma unroll
      for (int i = 32; i < 64; i++) asm volatile("" : "+f"(s[i])::"memory");
      mbar_arrive_if(kb + (B_VEMPTY - B_KFULL), wtid == 64 && !redo && g > 0);
      finish_p(a0, a1);
      if (__any_sync(0xffffffffu, !(mbar_try(v_full + 8 * (g & 1), ((g >> 1) & 1) | dep) &
                                    mbar_try(q_full + 8 * (rnd & 1), ((rnd >> 1) & 1) | dep)) ||
                                      !(a0 + a1 < 1.0995116e12f) || !(fminf(a0, a1) > (first ? 9.094947e-13f : -1.f)))) {
      check:
        bool bad = !(a0 + a1 < 1.0995116e12f);
        if (first) bad |= !(fminf(quad_sum(a0), quad_sum(a1)) > 9.094947e-13f);
        if (!redo && __any_sync(0xffffffffu, bad)) {
          d0 = d1 = first ? -INFINITY : 0.f;
#pragma unroll
          for (int j = 0; j < 16; j++) {
            if (j < 8 || !kill) {
              d0 = fmaxf(d0, fmaxf(s[4 * j], s[4 * j + 1]));
              d1 = fmaxf(d1, fmaxf(s[4 * j + 2], s[4 * j + 3]));
            }
          }
#pragma unroll
          for (int x = 1; x <= 2; x++) {
            d0 = fmaxf(d0, __shfl_xor_sync(0xffffffffu, d0, x));
            d1 = fmaxf(d1, __shfl_xor_sync(0xffffffffu, d1, x));
          }
          b0 += d0;
          b1 += d1;
          if (!first) {
            const float al0 = ex2(-d0), al1 = ex2(-d1);
            l0 *= al0;
            l1 *= al1;
#pragma unroll
            for (int j = 0; j < 16; j++) {
              o[4 * j] *= al0;
              o[4 * j + 1] *= al0;
              o[4 * j + 2] *= al1;
              o[4 * j + 3] *= al1;
            }
          }
          fl = 3;
          break;
        }
        mbar_wait(v_full + 8 * (g & 1), (g >> 1) & 1);
        mbar_wait(q_full + 8 * (rnd & 1), (rnd >> 1) & 1);
      }
      named_bar_sync(sched_own, 256);
      if (g == A_STEPS - 1) {
        if (first) write_o(pi0, pi1);
        fence_regs(o);
        wgmma_fence();
        issue_pv(vd, !first, 8);
        named_bar_arrive(sched_other, 256);
        if (first) store_o(rnd - 2, ST_BOX2);
        pi0 = rcp(quad_sum(l0 + a0));
        pi1 = rcp(quad_sum(l1 + a1));
        goto done;
      }
      wgmma_fence();
      issue_qk(qd0 + (rnd & 1) * DST, kd);
      if (first) write_o(pi0, pi1);
      fence_regs(o);
      if (kill) {
        wgmma_fence();
        issue_pv(vd, !first, 4);
      } else {
        wgmma_fence();
        issue_pv(vd, !first, 8);
      }
      named_bar_arrive(sched_other, 256);
      fl &= 2;
      l0 += a0;
      l1 += a1;
      if (rem == 0 || first) {
        if (first && (g > 0 || after_qkv)) store_o(g ? rnd - (rem == 0 ? 2 : 1) : 2, g ? ST_BOX2 : ST_BOX2Q);
        first = rem == 0;
        if (first) {
          pi0 = rcp(quad_sum(l0));
          pi1 = rcp(quad_sum(l1));
          l0 = l1 = b0 = b1 = 0.f;
          fl = 0;
          rem = item_m(item_of(maps, rnd)) + 1;
        }
      }
      rem--;
      g++;
      wgmma_wait<1>();
      fence_regs(s);
      mbar_arrive_if(kb + (B_KEMPTY - B_KFULL), wtid == 32);
      ST(g + 1)
      if (rem == 0 || shifted) {
        d0 = b0;
        d1 = b1;
        break;
      }
    }
  }
done:
#undef redo
#undef shifted
  wgmma_wait<0>();
  fence_regs(o);
  write_o(pi0, pi1);
  store_o(3, ST_BOX2L);
  ST(35)
  return sn;
}

constexpr int O_STAGES = 5;
constexpr int O_STAGE_BYTES = 32768;
constexpr int O_Y_OFF = 5 * 32768;
constexpr int O_X_OFF = 6 * 32768 + 2048;
constexpr int O_NK = HDIM / 64;

__device__ __forceinline__ uint32_t out_stage(uint32_t st) { return ((0x43120u >> (4 * st)) & 7) * O_STAGE_BYTES; }

__device__ __forceinline__ void out_producer(const Maps& maps, uint32_t sbase, bool after_attn, bool dry) {
  const uint32_t bar = sbase + BAR_OFF;
  const uint32_t rank = blockIdx.x & 1;
  const int m_tile = maps.id[blockIdx.x][2] & 15, n_tile = maps.id[blockIdx.x][2] >> 4;
  uint32_t stage = 0, phase = 0;
  const int kx = dry ? 0 : 17 + (blockIdx.x >> 1) % 12;
#pragma unroll 1
  for (int ki = 0; ki < (dry ? 1 : O_NK); ki++) {
    const int kt = (ki & 14) * 4 + ((A_ORDER >> ((ki >> 4) * 4)) & 3) * 2 + (ki & 1);
    const uint32_t fb = bar + B_OFULL + 8 * stage, eb = bar + B_OEMPTY + 8 * stage;
    const uint32_t sa = sbase + out_stage(stage);
    if (ki < O_STAGES) {
      constexpr uint32_t LASTB = B_KEMPTY | ((B_QEMPTY + 8) << 8) | ((B_KEMPTY + 8) << 16) | (B_VEMPTY << 24);
      if (ki > 0 && after_attn) mbar_wait_sleep(bar + ((LASTB >> (8 * ki - 8)) & 255), ki == 2);
      mbar_arrive_cluster_if(eb, 0, !dry);
      mbar_arrive_cluster_if(eb, 1, !dry);
    }
    if (ki == (dry ? 0 : 16)) cnt_wait(CNT_CTX + 1, dry ? 0 : A_ITEMS);
    if (ki == kx) {
      if (after_attn && !dry) {
        mbar_wait_sleep(bar + B_OFREE, 0);
        mbar_wait_sleep(bar + B_OFREE + 8, 0);
      }
      if (!dry) {
        mbar_expect_tx(bar + B_OY, 32768);
        tma_load_4d(sbase + O_X_OFF, &maps.ox, bar + B_OY, n_tile * 128, m_tile);
        tma_load_4d(sbase + O_X_OFF + 16384, &maps.ox, bar + B_OY, n_tile * 128 + 64, m_tile);
      }
    }
    if (!dry) {
      mbar_wait_sleep(eb, phase);
      mbar_expect_tx(fb, O_STAGE_BYTES);
      tma_load_2d_mc(sa + 16384 + rank * 8192, &maps.ob, fb, n_tile * 128 + rank * 64, kt * 64, (uint16_t)3);
      tma_load_4d(sa, &maps.oa, fb, kt * 64, m_tile);
    }
    if (++stage == O_STAGES) { stage = 0; phase ^= 1; }
  }
  if (!dry) mbar_wait_sleep(bar + B_OY2, 0);
}

__device__ __forceinline__ void out_side(const Maps& maps, uint32_t smem0, const float (&gv)[4]) {
  PHASE_PROLOGUE
  const int m_tile = maps.id[blockIdx.x][2] & 15, n_tile = maps.id[blockIdx.x][2] >> 4;
  const int w4 = __shfl_sync(0xffffffffu, warp, 0);
  if (w4 == 0) {
    if (elect_one()) {
      mbar_expect_tx(bar + B_OY, 32768 - 4096);
      TD(10)
      GS(0)
      cnt_wait(CNT_Y2, DM - 128);
      GS(1)
      TD(7)
      for (const uint32_t t = clock(); (uint32_t)clock() - t < (blockIdx.x & 14) * 200;) __nanosleep(32);
      TD(11)
      GS(2)
      fence_proxy_async();
      tma_load_2d(sbase + O_Y_OFF, &maps.y, bar + B_OY, m_tile * 128, n_tile * 128);
      tma_load_2d(sbase + O_Y_OFF + 16384, &maps.y, bar + B_OY, m_tile * 128 + 64, n_tile * 128);
    }
  }
  mbar_wait_sleep(bar + B_OY, 0);
  const int st_row = warp * 16 + (lane & 7) + ((lane >> 3) & 1) * 8;
  const int mrow = (lane & 7) + ((lane >> 4) & 1) * 8;
  const int mchunk = warp * 2 + ((lane >> 3) & 1);
  const uint32_t xrow = sbase + O_X_OFF + st_row * 128;
  const uint32_t yrow = sbase + O_Y_OFF + mrow * 128 + ((mchunk ^ (lane & 7)) << 4);
  uint32_t y[7][4], x[7][4], om[4];
#pragma unroll
  for (int i = 0; i < 4; i++) om[i] = pack_bf16(1.0f - gv[i], 1.0f - gv[i]);
  auto xa = [&](int h, int i) { return xrow + h * 8192 + (i >> 2) * 16384 + ((((i & 3) * 2 + (lane >> 4)) ^ (lane & 7)) << 4); };
  auto load = [&](int r, int h, int i) {
    ldsm4t(y[r], yrow + h * 16384 + i * 2048);
    asm volatile("ldmatrix.sync.aligned.m8n8.x4.shared.b16 {%0, %1, %2, %3}, [%4];"
                 : "=r"(x[r][0]), "=r"(x[r][1]), "=r"(x[r][2]), "=r"(x[r][3])
                 : "r"(xa(h, i)));
  };
  auto store = [&](int r, int h, int i, uint32_t om0, uint32_t om1) {
    stmatrix_x4(xa(h, i), mul_bf2(om0, mul_bf2(x[r][0], y[r][0])), mul_bf2(om1, mul_bf2(x[r][1], y[r][1])),
                mul_bf2(om0, mul_bf2(x[r][2], y[r][2])), mul_bf2(om1, mul_bf2(x[r][3], y[r][3])));
  };
  if (wtid == 0) { TD(12) GS(3) }
#pragma unroll 1
  for (int h = 0; h < 2; h++) {
#pragma unroll
    for (int i = 0; i < 7; i++) load(i, h, i);
#pragma unroll
    for (int i = 0; i < 7; i++) store(i, h, i, h ? om[2] : om[0], h ? om[3] : om[1]);
  }
  if (wtid == 0) { TD(4) GS(4) }
  if (w4 == 0) {
    if (elect_one()) {
      mbar_expect_tx(bar + B_OY2, 4096);
      cnt_wait(CNT_Y2 + 1, 128);
      GS(5)
      for (int i = 0; i < 2; i++)
        tma_load_2d(sbase + O_Y_OFF + i * 16384 + 112 * 128, &maps.y2, bar + B_OY2, m_tile * 128 + i * 64,
                    n_tile * 128 + 112);
    }
  }
  mbar_wait_sleep(bar + B_OY2, 0);
#pragma unroll
  for (int h = 0; h < 2; h++) load(h, h, 7);
#pragma unroll
  for (int h = 0; h < 2; h++) store(h, h, 7, om[2 * h], om[2 * h + 1]);
  __syncwarp();
  mbar_arrive_if(bar + B_OY + 8, lane == 0);
  if (wtid == 0) { TD(13) GS(6) }
#pragma unroll
  for (int i = 0; i < 4; i++) {
    const int h = i >> 1, c = i & 1;
    named_bar_sync(6 + i, 256);
    if (elect_one()) {
      fence_proxy_async();
      tma_store_4d(&maps.oc, sbase + O_X_OFF + c * 16384 + h * 8192 + w4 * 2048, n_tile * 128 + c * 64, 2 * w4,
                   2 * m_tile + h);
      tma_store_commit();
    }
  }
}

__device__ __forceinline__ void out_gemm(const Maps& maps, uint32_t smem0) {
  PHASE_PROLOGUE
  const int m_tile = maps.id[blockIdx.x][2] & 15;
  float acc[2][64];
  undef_regs(acc[0]);
  undef_regs(acc[1]);
  uint32_t stage = 0, phase = 0, prev_stage = 0;
  GT(gti++)
  const float* gp = g_gate + m_tile * 128 + warp * 2 + (lane >> 2) * 8;
  const float gv[4] = {__ldcg(gp), __ldcg(gp + 1), __ldcg(gp + 64), __ldcg(gp + 65)};
  if (wg == 1) {
    out_side(maps, smem0, gv);
    return;
  }
  constexpr uint64_t DHI = DESC_SW128 | ((uint64_t)(1024 >> 4) << 32);
#pragma unroll 1
  for (int kt = 0; kt < O_NK - 1; kt++) {
    uint32_t da = (uint32_t)make_desc(sbase + out_stage(stage), 16, 0, 0);
    uint32_t db = (uint32_t)make_desc(sbase + out_stage(stage) + 16384, 8192, 0, 0);
    asm volatile("" : "+r"(da), "+r"(db));
    mbar_wait(bar + B_OFULL + 8 * stage, phase);
    GT(gti++)
    constexpr int OWAIT = 2;
#pragma unroll
    for (int kk = 0; kk < 4; kk++) {
      wgmma_wait<OWAIT>();
      if (kk == OWAIT)
        mbar_arrive_cluster_if(bar + B_OEMPTY + 8 * prev_stage, wtid >> 6,
                               (wtid & 63) == 32 && kt > 0 && kt - 1 + O_STAGES < O_NK);
      wgmma_fence();
      wgmma_m64n128_ss_tb(acc[0], DHI | (da + kk * 2), DHI | (db + kk * 128), (kt | kk) != 0);
      wgmma_m64n128_ss_tb(acc[1], DHI | (da + 512 + kk * 2), DHI | (db + kk * 128), (kt | kk) != 0);
      wgmma_commit();
    }
    prev_stage = stage;
    if (++stage == O_STAGES) { stage = 0; phase ^= 1; }
  }
  {
    const uint32_t da = (uint32_t)make_desc(sbase + out_stage((O_NK - 1) % O_STAGES), 16, 0, 0);
    const uint32_t db = (uint32_t)make_desc(sbase + out_stage((O_NK - 1) % O_STAGES) + 16384, 8192, 0, 0);
    mbar_wait(bar + B_OFULL + 8 * ((O_NK - 1) % O_STAGES), ((O_NK - 1) / O_STAGES) & 1);
    GT(gti++)
#pragma unroll
    for (int h = 0; h < 2; h++) {
      wgmma_fence();
#pragma unroll
      for (int kk = 0; kk < 4; kk++)
        wgmma_m64n128_ss_tb(acc[h], DHI | (da + h * 512 + kk * 2), DHI | (db + kk * 128), 1);
      wgmma_commit();
    }
  }
  if (tid == 0) { TD(14) }
  const int st_row = warp * 16 + (lane & 7) + ((lane >> 3) & 1) * 8;
  const uint32_t rowa = sbase + O_X_OFF + st_row * 128;
  auto oa = [&](int i) { return rowa + (i >> 3) * 8192 + (i & 4) * 4096 + ((((i & 3) * 2 + (lane >> 4)) ^ (st_row & 7)) << 4); };
  uint32_t b[16][4];
  mbar_wait(bar + B_OY + 8, 0);
#pragma unroll
  for (int i = 0; i < 16; i++)
    asm volatile("ldmatrix.sync.aligned.m8n8.x4.shared.b16 {%0, %1, %2, %3}, [%4];"
                 : "=r"(b[i][0]), "=r"(b[i][1]), "=r"(b[i][2]), "=r"(b[i][3])
                 : "r"(oa(i)));
  uint32_t gg[4];
#pragma unroll
  for (int i = 0; i < 4; i++) gg[i] = pack_bf16(gv[i], gv[i]);
#pragma unroll
  for (int i = 0; i < 16; i++) {
    const int h = i >> 3;
    if (i == 0) wgmma_wait<1>();
    if (i == 8) wgmma_wait<0>();
    if (i % 8 == 0) fence_regs(acc[h]);
    const float* a = acc[h] + 8 * (i & 7);
    const uint32_t gg0 = gg[2 * h], gg1 = gg[2 * h + 1];
    stmatrix_x4(oa(i), fma_bf2(gg0, pack_bf16(a[0], a[1]), b[i][0]), fma_bf2(gg1, pack_bf16(a[2], a[3]), b[i][1]),
                fma_bf2(gg0, pack_bf16(a[4], a[5]), b[i][2]), fma_bf2(gg1, pack_bf16(a[6], a[7]), b[i][3]));
    if (i % 4 == 3) named_bar_arrive(6 + i / 4, 256);
  }
  GT(gti++)
}

__device__ __noinline__ void leave_kernel(int mask) {
  if (!(mask & 4)) return;
  if (atomicAdd(g_cnt + CNT_DONE * 32, 1u) == 2 * gridDim.x - 1) {
    for (int i = 0; i < CNT_N; i++) g_cnt[i * 32] = 0;
  }
}

__device__ __noinline__ void side_jobs(const Maps& maps, uint32_t sbase) {
  const int w12 = __shfl_sync(0xffffffffu, threadIdx.x >> 5, 0);
  gate_rows(maps, sbase, (blockIdx.x - 128) * 12 + w12, w12, threadIdx.x & 31);
  fence_proxy_async();
  __syncthreads();
  if (threadIdx.x == 320) cnt_signal_release(CNT_PREP, 1);
}

__global__ void __launch_bounds__(384, 1) fused_kernel(int mask, const __grid_constant__ Maps maps) {
  extern __shared__ __align__(1024) uint8_t smem_raw[];
  {
    const uint32_t sbase = __shfl_sync(0xffffffffu, smem_u32(smem_raw), 0);
    const uint32_t bar = sbase + BAR_OFF;
    const int tid = threadIdx.x;
    const bool do_qkv = (mask & 1) && blockIdx.x < 128;
    TL(0, 0)
    if (__shfl_sync(0xffffffffu, tid >> 5, 0) == 1 && do_qkv) {
      if (elect_one()) {
        for (int i = 0; i < G_STAGES; i++) mbar_init(bar + B_GFULL + 8 * i, 1);
        fence_barrier_init();
        qkv_producer(maps, sbase, true);
      }
    }
    if (tid == 0) {
      for (int i = 0; i < G_STAGES; i++) {
        mbar_init(bar + B_GEMPTY + 8 * i, 2);
        mbar_init(bar + B_SFULL + 8 * i, 4);
        mbar_init(bar + B_SFREE + 8 * i, 1);
      }
      for (int i = 0; i < 2; i++) {
        mbar_init(bar + B_OFREE + 8 * i, 1);
        mbar_init(bar + B_QFULL + 8 * i, 1);
        mbar_init(bar + B_QEMPTY + 8 * i, 2);
        mbar_init(bar + B_KFULL + 8 * i, 1);
        mbar_init(bar + B_KEMPTY + 8 * i, 2);
        mbar_init(bar + B_VFULL + 8 * i, 1);
        mbar_init(bar + B_VEMPTY + 8 * i, 2);
      }
      for (int i = 0; i < O_STAGES; i++) {
        mbar_init(bar + B_OFULL + 8 * i, 1);
        mbar_init(bar + B_OEMPTY + 8 * i, 2);
      }
      mbar_init(bar + B_OY, 2);
      mbar_init(bar + B_OY2, 1);
      mbar_init(bar + B_OY + 8, 4);
      mbar_init(bar + B_QDONE, 2);
      for (int i = 0; i < 8; i++) mbar_init(bar + B_CFULL + 8 * i, 1);
      for (int i = 0; i < CNT_N; i++) asm volatile("st.shared.u32 [%0], 0;" ::"r"(bar + B_PEND + 4 * i) : "memory");
      fence_barrier_init();
    }
    __syncthreads();
    asm volatile("barrier.cluster.arrive.relaxed.aligned;" ::: "memory");
    if ((mask & 1) && blockIdx.x >= 128) side_jobs(maps, sbase);
  }
  uint32_t smem0 = smem_u32(smem_raw);
  PHASE_PROLOGUE
  const bool do_qkv = (mask & 1) && blockIdx.x < 128, do_out = (mask & 4) && blockIdx.x < 128;
  TL(0, 1)

  if (wg != 2) {
    reg_alloc<232>();
    uint32_t sn = 0;
    float o[64];
    if (do_qkv) {
      sn = qkv_consumer(maps, smem_u32(smem_raw), mask & 2, o);
    } else {
      undef_regs(o);
    }
    TL(0, 2) TL(1, 0) TL(1, 1)
    asm volatile("barrier.cluster.wait.acquire.aligned;" ::: "memory");
    if (mask & 2) {
      sn = attn_consumer(maps, smem_u32(smem_raw), sn, o, mask & 1);
      TL(2, 0)
      if ((mask & 4) && blockIdx.x < 128 && __shfl_sync(0xffffffffu, threadIdx.x, 0) < 128) {
        named_bar_arrive(3, 256);
      } else {
        named_bar_sync(3, 256);
        const uint32_t b2 = blockIdx.x * 2 + (threadIdx.x >> 7);
        const bool fused = mask & 4, mainc = blockIdx.x < 128;
        const uint32_t first = __shfl_sync(0xffffffffu, !fused ? b2 : mainc ? conv_first(maps) : (b2 - 255) * 128 - C_SIDE, 0);
        conv_consumer(maps, smem_u32(smem_raw), first, !fused ? 264 : mainc ? 16 : 1,
                      !fused ? DM : (first | 127) + 1 - (mainc ? C_SIDE : 0));
      }
      TL(1, 2) TL(2, 1) TL(2, 2)
    }
    TL(3, 0) TL(3, 1)
    if ((mask & 4) && blockIdx.x < 128) out_gemm(maps, smem_u32(smem_raw));
    if (!(mask & 2) || blockIdx.x >= 128) {
      uint32_t smem0 = smem_u32(smem_raw);
      PHASE_PROLOGUE
      st_wait(bar, wg, sn - 2);
      st_post(bar, wg, wtid, sn, ST_END, nullptr, 0, 0, 0, -1);
    }
    tma_store_wait_read<0>();
    TL2(3, 2)
  } else {
    reg_dealloc<40>();
    asm volatile("barrier.cluster.wait.acquire.aligned;" ::: "memory");
    const int w = __shfl_sync(0xffffffffu, tid >> 5, 0) - 8;
    if (w < 2) {
      if (do_qkv) prep_agent(maps, sbase, w, lane);
      if (elect_one()) store_agent(bar, w);
    } else {
      if (elect_one()) {
        const bool dry = w == 2;
        if (do_qkv && !dry) qkv_producer(maps, sbase, false);
        if (mask & 2) attn_producer(maps, sbase, do_qkv, do_out, dry);
        if (do_out) out_producer(maps, sbase, mask & 2, dry);
        if (dry) { TD(5) }
      }
      __syncwarp();
      if (w == 2) publisher(bar, tid & 31, !(mask & 2) ? 2 : do_out ? 3 : 4);
      if ((tid & 31) == 0) leave_kernel(mask);
    }
  }
}

typedef CUresult (*PFN_tmapEncode)(CUtensorMap*, CUtensorMapDataType, cuuint32_t, void*, const cuuint64_t*,
                                   const cuuint64_t*, const cuuint32_t*, const cuuint32_t*, CUtensorMapInterleave,
                                   CUtensorMapSwizzle, CUtensorMapL2promotion, CUtensorMapFloatOOBfill);
static PFN_tmapEncode s_encode = nullptr;

static void make_map_2d(CUtensorMap* m, const void* ptr, int rows, int cols, int box_rows) {
  cuuint64_t dims[2] = {(cuuint64_t)cols, (cuuint64_t)rows};
  cuuint64_t strides[1] = {(cuuint64_t)cols * 2};
  cuuint32_t box[2] = {64, (cuuint32_t)box_rows};
  cuuint32_t es[2] = {1, 1};
  s_encode(m, CU_TENSOR_MAP_DATA_TYPE_BFLOAT16, 2, const_cast<void*>(ptr), dims, strides, box, es,
           CU_TENSOR_MAP_INTERLEAVE_NONE, CU_TENSOR_MAP_SWIZZLE_128B, CU_TENSOR_MAP_L2_PROMOTION_L2_256B,
           CU_TENSOR_MAP_FLOAT_OOB_FILL_NONE);
}
static void make_map_3d(CUtensorMap* m, const void* ptr, int rows, int cols, int box_rows, int box_chunks) {
  cuuint64_t dims[3] = {64, (cuuint64_t)rows, (cuuint64_t)(cols / 64)};
  cuuint64_t strides[2] = {(cuuint64_t)cols * 2, 128};
  cuuint32_t box[3] = {64, (cuuint32_t)box_rows, (cuuint32_t)box_chunks};
  cuuint32_t es[3] = {1, 1, 1};
  s_encode(m, CU_TENSOR_MAP_DATA_TYPE_BFLOAT16, 3, const_cast<void*>(ptr), dims, strides, box, es,
           CU_TENSOR_MAP_INTERLEAVE_NONE, CU_TENSOR_MAP_SWIZZLE_128B, CU_TENSOR_MAP_L2_PROMOTION_L2_256B,
           CU_TENSOR_MAP_FLOAT_OOB_FILL_NONE);
}

static void make_map_4d(CUtensorMap* m, const void* ptr, int rows, int cols, int b2, int groups) {
  cuuint64_t dims[4] = {(cuuint64_t)cols, 8, 8, (cuuint64_t)(rows / 64)};
  cuuint64_t strides[3] = {(cuuint64_t)cols * 16, (cuuint64_t)cols * 2, (cuuint64_t)cols * 128};
  cuuint32_t box[4] = {64, 8, (cuuint32_t)b2, (cuuint32_t)groups};
  cuuint32_t es[4] = {1, 1, 1, 1};
  s_encode(m, CU_TENSOR_MAP_DATA_TYPE_BFLOAT16, 4, const_cast<void*>(ptr), dims, strides, box, es,
           CU_TENSOR_MAP_INTERLEAVE_NONE, CU_TENSOR_MAP_SWIZZLE_128B, CU_TENSOR_MAP_L2_PROMOTION_L2_256B,
           CU_TENSOR_MAP_FLOAT_OOB_FILL_NONE);
}

static cudaLaunchConfig_t fused_cfg(cudaLaunchAttribute* at) {
  cudaLaunchConfig_t cfg = {};
  cfg.gridDim = dim3(132);
  cfg.blockDim = dim3(384);
  cfg.dynamicSmemBytes = SMEM_BYTES;
  cfg.stream = cudaStreamPerThread;
  at[0].id = cudaLaunchAttributeClusterDimension;
  at[0].val.clusterDim.x = 2;
  at[0].val.clusterDim.y = 1;
  at[0].val.clusterDim.z = 1;
  cfg.attrs = at;
  cfg.numAttrs = 1;
  return cfg;
}

extern "C" void kernel_launch(void* const* d_in, const int* in_sizes, int n_in, void* d_out, int out_size) {
  const bf16* x = (const bf16*)d_in[0];
  const bf16* ckv = (const bf16*)d_in[1];
  const bf16* wq = (const bf16*)d_in[2];
  const bf16* wuk = (const bf16*)d_in[3];
  const bf16* wuv = (const bf16*)d_in[4];
  const bf16* wo = (const bf16*)d_in[5];
  const bf16* bk = (const bf16*)d_in[7];
  const bf16* bv = (const bf16*)d_in[8];
  const bf16* shift_k = (const bf16*)d_in[9];
  const bf16* ssm_k = (const bf16*)d_in[10];
  const bf16* ssm_D = (const bf16*)d_in[11];
  const bf16* gate_w = (const bf16*)d_in[12];
  bf16* out = (bf16*)d_out;

  static void *pq = nullptr, *pk = nullptr, *pv = nullptr, *pctx = nullptr, *pb = nullptr;
  static int max_clusters = 0;
  if (!s_encode) {
    void* fn = nullptr;
    cudaDriverEntryPointQueryResult qres;
    cudaGetDriverEntryPoint("cuTensorMapEncodeTiled", &fn, cudaEnableDefault, &qres);
    s_encode = (PFN_tmapEncode)fn;
    cudaGetSymbolAddress(&pq, g_q);
    cudaGetSymbolAddress(&pk, g_k);
    cudaGetSymbolAddress(&pv, g_v);
    cudaGetSymbolAddress(&pctx, g_ctx);
    cudaGetSymbolAddress(&pb, g_y2T);
    cudaFuncSetAttribute(fused_kernel, cudaFuncAttributeMaxDynamicSharedMemorySize, SMEM_BYTES);
    cudaLaunchAttribute at[1];
    cudaLaunchConfig_t cfg = fused_cfg(at);
    if (cudaOccupancyMaxActiveClusters(&max_clusters, fused_kernel, &cfg) != cudaSuccess) max_clusters = 0;
  }

  Maps all = {};
  make_map_2d(&all.a[0], x, S_LEN, DM, 128);
  make_map_2d(&all.a[1], ckv, S_LEN, DC, 128);
  make_map_3d(&all.b[0], wq, DM, HDIM, 64, 4);
  make_map_3d(&all.b[1], wuk, DC, HDIM, 64, 4);
  make_map_3d(&all.b[2], wuv, DC, HDIM, 64, 4);
  make_map_2d(&all.c[0], pq, S_LEN, HDIM, 64);
  make_map_2d(&all.c[1], pk, S_LEN, HDIM, 64);
  make_map_2d(&all.c[2], pv, S_LEN, HDIM, 64);
  make_map_3d(&all.q, pq, S_LEN, HDIM, 128, 2);
  make_map_3d(&all.k, pk, S_LEN, HDIM, 128, 2);
  make_map_3d(&all.v, pv, S_LEN, HDIM, 128, 2);
  make_map_2d(&all.o, pctx, S_LEN, HDIM, 64);
  all.ssm_k = ssm_k;
  all.ssm_D = ssm_D;
  make_map_4d(&all.oa, pctx, S_LEN, HDIM, 8, 2);
  make_map_4d(&all.ox, x, S_LEN, DM, 8, 2);
  make_map_2d(&all.ob, wo, HDIM, DM, 64);
  make_map_4d(&all.oc, out, S_LEN, DM, 2, 1);
  make_map_2d(&all.y, pb, DM, S_LEN, 112);
  make_map_2d(&all.y2, pb, DM, S_LEN, 16);

  make_map_2d(&all.bk, bk, S_LEN, DM, 35);
  make_map_2d(&all.bv, bv, S_LEN, DM, 32);
  for (int b = 0; b < 128; b++) {
    const int c = b >> 1, r = b & 1;
    const int G = c < 4 ? 0 : c < 36 ? (c - 4) % 8 : 1 + (c - 36) % 7;
    const int i = c < 4 ? 4 + c : c < 36 ? (c - 4) / 8 : 4 + (c - 36) / 7;
    all.id[b][0] = r + 2 * (i & 1) + 4 * (G & 3) + 16 * (i >> 1) + 64 * (G >> 2);
    all.id[b][1] = r + 2 * i + 16 * G;
    all.id[b][2] = r + 2 * G + 16 * i;
  }
  all.shift_k = shift_k;
  all.x = x;
  all.gate_w = gate_w;
  cudaLaunchAttribute at[1];
  cudaLaunchConfig_t cfg = fused_cfg(at);
  if (max_clusters >= 66) {
    cudaLaunchKernelEx(&cfg, fused_kernel, 7, all);
  } else {
    for (int m = 1; m <= 4; m <<= 1) cudaLaunchKernelEx(&cfg, fused_kernel, m, all);
  }
}
```

```cpp
#include <cuda_runtime.h>
#include <cuda_bf16.h>
#include <cuda.h>
#include <stdint.h>

typedef __nv_bfloat16 bf16;
#define INPLACE 3

constexpr int S_LEN = 2048;
constexpr int DM = 1024;
constexpr int NH = 32;
constexpr int HD = 128;
constexpr int DC = 512;
constexpr int HDIM = NH * HD;

__device__ __align__(1024) bf16 g_q[S_LEN * HDIM];
__device__ __align__(1024) bf16 g_k[S_LEN * HDIM];
__device__ __align__(1024) bf16 g_v[S_LEN * HDIM];
#define g_ctx g_q
__device__ __align__(1024) bf16 g_kvT[DM * S_LEN];
#define g_y2T g_kvT
__device__ __align__(1024) float g_gate[S_LEN];
enum { CNT_KV = 0, CNT_PREP = CNT_KV + 2, CNT_CTX, CNT_Y2 = CNT_CTX + 2, CNT_DONE = CNT_Y2 + 2, CNT_N };
__device__ unsigned int g_cnt[CNT_N * 32];

#define TL(k, i)
#define TL2(k, i)
#define TD(i)
#define LT(i, thr)
#define CLK_DECL
#define CLK_SAMPLE
#define CLK_END
#define CT(i)
#define GT(i)
#define GS(i)
#define GA(i)
#define ST(i)

__device__ __forceinline__ uint32_t smem_u32(const void* p) { return (uint32_t)__cvta_generic_to_shared(p); }

__device__ __forceinline__ void mbar_init(uint32_t bar, uint32_t count) {
  asm volatile("mbarrier.init.shared::cta.b64 [%0], %1;" ::"r"(bar), "r"(count));
}
__device__ __forceinline__ void mbar_expect_tx(uint32_t bar, uint32_t bytes) {
  asm volatile("mbarrier.arrive.expect_tx.shared::cta.b64 _, [%0], %1;" ::"r"(bar), "r"(bytes) : "memory");
}
__device__ __forceinline__ void mbar_arrive(uint32_t bar) {
  asm volatile("mbarrier.arrive.shared::cta.b64 _, [%0];" ::"r"(bar) : "memory");
}
__device__ __forceinline__ void mbar_wait(uint32_t bar, uint32_t parity) {
  uint32_t done;
  uint32_t spins = 0;
  do {
    asm volatile(
        "{\n.reg .pred p;\n"
        "mbarrier.try_wait.parity.shared::cta.b64 p, [%1], %2;\n"
        "selp.u32 %0, 1, 0, p;\n}\n"
        : "=r"(done)
        : "r"(bar), "r"(parity)
        : "memory");
    if (++spins > (1u << 22)) break;
  } while (!done);
}
__device__ __forceinline__ bool mbar_try(uint32_t bar, uint32_t parity) {
  uint32_t done;
  asm volatile(
      "{\n.reg .pred p;\n"
      "mbarrier.try_wait.parity.shared::cta.b64 p, [%1], %2;\n"
      "selp.u32 %0, 1, 0, p;\n}\n"
      : "=r"(done)
      : "r"(bar), "r"(parity)
      : "memory");
  return done != 0;
}
__device__ __forceinline__ bool elect_one() {
  uint32_t pred;
  asm volatile("{\n.reg .pred p;\nelect.sync _|p, 0xffffffff;\nselp.u32 %0, 1, 0, p;\n}\n" : "=r"(pred));
  return pred != 0;
}
__device__ __forceinline__ void mbar_arrive_if(uint32_t bar, bool pred) {
  asm volatile(
      "{\n.reg .pred p;\nsetp.ne.b32 p, %1, 0;\n"
      "@p mbarrier.arrive.shared::cta.b64 _, [%0];\n}\n" ::"r"(bar),
      "r"((uint32_t)pred)
      : "memory");
}
__device__ __forceinline__ void mbar_wait_sleep(uint32_t bar, uint32_t parity) {
  uint32_t done;
  uint32_t spins = 0;
  do {
    asm volatile(
        "{\n.reg .pred p;\n"
        "mbarrier.try_wait.parity.shared::cta.b64 p, [%1], %2, %3;\n"
        "selp.u32 %0, 1, 0, p;\n}\n"
        : "=r"(done)
        : "r"(bar), "r"(parity), "r"(20000u)
        : "memory");
    if (++spins > (1u << 16)) break;
  } while (!done);
}
__device__ __forceinline__ void fence_barrier_init() {
  asm volatile("fence.mbarrier_init.release.cluster;" ::: "memory");
}
__device__ __forceinline__ void fence_proxy_async() {
  asm volatile("fence.proxy.async.shared::cta;" ::: "memory");
}
__device__ __forceinline__ void named_bar_sync(int id, int nthreads) {
  asm volatile("bar.sync %0, %1;" ::"r"(id), "r"(nthreads) : "memory");
}
__device__ __forceinline__ void named_bar_arrive(int id, int nthreads) {
  asm volatile("bar.arrive %0, %1;" ::"r"(id), "r"(nthreads) : "memory");
}
__device__ __forceinline__ void tma_load_2d(uint32_t dst, const CUtensorMap* m, uint32_t bar, int c0, int c1) {
  asm volatile(
      "cp.async.bulk.tensor.2d.shared::cluster.global.mbarrier::complete_tx::bytes [%0], [%1, {%3, %4}], [%2];" ::"r"(dst),
      "l"(reinterpret_cast<uint64_t>(m)), "r"(bar), "r"(c0), "r"(c1)
      : "memory");
}
__device__ __forceinline__ void tma_load_3d(uint32_t dst, const CUtensorMap* m, uint32_t bar, int c0, int c1, int c2) {
  asm volatile(
      "cp.async.bulk.tensor.3d.shared::cluster.global.mbarrier::complete_tx::bytes [%0], [%1, {%3, %4, %5}], [%2];" ::"r"(dst),
      "l"(reinterpret_cast<uint64_t>(m)), "r"(bar), "r"(c0), "r"(c1), "r"(c2)
      : "memory");
}
__device__ __forceinline__ void tma_store_2d(const CUtensorMap* m, uint32_t src, int c0, int c1) {
  asm volatile("cp.async.bulk.tensor.2d.global.shared::cta.bulk_group [%0, {%2, %3}], [%1];" ::"l"(
                   reinterpret_cast<uint64_t>(m)),
               "r"(src), "r"(c0), "r"(c1)
               : "memory");
}
__device__ __forceinline__ void tma_load_4d(uint32_t dst, const CUtensorMap* m, uint32_t bar, int c0, int tile) {
  asm volatile(
      "cp.async.bulk.tensor.4d.shared::cluster.global.mbarrier::complete_tx::bytes [%0], [%1, {%3, %4, %4, %5}], [%2];" ::"r"(dst),
      "l"(reinterpret_cast<uint64_t>(m)), "r"(bar), "r"(c0), "r"(0), "r"(2 * tile)
      : "memory");
}
__device__ __forceinline__ void tma_store_4d(const CUtensorMap* m, uint32_t src, int c0, int c2, int group) {
  asm volatile("cp.async.bulk.tensor.4d.global.shared::cta.bulk_group [%0, {%2, %3, %4, %5}], [%1];" ::"l"(
                   reinterpret_cast<uint64_t>(m)),
               "r"(src), "r"(c0), "r"(0), "r"(c2), "r"(group)
               : "memory");
}
__device__ __forceinline__ void bulk_load(uint32_t dst, const void* src, uint32_t bytes, uint32_t bar) {
  asm volatile("cp.async.bulk.shared::cluster.global.mbarrier::complete_tx::bytes [%0], [%1], %2, [%3];" ::"r"(dst),
               "l"(src), "r"(bytes), "r"(bar)
               : "memory");
}
__device__ __forceinline__ void tma_load_2d_mc(uint32_t dst, const CUtensorMap* m, uint32_t bar, int c0, int c1,
                                               uint16_t mask) {
  asm volatile(
      "cp.async.bulk.tensor.2d.shared::cluster.global.mbarrier::complete_tx::bytes.multicast::cluster [%0], [%1, {%3, "
      "%4}], [%2], %5;" ::"r"(dst),
      "l"(reinterpret_cast<uint64_t>(m)), "r"(bar), "r"(c0), "r"(c1), "h"(mask)
      : "memory");
}
__device__ __forceinline__ void mbar_arrive_cluster_if(uint32_t bar, uint32_t cta, bool pred) {
  asm volatile(
      "{\n.reg .b32 ra;\n.reg .pred p;\nsetp.ne.b32 p, %2, 0;\n"
      "mapa.shared::cluster.u32 ra, %0, %1;\n"
      "@p mbarrier.arrive.shared::cluster.b64 _, [ra];\n}\n" ::"r"(bar),
      "r"(cta), "r"((uint32_t)pred)
      : "memory");
}
__device__ __forceinline__ uint64_t policy_evict_first() {
  uint64_t pol;
  asm volatile("createpolicy.fractional.L2::evict_first.b64 %0, 1.0;" : "=l"(pol));
  return pol;
}
__device__ __forceinline__ void tma_load_2d_hint(uint32_t dst, const CUtensorMap* m, uint32_t bar, int c0, int c1,
                                                 uint64_t pol) {
  asm volatile(
      "cp.async.bulk.tensor.2d.shared::cluster.global.mbarrier::complete_tx::bytes.L2::cache_hint [%0], [%1, {%3, %4}], "
      "[%2], %5;" ::"r"(dst),
      "l"(reinterpret_cast<uint64_t>(m)), "r"(bar), "r"(c0), "r"(c1), "l"(pol)
      : "memory");
}
__device__ __forceinline__ void tma_load_3d_hint(uint32_t dst, const CUtensorMap* m, uint32_t bar, int c0, int c1,
                                                 int c2, uint64_t pol) {
  asm volatile(
      "cp.async.bulk.tensor.3d.shared::cluster.global.mbarrier::complete_tx::bytes.L2::cache_hint [%0], [%1, {%3, %4, "
      "%5}], [%2], %6;" ::"r"(dst),
      "l"(reinterpret_cast<uint64_t>(m)), "r"(bar), "r"(c0), "r"(c1), "r"(c2), "l"(pol)
      : "memory");
}
__device__ __forceinline__ void bulk_load_hint(uint32_t dst, const void* src, uint32_t bytes, uint32_t bar, uint64_t pol) {
  asm volatile(
      "cp.async.bulk.shared::cluster.global.mbarrier::complete_tx::bytes.L2::cache_hint [%0], [%1], %2, [%3], %4;" ::"r"(dst),
      "l"(src), "r"(bytes), "r"(bar), "l"(pol)
      : "memory");
}
__device__ __forceinline__ void cnt_signal_release(int which, uint32_t n) {
  asm volatile("red.release.gpu.global.add.u32 [%0], %1;" ::"l"(g_cnt + which * 32), "r"(n) : "memory");
}
__device__ __forceinline__ void cnt_wait(int which, uint32_t target) {
  uint32_t v, spins = 0;
  while (true) {
    asm volatile("ld.acquire.gpu.global.u32 %0, [%1];" : "=r"(v) : "l"(g_cnt + which * 32) : "memory");
    if (v >= target || ++spins > (1u << 18)) break;
    __nanosleep(64);
  }
  asm volatile("fence.proxy.async.global;" ::: "memory");
}
__device__ __forceinline__ void tma_store_commit() { asm volatile("cp.async.bulk.commit_group;" ::: "memory"); }
template <int N>
__device__ __forceinline__ void tma_store_wait_read() {
  asm volatile("cp.async.bulk.wait_group.read %0;" ::"n"(N) : "memory");
}
template <int N>
__device__ __forceinline__ void tma_store_wait() {
  asm volatile("cp.async.bulk.wait_group %0;" ::"n"(N) : "memory");
}
__device__ __forceinline__ void wgmma_fence() { asm volatile("wgmma.fence.sync.aligned;" ::: "memory"); }
__device__ __forceinline__ void wgmma_commit() { asm volatile("wgmma.commit_group.sync.aligned;" ::: "memory"); }
template <int N>
__device__ __forceinline__ void wgmma_wait() {
  asm volatile("wgmma.wait_group.sync.aligned %0;" ::"n"(N) : "memory");
}
template <int R>
__device__ __forceinline__ void reg_alloc() { asm volatile("setmaxnreg.inc.sync.aligned.u32 %0;" ::"n"(R)); }
template <int R>
__device__ __forceinline__ void reg_dealloc() { asm volatile("setmaxnreg.dec.sync.aligned.u32 %0;" ::"n"(R)); }

__device__ __forceinline__ void stmatrix_x4(uint32_t addr, uint32_t r0, uint32_t r1, uint32_t r2, uint32_t r3) {
  asm volatile("stmatrix.sync.aligned.m8n8.x4.shared.b16 [%0], {%1, %2, %3, %4};" ::"r"(addr), "r"(r0), "r"(r1),
               "r"(r2), "r"(r3)
               : "memory");
}
__device__ __forceinline__ uint32_t pack_bf16(float lo, float hi) {
  uint32_t r;
  asm("cvt.rn.bf16x2.f32 %0, %1, %2;" : "=r"(r) : "f"(hi), "f"(lo));
  return r;
}
__device__ __forceinline__ float bf16_round(float x) { return __bfloat162float(__float2bfloat16_rn(x)); }
__device__ __forceinline__ float bf_lo(uint32_t v) { return __uint_as_float(v << 16); }
__device__ __forceinline__ float bf_hi(uint32_t v) { return __uint_as_float(v & 0xffff0000u); }
__device__ __forceinline__ uint4 lds128(uint32_t a) {
  uint4 v;
  asm volatile("ld.shared.v4.u32 {%0, %1, %2, %3}, [%4];" : "=r"(v.x), "=r"(v.y), "=r"(v.z), "=r"(v.w) : "r"(a));
  return v;
}
__device__ __forceinline__ void sts128(uint32_t a, uint4 v) {
  asm volatile("st.shared.v4.u32 [%0], {%1, %2, %3, %4};" ::"r"(a), "r"(v.x), "r"(v.y), "r"(v.z), "r"(v.w) : "memory");
}
__device__ __forceinline__ uint32_t mul_bf2(uint32_t a, uint32_t b) {
  uint32_t r;
  asm("mul.rn.bf16x2 %0, %1, %2;" : "=r"(r) : "r"(a), "r"(b));
  return r;
}
__device__ __forceinline__ uint32_t add_bf2(uint32_t a, uint32_t b) {
  uint32_t r;
  asm("add.rn.bf16x2 %0, %1, %2;" : "=r"(r) : "r"(a), "r"(b));
  return r;
}
__device__ __forceinline__ float ex2(float x) {
  float y;
  asm("ex2.approx.ftz.f32 %0, %1;" : "=f"(y) : "f"(x));
  return y;
}
__device__ __forceinline__ float rcp(float x) {
  float y;
  asm("rcp.approx.ftz.f32 %0, %1;" : "=f"(y) : "f"(x));
  return y;
}
template <int N>
__device__ __forceinline__ void fence_regs(float (&r)[N]) {
#pragma unroll
  for (int i = 0; i < N; i++) asm volatile("" : "+f"(r[i])::"memory");
}

template <int N>
__device__ __forceinline__ void undef_regs(float (&r)[N]) {
#pragma unroll
  for (int i = 0; i < N; i++) asm volatile("" : "=f"(r[i]));
}
template <int N>
__device__ __forceinline__ void fence_regs_u(uint32_t (&r)[N]) {
#pragma unroll
  for (int i = 0; i < N; i++) asm volatile("" : "+r"(r[i])::"memory");
}

constexpr uint64_t DESC_SW128 = 1ull << 62;
__device__ __forceinline__ uint64_t make_desc(uint32_t addr, uint32_t lbo_bytes, uint32_t sbo_bytes, uint64_t swz) {
  return (uint64_t)((addr & 0x3FFFF) >> 4) | ((uint64_t)((lbo_bytes & 0x3FFFF) >> 4) << 16) |
         ((uint64_t)((sbo_bytes & 0x3FFFF) >> 4) << 32) | swz;
}

__device__ __forceinline__ uint64_t desc_add(uint64_t d, uint32_t off16) {
  return (d & 0xFFFFFFFF00000000ull) | (uint64_t)((uint32_t)d + off16);
}

__device__ __forceinline__ void wgmma_m64n256_ss_tb(float (&d)[128], uint64_t da, uint64_t db, int sd) {
  asm volatile(
    "{\n.reg .pred p;\nsetp.ne.b32 p, %130, 0;\n"
    "wgmma.mma_async.sync.aligned.m64n256k16.f32.bf16.bf16 "
    "{%0, %1, %2, %3, %4, %5, %6, %7, %8, %9, %10, %11, %12, %13, %14, %15, %16, %17, %18, %19, %20, %21, %22, %23, %24, %25, %26, %27, %28, %29, %30, %31, %32, %33, %34, %35, %36, %37, %38, %39, %40, %41, %42, %43, %44, %45, %46, %47, %48, %49, %50, %51, %52, %53, %54, %55, %56, %57, %58, %59, %60, %61, %62, %63, %64, %65, %66, %67, %68, %69, %70, %71, %72, %73, %74, %75, %76, %77, %78, %79, %80, %81, %82, %83, %84, %85, %86, %87, %88, %89, %90, %91, %92, %93, %94, %95, %96, %97, %98, %99, %100, %101, %102, %103, %104, %105, %106, %107, %108, %109, %110, %111, %112, %113, %114, %115, %116, %117, %118, %119, %120, %121, %122, %123, %124, %125, %126, %127}, %128, %129, p, 1, 1, 0, 1;\n}\n"
    : "+f"(d[0]), "+f"(d[1]), "+f"(d[2]), "+f"(d[3]), "+f"(d[4]), "+f"(d[5]), "+f"(d[6]), "+f"(d[7]), "+f"(d[8]), "+f"(d[9]), "+f"(d[10]), "+f"(d[11]), "+f"(d[12]), "+f"(d[13]), "+f"(d[14]), "+f"(d[15]), "+f"(d[16]), "+f"(d[17]), "+f"(d[18]), "+f"(d[19]), "+f"(d[20]), "+f"(d[21]), "+f"(d[22]), "+f"(d[23]), "+f"(d[24]), "+f"(d[25]), "+f"(d[26]), "+f"(d[27]), "+f"(d[28]), "+f"(d[29]), "+f"(d[30]), "+f"(d[31]), "+f"(d[32]), "+f"(d[33]), "+f"(d[34]), "+f"(d[35]), "+f"(d[36]), "+f"(d[37]), "+f"(d[38]), "+f"(d[39]), "+f"(d[40]), "+f"(d[41]), "+f"(d[42]), "+f"(d[43]), "+f"(d[44]), "+f"(d[45]), "+f"(d[46]), "+f"(d[47]), "+f"(d[48]), "+f"(d[49]), "+f"(d[50]), "+f"(d[51]), "+f"(d[52]), "+f"(d[53]), "+f"(d[54]), "+f"(d[55]), "+f"(d[56]), "+f"(d[57]), "+f"(d[58]), "+f"(d[59]), "+f"(d[60]), "+f"(d[61]), "+f"(d[62]), "+f"(d[63]), "+f"(d[64]), "+f"(d[65]), "+f"(d[66]), "+f"(d[67]), "+f"(d[68]), "+f"(d[69]), "+f"(d[70]), "+f"(d[71]), "+f"(d[72]), "+f"(d[73]), "+f"(d[74]), "+f"(d[75]), "+f"(d[76]), "+f"(d[77]), "+f"(d[78]), "+f"(d[79]), "+f"(d[80]), "+f"(d[81]), "+f"(d[82]), "+f"(d[83]), "+f"(d[84]), "+f"(d[85]), "+f"(d[86]), "+f"(d[87]), "+f"(d[88]), "+f"(d[89]), "+f"(d[90]), "+f"(d[91]), "+f"(d[92]), "+f"(d[93]), "+f"(d[94]), "+f"(d[95]), "+f"(d[96]), "+f"(d[97]), "+f"(d[98]), "+f"(d[99]), "+f"(d[100]), "+f"(d[101]), "+f"(d[102]), "+f"(d[103]), "+f"(d[104]), "+f"(d[105]), "+f"(d[106]), "+f"(d[107]), "+f"(d[108]), "+f"(d[109]), "+f"(d[110]), "+f"(d[111]), "+f"(d[112]), "+f"(d[113]), "+f"(d[114]), "+f"(d[115]), "+f"(d[116]), "+f"(d[117]), "+f"(d[118]), "+f"(d[119]), "+f"(d[120]), "+f"(d[121]), "+f"(d[122]), "+f"(d[123]), "+f"(d[124]), "+f"(d[125]), "+f"(d[126]), "+f"(d[127])
    : "l"(da), "l"(db), "r"(sd));
}

__device__ __forceinline__ void wgmma_m64n128_ss(float (&d)[64], uint64_t da, uint64_t db, int sd) {
  asm volatile(
    "{\n.reg .pred p;\nsetp.ne.b32 p, %66, 0;\n"
    "wgmma.mma_async.sync.aligned.m64n128k16.f32.bf16.bf16 "
    "{%0, %1, %2, %3, %4, %5, %6, %7, %8, %9, %10, %11, %12, %13, %14, %15, %16, %17, %18, %19, %20, %21, %22, %23, %24, %25, %26, %27, %28, %29, %30, %31, %32, %33, %34, %35, %36, %37, %38, %39, %40, %41, %42, %43, %44, %45, %46, %47, %48, %49, %50, %51, %52, %53, %54, %55, %56, %57, %58, %59, %60, %61, %62, %63}, %64, %65, p, 1, 1, 0, 0;\n}\n"
    : "+f"(d[0]), "+f"(d[1]), "+f"(d[2]), "+f"(d[3]), "+f"(d[4]), "+f"(d[5]), "+f"(d[6]), "+f"(d[7]), "+f"(d[8]), "+f"(d[9]), "+f"(d[10]), "+f"(d[11]), "+f"(d[12]), "+f"(d[13]), "+f"(d[14]), "+f"(d[15]), "+f"(d[16]), "+f"(d[17]), "+f"(d[18]), "+f"(d[19]), "+f"(d[20]), "+f"(d[21]), "+f"(d[22]), "+f"(d[23]), "+f"(d[24]), "+f"(d[25]), "+f"(d[26]), "+f"(d[27]), "+f"(d[28]), "+f"(d[29]), "+f"(d[30]), "+f"(d[31]), "+f"(d[32]), "+f"(d[33]), "+f"(d[34]), "+f"(d[35]), "+f"(d[36]), "+f"(d[37]), "+f"(d[38]), "+f"(d[39]), "+f"(d[40]), "+f"(d[41]), "+f"(d[42]), "+f"(d[43]), "+f"(d[44]), "+f"(d[45]), "+f"(d[46]), "+f"(d[47]), "+f"(d[48]), "+f"(d[49]), "+f"(d[50]), "+f"(d[51]), "+f"(d[52]), "+f"(d[53]), "+f"(d[54]), "+f"(d[55]), "+f"(d[56]), "+f"(d[57]), "+f"(d[58]), "+f"(d[59]), "+f"(d[60]), "+f"(d[61]), "+f"(d[62]), "+f"(d[63])
    : "l"(da), "l"(db), "r"(sd));
}

__device__ __forceinline__ void wgmma_m64n128_ss_tb(float (&d)[64], uint64_t da, uint64_t db, int sd) {
  asm volatile(
    "{\n.reg .pred p;\nsetp.ne.b32 p, %66, 0;\n"
    "wgmma.mma_async.sync.aligned.m64n128k16.f32.bf16.bf16 "
    "{%0, %1, %2, %3, %4, %5, %6, %7, %8, %9, %10, %11, %12, %13, %14, %15, %16, %17, %18, %19, %20, %21, %22, %23, %24, %25, %26, %27, %28, %29, %30, %31, %32, %33, %34, %35, %36, %37, %38, %39, %40, %41, %42, %43, %44, %45, %46, %47, %48, %49, %50, %51, %52, %53, %54, %55, %56, %57, %58, %59, %60, %61, %62, %63}, %64, %65, p, 1, 1, 0, 1;\n}\n"
    : "+f"(d[0]), "+f"(d[1]), "+f"(d[2]), "+f"(d[3]), "+f"(d[4]), "+f"(d[5]), "+f"(d[6]), "+f"(d[7]), "+f"(d[8]), "+f"(d[9]), "+f"(d[10]), "+f"(d[11]), "+f"(d[12]), "+f"(d[13]), "+f"(d[14]), "+f"(d[15]), "+f"(d[16]), "+f"(d[17]), "+f"(d[18]), "+f"(d[19]), "+f"(d[20]), "+f"(d[21]), "+f"(d[22]), "+f"(d[23]), "+f"(d[24]), "+f"(d[25]), "+f"(d[26]), "+f"(d[27]), "+f"(d[28]), "+f"(d[29]), "+f"(d[30]), "+f"(d[31]), "+f"(d[32]), "+f"(d[33]), "+f"(d[34]), "+f"(d[35]), "+f"(d[36]), "+f"(d[37]), "+f"(d[38]), "+f"(d[39]), "+f"(d[40]), "+f"(d[41]), "+f"(d[42]), "+f"(d[43]), "+f"(d[44]), "+f"(d[45]), "+f"(d[46]), "+f"(d[47]), "+f"(d[48]), "+f"(d[49]), "+f"(d[50]), "+f"(d[51]), "+f"(d[52]), "+f"(d[53]), "+f"(d[54]), "+f"(d[55]), "+f"(d[56]), "+f"(d[57]), "+f"(d[58]), "+f"(d[59]), "+f"(d[60]), "+f"(d[61]), "+f"(d[62]), "+f"(d[63])
    : "l"(da), "l"(db), "r"(sd));
}

__device__ __forceinline__ void wgmma_m64n128_rs_tb(float* d, uint32_t a0, uint32_t a1, uint32_t a2, uint32_t a3, uint64_t db, int sd) {
  asm volatile(
    "{\n.reg .pred p;\nsetp.ne.b32 p, %69, 0;\n"
    "wgmma.mma_async.sync.aligned.m64n128k16.f32.bf16.bf16 "
    "{%0, %1, %2, %3, %4, %5, %6, %7, %8, %9, %10, %11, %12, %13, %14, %15, %16, %17, %18, %19, %20, %21, %22, %23, %24, %25, %26, %27, %28, %29, %30, %31, %32, %33, %34, %35, %36, %37, %38, %39, %40, %41, %42, %43, %44, %45, %46, %47, %48, %49, %50, %51, %52, %53, %54, %55, %56, %57, %58, %59, %60, %61, %62, %63}, {%64, %65, %66, %67}, %68, p, 1, 1, 1;\n}\n"
    : "+f"(d[0]), "+f"(d[1]), "+f"(d[2]), "+f"(d[3]), "+f"(d[4]), "+f"(d[5]), "+f"(d[6]), "+f"(d[7]), "+f"(d[8]), "+f"(d[9]), "+f"(d[10]), "+f"(d[11]), "+f"(d[12]), "+f"(d[13]), "+f"(d[14]), "+f"(d[15]), "+f"(d[16]), "+f"(d[17]), "+f"(d[18]), "+f"(d[19]), "+f"(d[20]), "+f"(d[21]), "+f"(d[22]), "+f"(d[23]), "+f"(d[24]), "+f"(d[25]), "+f"(d[26]), "+f"(d[27]), "+f"(d[28]), "+f"(d[29]), "+f"(d[30]), "+f"(d[31]), "+f"(d[32]), "+f"(d[33]), "+f"(d[34]), "+f"(d[35]), "+f"(d[36]), "+f"(d[37]), "+f"(d[38]), "+f"(d[39]), "+f"(d[40]), "+f"(d[41]), "+f"(d[42]), "+f"(d[43]), "+f"(d[44]), "+f"(d[45]), "+f"(d[46]), "+f"(d[47]), "+f"(d[48]), "+f"(d[49]), "+f"(d[50]), "+f"(d[51]), "+f"(d[52]), "+f"(d[53]), "+f"(d[54]), "+f"(d[55]), "+f"(d[56]), "+f"(d[57]), "+f"(d[58]), "+f"(d[59]), "+f"(d[60]), "+f"(d[61]), "+f"(d[62]), "+f"(d[63])
    : "r"(a0), "r"(a1), "r"(a2), "r"(a3), "l"(db), "r"(sd));
}

__device__ __forceinline__ void wgmma_m64n64_rs(float (&d)[32], const uint32_t* a, uint64_t db, int sd) {
  asm volatile(
    "{\n.reg .pred p;\nsetp.ne.b32 p, %37, 0;\n"
    "wgmma.mma_async.sync.aligned.m64n64k16.f32.bf16.bf16 "
    "{%0, %1, %2, %3, %4, %5, %6, %7, %8, %9, %10, %11, %12, %13, %14, %15, %16, %17, %18, %19, %20, %21, %22, %23, %24, %25, %26, %27, %28, %29, %30, %31}, {%32, %33, %34, %35}, %36, p, 1, 1, 0;\n}\n"
    : "+f"(d[0]), "+f"(d[1]), "+f"(d[2]), "+f"(d[3]), "+f"(d[4]), "+f"(d[5]), "+f"(d[6]), "+f"(d[7]), "+f"(d[8]), "+f"(d[9]), "+f"(d[10]), "+f"(d[11]), "+f"(d[12]), "+f"(d[13]), "+f"(d[14]), "+f"(d[15]), "+f"(d[16]), "+f"(d[17]), "+f"(d[18]), "+f"(d[19]), "+f"(d[20]), "+f"(d[21]), "+f"(d[22]), "+f"(d[23]), "+f"(d[24]), "+f"(d[25]), "+f"(d[26]), "+f"(d[27]), "+f"(d[28]), "+f"(d[29]), "+f"(d[30]), "+f"(d[31])
    : "r"(a[0]), "r"(a[1]), "r"(a[2]), "r"(a[3]), "l"(db), "r"(sd));
}

constexpr int G_STAGES = 4;
constexpr int G_A_BYTES = 128 * 64 * 2;
constexpr int G_B_BYTES = 256 * 64 * 2;
constexpr int G_STAGE_BYTES = G_A_BYTES + G_B_BYTES;
constexpr int G_STG_OFF = G_STAGES * G_STAGE_BYTES;
constexpr int BAR_OFF = G_STG_OFF + 32768 + 2048;
constexpr int SMEM_BYTES = BAR_OFF + 1024;
constexpr int B_GFULL = 0, B_GEMPTY = 32, B_OY2 = 64, B_PFULL = 224;
constexpr int B_KFULL = 80, B_KEMPTY = 96, B_VFULL = 112, B_VEMPTY = 128, B_QFULL = 144, B_QEMPTY = 160,
              B_QDONE = 184;
constexpr int B_CFULL = 192;
constexpr int B_OFREE = 256, B_OFULL = 272, B_OEMPTY = 320, B_OY = 368;
constexpr int B_SFULL = 392, B_SFREE = 424, B_PEND = 456, B_SCMD = 512;

#define PHASE_PROLOGUE                                                                \
  uint32_t tid, rt_zero;                                                              \
  asm volatile("mov.u32 %0, %%tid.x;" : "=r"(tid));                                   \
  asm volatile("mov.u32 %0, %%nctaid.y;" : "=r"(rt_zero));                            \
  asm volatile("" : "+r"(smem0));                                                     \
  rt_zero = __shfl_sync(0xffffffffu, rt_zero >> 8, 0);   \
  const uint32_t sbase = __shfl_sync(0xffffffffu, smem0, 0);                          \
  const uint32_t bar = sbase + BAR_OFF;                                               \
  const int wg = __shfl_sync(0xffffffffu, tid >> 7, 0);                               \
  const int warp = (tid >> 5) & 3, lane = tid & 31, wtid = tid & 127;                 \
  (void)rt_zero; (void)bar; (void)warp; (void)lane; (void)wtid;

enum { ST_END = 0, ST_BOX1, ST_BOX2, ST_BOX2Q, ST_BOX2L };
__device__ __forceinline__ void st_post(uint32_t bar, int wg, int wtid, uint32_t n, int kind, const void* dst,
                                        uint32_t src, int c0, int c1, int sig) {
  if (wtid == 0) {
    const uint32_t c = bar + B_SCMD + wg * 64 + (n & 1) * 32;
    const uint64_t d = reinterpret_cast<uint64_t>(dst);
    sts128(c, make_uint4(kind, src, c0, c1));
    sts128(c + 16, make_uint4((uint32_t)d, (uint32_t)(d >> 32), sig, 0));
  }
  fence_proxy_async();
  __syncwarp();
  mbar_arrive_if(bar + B_SFULL + wg * 16 + (n & 1) * 8, (wtid & 31) == 0);
}
__device__ __forceinline__ void st_wait(uint32_t bar, int wg, uint32_t n) {
  const uint32_t b = bar + B_SFREE + wg * 16 + (n & 1) * 8;
  if (!mbar_try(b, ~(n >> 1) & 1)) mbar_wait(b, ~(n >> 1) & 1);
}
__device__ __forceinline__ void note(uint32_t bar, uint32_t cnt) {
  asm volatile("red.release.cta.shared.add.u32 [%0], 1;" ::"r"(bar + B_PEND + 4 * cnt) : "memory");
}
__device__ __forceinline__ void store_agent(uint32_t bar, int wg) {
  mbar_arrive(bar + B_SFREE + wg * 16);
  mbar_arrive(bar + B_SFREE + wg * 16 + 8);
  for (uint32_t n = 0;; n++) {
    mbar_wait_sleep(bar + B_SFULL + wg * 16 + (n & 1) * 8, (n >> 1) & 1);
    const uint4 c = lds128(bar + B_SCMD + wg * 64 + (n & 1) * 32);
    const uint4 d = lds128(bar + B_SCMD + wg * 64 + (n & 1) * 32 + 16);
    if (c.x == ST_END) break;
    const CUtensorMap* dst = reinterpret_cast<const CUtensorMap*>((uint64_t)d.x | ((uint64_t)d.y << 32));
    tma_store_2d(dst, c.y, c.z, c.w);
    if (c.x >= ST_BOX2) tma_store_2d(dst, c.y + 8192, c.z + 64, c.w);
    tma_store_commit();
    tma_store_wait_read<0>();
    mbar_arrive(bar + B_SFREE + wg * 16 + (n & 1) * 8);
    if (c.x == ST_BOX2L) mbar_arrive(bar + B_OFREE + 8 * wg);
    if ((int)d.z >= 0) {
      tma_store_wait<0>();
      if (d.z == 0) { TD(6) }
      asm volatile("fence.proxy.async.global;" ::: "memory");
      if (c.x == ST_BOX2Q) mbar_arrive(bar + B_QDONE);
      else note(bar, d.z);
      if (c.x == ST_BOX2L) break;
    }
  }
  note(bar, CNT_DONE);
}

struct Maps {
  const bf16 *shift_k, *x, *gate_w, *ssm_k, *ssm_D;
  uint8_t id[128][4];
  CUtensorMap a[2];
  CUtensorMap b[3];
  CUtensorMap c[3];
  CUtensorMap bk, bv;
  CUtensorMap q, k, v, o;
  CUtensorMap oa, ob, oc, ox;
  CUtensorMap y, y2;
};

constexpr int P_SLOT = 67 * 128, P_V = 35 * 128, P_TAPS = 2 * P_SLOT;
__device__ __forceinline__ void ldsm4t(uint32_t (&r)[4], uint32_t a) {
  asm volatile("ldmatrix.sync.aligned.m8n8.x4.trans.shared.b16 {%0, %1, %2, %3}, [%4];"
               : "=r"(r[0]), "=r"(r[1]), "=r"(r[2]), "=r"(r[3])
               : "r"(a));
}
__device__ __forceinline__ uint32_t fma_bf2(uint32_t a, uint32_t b, uint32_t c) {
  uint32_t r;
  asm("fma.rn.bf16x2 %0, %1, %2, %3;" : "=r"(r) : "r"(a), "r"(b), "r"(c));
  return r;
}
__device__ __forceinline__ void prep_agent(const Maps& maps, uint32_t sbase, int w, int lane) {
  const uint32_t bar = sbase + BAR_OFF, pb = bar + B_PFULL + w * 16;
  const int d0 = (blockIdx.x >> 3) * 64, t0 = (blockIdx.x & 7) * 256 + w * 128;
  mbar_wait_sleep(bar + B_GFULL + 8 * (G_STAGES - 1), 0);
#pragma unroll 1
  for (int i = -1; i < 4; i++) {
    GA(82 + 2 * i)
    if (i >= 0) mbar_wait_sleep(pb + (i & 1) * 8, i >> 1);
    GA(83 + 2 * i)
    const uint32_t so = sbase + G_STG_OFF + w * (P_TAPS + 512) + (i & 1) * P_SLOT;
    if (i < 3 && elect_one()) {
      const uint32_t b = pb + (~i & 1) * 8, dst = so + (i & 1 ? -P_SLOT : P_SLOT);
      mbar_expect_tx(b, i < 0 ? P_SLOT + 512 : P_SLOT);
      const uint64_t pol = policy_evict_first();
      tma_load_2d_hint(dst, &maps.bk, b, d0, t0 + 32 * i + 29, pol);
      tma_load_2d_hint(dst + P_V, &maps.bv, b, d0, t0 + 32 * i + 32, pol);
      if (i < 0) bulk_load(sbase + G_STG_OFF + P_TAPS, maps.shift_k + d0 * 4, 512, b);
    }
    if (i < 0) continue;
    uint32_t ak[4];
#pragma unroll
    for (int r = 0; r < 4; r++) {
      const uint32_t a = so / 128 + r + 4 * (lane & 6) + (((((lane >> 2) ^ lane) & 6) + (lane & 1)) ^ 7);
      ak[r] = a * 128 + (a & 7) * 16;
    }
    bf16* dst = g_kvT + (size_t)(d0 + (lane >> 2)) * S_LEN + t0 + ((lane & 3) + 4 * i) * 8;
#pragma unroll 1
    for (int cg = 0; cg < 128; cg += 16) {
      uint32_t t01, t23, k[4][4], v[4];
      asm volatile("ld.shared.v2.u32 {%0, %1}, [%2];"
                   : "=r"(t01), "=r"(t23)
                   : "r"(sbase + G_STG_OFF + P_TAPS + cg * 4 + (lane >> 2) * 8));
#pragma unroll
      for (int r = 0; r < 4; r++) ldsm4t(k[r], ak[r] ^ cg);
      ldsm4t(v, (ak[3] ^ cg) + 4096);
      const uint32_t w0 = __byte_perm(t01, 0, 0x1010), w1 = __byte_perm(t01, 0, 0x3232);
      const uint32_t w2 = __byte_perm(t23, 0, 0x1010), w3 = __byte_perm(t23, 0, 0x3232);
#pragma unroll
      for (int j = 0; j < 4; j++)
        v[j] = mul_bf2(fma_bf2(k[3][j], w0, fma_bf2(k[2][j], w1, fma_bf2(k[1][j], w2, mul_bf2(k[0][j], w3)))), v[j]);
      const bool s1 = lane & 1, s2 = lane & 2;
      const uint32_t a0 = s1 ? v[1] : v[0], a1 = s1 ? v[0] : v[1], a2 = s1 ? v[3] : v[2], a3 = s1 ? v[2] : v[3];
      *reinterpret_cast<uint4*>(dst) = make_uint4(s2 ? a2 : a0, s2 ? a3 : a1, s2 ? a0 : a2, s2 ? a1 : a3);
      dst += 8 * S_LEN;
    }
    fence_proxy_async();
    __syncwarp();
  }
  GA(90)
  if (lane == 0) note(bar, CNT_PREP);
  __syncwarp();
  GA(91)
}

__device__ __forceinline__ void qkv_tile(const Maps& maps, int it, int& which, int& m_tile, int& n_tile) {
  const bool q = it == 0 || it >= 5;
  const int b = maps.id[blockIdx.x][it >= 5];
  which = q ? 0 : 2 - (it & 1);
  m_tile = b & 15;
  n_tile = (b >> 4) * 2 + ((0x19 >> it) & 1);
}

constexpr int G_NTILES = 6;
__device__ __forceinline__ void qkv_producer(const Maps& maps, uint32_t sbase, bool first) {
  const uint32_t bar = sbase + BAR_OFF;
  uint32_t stage = 0, phase = 0;
#pragma unroll 1
  for (int it = 0; it < (first ? 1 : G_NTILES); it++) {
    int which, m_tile, n_tile;
    qkv_tile(maps, it, which, m_tile, n_tile);
    const CUtensorMap* ma = &maps.a[which == 0 ? 0 : 1];
    const CUtensorMap* mb = &maps.b[which];
    const int nk = first ? G_STAGES : which == 0 ? 16 : 8;
#pragma unroll 1
    for (int kt = (it == 0 && !first) ? G_STAGES : 0; kt < nk; kt++) {
      if (!first) mbar_wait_sleep(bar + B_GEMPTY + 8 * stage, phase);
      const uint32_t fb = bar + B_GFULL + 8 * stage;
      const uint32_t sa = sbase + stage * G_STAGE_BYTES;
      mbar_expect_tx(fb, G_STAGE_BYTES);
      tma_load_2d(sa, ma, fb, kt * 64, m_tile * 128);
      tma_load_3d(sa + G_A_BYTES, mb, fb, 0, kt * 64, n_tile * 4);
      if (++stage == G_STAGES) { stage = 0; phase ^= 1; }
      {
        const int b = maps.id[blockIdx.x][1];
        if (it == 2 && kt == (b & 7))
          asm volatile("cp.async.bulk.prefetch.tensor.3d.L2.global.tile [%0, {%1, %2, %3}];" ::"l"(&maps.b[1 + (b >> 6)]),
                       "r"(0), "r"(((b >> 3) & 7) * 64), "r"((b & 7) * 8 + 4)
                       : "memory");
        if (it == 3 && kt == (b & 7))
          asm volatile("cp.async.bulk.prefetch.tensor.3d.L2.global.tile [%0, {%1, %2, %3}];" ::"l"(&maps.b[0]), "r"(0),
                       "r"((b & 15) * 64), "r"((b >> 4) * 8)
                       : "memory");
      }
    }
  }
}

__device__ __noinline__ void publisher(uint32_t bar, int lane, uint32_t nsrc) {
  uint32_t done = 0;
  CLK_DECL
#pragma unroll 1
  for (uint32_t spins = 0; done < nsrc && spins < (1u << 20); spins++) {
    CLK_SAMPLE
    uint32_t v = 0;
    if (lane < CNT_N)
      asm volatile("atom.acquire.cta.shared.exch.b32 %0, [%1], 0;" : "=r"(v) : "r"(bar + B_PEND + 4 * lane) : "memory");
    done += __shfl_sync(0xffffffffu, v, CNT_DONE);
    if (lane == CNT_DONE) v = 0;
    if (done == nsrc && lane < CNT_DONE) {
      uint32_t w;
      asm volatile("atom.acquire.cta.shared.exch.b32 %0, [%1], 0;" : "=r"(w) : "r"(bar + B_PEND + 4 * lane) : "memory");
      v += w;
    }
    if (v && lane == 0) { TD(0) }
    if (v) cnt_signal_release(lane, v);
    if (v && lane == 0) { TD(1) }
    if (!__any_sync(0xffffffffu, v != 0)) __nanosleep(200);
  }
  CLK_END
  __threadfence();
  __syncwarp();
}

__device__ __forceinline__ void gate_rows(const Maps& maps, uint32_t sbase, int w48, int w12, int lane) {
  const uint32_t buf = sbase + w12 * 16384, gb = sbase + BAR_OFF + 768 + w12 * 16;
  if (lane == 0) {
    mbar_init(gb, 1);
    mbar_init(gb + 8, 1);
    fence_barrier_init();
    for (int i = 0; i < 2; i++) {
      mbar_expect_tx(gb + 8 * i, 8192);
      bulk_load(buf + i * 8192, maps.x + (size_t)(w48 + 48 * i) * 4 * DM, 8192, gb + 8 * i);
    }
  }
  __syncwarp();
  uint4 wv[4];
#pragma unroll
  for (int i = 0; i < 4; i++) wv[i] = __ldg(reinterpret_cast<const uint4*>(maps.gate_w + (i * 32 + lane) * 8));
  int it = 0;
#pragma unroll 1
  for (int row = w48 * 4; row < S_LEN; row += 48 * 4, it++) {
    mbar_wait(gb + 8 * (it & 1), (it >> 1) & 1);
    uint4 xv[4][4];
#pragma unroll
    for (int r = 0; r < 4; r++)
#pragma unroll
      for (int i = 0; i < 4; i++) xv[r][i] = lds128(buf + (it & 1) * 8192 + r * 2048 + (i * 32 + lane) * 16);
    float d[2][4];
#pragma unroll
    for (int pr = 0; pr < 2; pr++) {
      d[pr][0] = d[pr][1] = d[pr][2] = d[pr][3] = 0.f;
      auto acc = [&](uint32_t a0, uint32_t a2, uint32_t b0, uint32_t b2, uint32_t w0, uint32_t w2) {
        asm volatile(
            "mma.sync.aligned.m16n8k16.row.col.f32.bf16.bf16.f32 {%0, %1, %2, %3}, {%4, %5, %6, %7}, {%8, %8}, "
            "{%0, %1, %2, %3};"
            : "+f"(d[pr][0]), "+f"(d[pr][1]), "+f"(d[pr][2]), "+f"(d[pr][3])
            : "r"(mul_bf2(a0, w0)), "r"(mul_bf2(b0, w0)), "r"(mul_bf2(a2, w2)), "r"(mul_bf2(b2, w2)), "r"(0x3f803f80u));
      };
#pragma unroll
      for (int i = 0; i < 4; i++) {
        acc(xv[2 * pr][i].x, xv[2 * pr][i].y, xv[2 * pr + 1][i].x, xv[2 * pr + 1][i].y, wv[i].x, wv[i].y);
        acc(xv[2 * pr][i].z, xv[2 * pr][i].w, xv[2 * pr + 1][i].z, xv[2 * pr + 1][i].w, wv[i].z, wv[i].w);
      }
    }
    float sum = (lane & 2) ? ((lane & 1) ? d[1][2] : d[1][0]) : ((lane & 1) ? d[0][2] : d[0][0]);
#pragma unroll
    for (int off = 16; off >= 4; off >>= 1) sum += __shfl_xor_sync(0xffffffffu, sum, off);
    if (lane < 4) g_gate[row + lane] = bf16_round(rcp(1.0f + __expf(-bf16_round(sum))));
    if (lane == 0 && row + 2 * 48 * 4 < S_LEN) {
      mbar_expect_tx(gb + 8 * (it & 1), 8192);
      bulk_load(buf + (it & 1) * 8192, maps.x + (size_t)(row + 2 * 48 * 4) * DM, 8192, gb + 8 * (it & 1));
    }
  }
}

constexpr float Q_SCALE = 0.08838834764831845f * 1.4426950408889634f;
__device__ __forceinline__ uint32_t qkv_consumer(const Maps& maps, uint32_t smem0, bool fused, float (&rest)[64]) {
  PHASE_PROLOGUE
  constexpr int NTILES = G_NTILES;
  float acc[128];
  uint32_t stage = 0, phase = 0;
  const uint32_t stg = sbase + G_STG_OFF + wg * 18432;
  const int st_row = warp * 16 + (lane & 7) + ((lane >> 3) & 1) * 8;
  const int st_cb = lane >> 4;
  uint32_t pend[64];
  const CUtensorMap* pend_map = nullptr;
  int pend_c0 = 0, pend_c1 = 0;
  uint32_t sn = 0;
  auto put_box = [&](uint32_t buf, const uint32_t* v) {
#pragma unroll
    for (int jp = 0; jp < 4; jp++) {
      const int chunk = jp * 2 + st_cb;
      const uint32_t addr = buf + st_row * 128 + ((chunk ^ (st_row & 7)) << 4);
      stmatrix_x4(addr, v[jp * 4], v[jp * 4 + 1], v[jp * 4 + 2], v[jp * 4 + 3]);
    }
  };
  GT(gti++)
#pragma unroll 1
  for (int it = 0; it <= NTILES; it++) {
    int which, m_tile, n_tile;
    qkv_tile(maps, it, which, m_tile, n_tile);
    const int nk = (which == 0 && it < NTILES) ? 16 : 8;
    uint32_t prev_stage = 0;
#pragma unroll 1
    for (int kt = 0; kt < nk; kt++) {
      if (it < NTILES) {
        mbar_wait((bar + B_GFULL) + 8 * stage, phase);
        GT(gti++)
        const uint64_t da0 = make_desc(sbase + stage * G_STAGE_BYTES + wg * 8192, 16, 1024, DESC_SW128);
        const uint64_t db0 = make_desc(sbase + stage * G_STAGE_BYTES + G_A_BYTES, 8192, 1024, DESC_SW128);
        wgmma_fence();
#pragma unroll
        for (int kk = 0; kk < 4; kk++) {
          wgmma_m64n256_ss_tb(acc, desc_add(da0, kk * 2), desc_add(db0, kk * 128), (kt | kk) != 0);
        }
        wgmma_commit();
      }
      const uint32_t when = it == 0 ? 0 : it == 5 ? 0x922 << wg : wg ? 0xAA : 0x55;
      if ((when >> kt) & 1) {
        const int c = __popc(when & ~(~0u << kt));
        st_wait(bar, wg, sn - 2);
        const uint32_t buf = stg + (c & 1) * 8192;
        switch (c) {
          case 0: put_box(buf, pend); break;
          case 1: put_box(buf, pend + 16); break;
          case 2: put_box(buf, pend + 32); break;
          default: put_box(buf, pend + 48); break;
        }
        st_post(bar, wg, wtid, sn, ST_BOX1, pend_map, buf, pend_c0 + c * 64, pend_c1, (c == 3 && it > 1) ? CNT_KV + (it > 3) : -1);
        sn++;
      }
      if (it < NTILES) {
        wgmma_wait<1>();
        mbar_arrive_if((bar + B_GEMPTY) + 8 * prev_stage, wtid == 32 && kt > 0);
        prev_stage = stage;
        if (++stage == G_STAGES) { stage = 0; phase ^= 1; }
      }
    }
    wgmma_wait<0>();
    fence_regs(acc);
    if (it == NTILES) break;
    GT(gti++)
    mbar_arrive_if((bar + B_GEMPTY) + 8 * prev_stage, wtid == 32);
    if (it == NTILES - 1 && fused) break;
    if (which == 0) {
#pragma unroll
      for (int j = 0; j < 128; j++) acc[j] *= Q_SCALE;
    }
#pragma unroll
    for (int j = 0; j < 64; j++) pend[j] = pack_bf16(acc[2 * j], acc[2 * j + 1]);
    pend_map = &maps.c[which];
    pend_c0 = n_tile * 256;
    pend_c1 = m_tile * 128 + wg * 64;
  }
  mbar_wait(bar + B_GEMPTY, 1);
#pragma unroll
  for (int j = 0; j < 32; j++) pend[j] = pack_bf16(acc[2 * j] * Q_SCALE, acc[2 * j + 1] * Q_SCALE);
  put_box(sbase + wg * 8192, pend);
  put_box(sbase + 16384 + wg * 8192, pend + 16);
  fence_proxy_async();
#pragma unroll
  for (int j = 0; j < 64; j++) rest[j] = acc[64 + j];
  GT(gti++)
  return sn;
}

constexpr int A_TILE = 128 * 128 * 2;
constexpr int A_Q_OFF = 0;
constexpr int A_K_OFF = 2 * A_TILE;
constexpr int A_V_OFF = 4 * A_TILE;
constexpr int A_O_OFF = 6 * A_TILE;
constexpr int A_ITEMS = NH * (S_LEN / 128);

constexpr uint32_t A_ORDER = 0x3120, A_STEPS = 34;
__device__ __forceinline__ int item_m(uint32_t it) { return it & 15; }
__device__ __forceinline__ int item_h(uint32_t it) { return it >> 4; }

constexpr int C_H0 = 16, C_U = C_H0 + 4096 + 112, C_SLOT = C_U + 4096;
constexpr int C_H1 = 2 * C_SLOT + 80;
constexpr int C_X_OFF = C_H1 + 4096 + 48;

__device__ __forceinline__ uint32_t item_of(const Maps& maps, uint32_t r) {
  const uint32_t b = maps.id[blockIdx.x & 127][1];
  return (b >> 4) * 64 + ((A_ORDER >> (4 * r)) & 3) * 16 + ((b ^ ((r & 1) * 15)) & 15);
}

constexpr uint32_t C_SIDE = 48;
__device__ __forceinline__ uint32_t conv_first(const Maps& maps) {
  const uint32_t b = maps.id[blockIdx.x & 127][1];
  return (b >> 4) * 128 + (b & 15);
}

__device__ __forceinline__ void conv_consumer(const Maps& maps, uint32_t smem0, uint32_t first, uint32_t step,
                                              uint32_t end) {
  PHASE_PROLOGUE
  const uint32_t full = bar + B_CFULL + wg * 16;
  const uint32_t ca = sbase + (wg ? A_V_OFF + A_TILE : A_Q_OFF);
  const int w4 = __shfl_sync(0xffffffffu, warp, 0);
  auto fetch = [&](uint32_t c, uint32_t slot) {
    if (w4 == 2 && c < end) {
      if (elect_one()) {
        const uint32_t sb = ca + slot * C_SLOT, fb = full + 8 * slot;
        const uint64_t pol = policy_evict_first();
        mbar_expect_tx(fb, 2 * 4096);
        bulk_load_hint(sb + C_H0, maps.ssm_k + (size_t)c * S_LEN, 4096, fb, pol);
        bulk_load_hint(sb + C_U, g_kvT + (size_t)c * S_LEN, 4096, fb, pol);
      }
    }
  };
  auto shift_h = [&](uint32_t so) {
    const uint32_t a = ca + so + C_H0 + wtid * 16;
#pragma unroll
    for (int i = 0; i < 2; i++) {
      uint32_t p;
      const uint4 v = lds128(a + i * 2048);
      asm volatile("ld.shared.u32 %0, [%1];" : "=r"(p) : "r"(a + i * 2048 - 4));
      sts128(ca + C_H1 + wtid * 16 + i * 2048, make_uint4(__byte_perm(p, v.x, 0x5432), __byte_perm(v.x, v.y, 0x5432),
                                                      __byte_perm(v.y, v.z, 0x5432), __byte_perm(v.z, v.w, 0x5432)));
    }
  };
  if (wtid == 96 && wg) { TD(15) }
  fetch(first, 0);
  if (wtid < 17)
    sts128(ca + (wtid >> 3) * C_SLOT + (wtid & 7 ? 4096 + (wtid & 7) * 16 : (wtid & 16) * 4), make_uint4(0, 0, 0, 0));
  fence_proxy_async();
  const uint32_t ha = ca + ((lane & 4) ? C_H1 : C_H0) + 4 * ((lane & 3) - (lane >> 3)) + w4 * 256;
  const uint32_t ua = ca + C_U + w4 * 256 + (lane >> 4) * 1024 + (lane & 15) * 16;
  const uint32_t xa = ca + C_X_OFF + lane * 8, xw = xa + w4 * 3072;
  uint32_t xg[3];
#pragma unroll
  for (int k = 0; k < 3; k++) {
    const int w = (w4 + k + 1) & 3;
    xg[k] = xa + (w * 12 + w4 - w - (w < w4 ? 1 : 0)) * 256;
  }
  const bool pp = step != 16;
  uint32_t h[2][16];
  const uint32_t hs = (lane & 4) ? 0 : C_SLOT;
  auto load_h = [&](uint32_t so, int a) {
#pragma unroll
    for (int i = 0; i < 16; i++)
      asm volatile("ld.shared.u32 %0, [%1];"
                   : "=r"(h[a & 1][i])
                   : "r"(ha + so + 1024 * a + 32 * (i >> 2) + (i & 1) * 128 + (~i & 2) * 8));
  };
  mbar_wait(full, 0);
  named_bar_sync(1 + wg, 128);
  shift_h(0);
  named_bar_sync(1 + wg, 128);
  fetch(first + step, 1);
  load_h(0, 0);
  load_h(0, 1);
  mbar_wait(bar + B_OFREE, 0);
  mbar_wait(bar + B_OFREE + 8, 0);
  uint32_t n = 0, ch = first;
  for (; ch < end; n++, ch += step) {
    CT(0)
    const uint32_t so = (n & 1) * C_SLOT, ho = (n & 1) * hs;
    uint32_t db = (uint32_t)make_desc(ca + so + C_U - 16, 16, 0, 0);
    asm volatile("" : "+r"(db));
    uint32_t dsk = __ldg(reinterpret_cast<const unsigned short*>(maps.ssm_D) + (ch | (lane & rt_zero)));
    float d[4][32], own[16];
    auto mma = [&](int a) {
      wgmma_fence();
#pragma unroll
      for (int c = a; c < 4; c++)
#pragma unroll
        for (int b = 0; b < 4; b++)
          wgmma_m64n64_rs(d[c], &h[a & 1][4 * b], (8ull << 32) | (db + 64 * (c - a) - 2 * b), (a | b) != 0);
      wgmma_commit();
    };
    auto put = [&](int c) {
      fence_regs(d[c]);
#pragma unroll
      for (int e = 0; e < 2; e++) {
        if (c == 0) asm volatile("mov.b32 %0, %1;" : "=f"(own[e]) : "f"(d[c][e]));
        else own[4 * c + e] += d[c][e];
        own[4 * c + 2 + e] = d[c][4 + e] + d[c][2 + e];
        if (c < 3) asm volatile("mov.b32 %0, %1;" : "=f"(own[4 * c + 4 + e]) : "f"(d[c][30 + e]));
      }
#pragma unroll
      for (int j = 1; j < 4; j++)
        asm volatile("{\n.reg .pred p;\nsetp.lt.s32 p, %3, 4;\n@p st.shared.v2.u32 [%0], {%1, %2};\n}\n" ::"r"(
                         xw + (3 * c + j - 1) * 256),
                     "r"(pack_bf16(d[c][8 * j] + d[c][8 * j - 2], d[c][8 * j + 1] + d[c][8 * j - 1])),
                     "r"(pack_bf16(d[c][8 * j + 4] + d[c][8 * j + 2], d[c][8 * j + 5] + d[c][8 * j + 3])),
                     "r"(c < 3 ? 0 : w4 + j)
                     : "memory");
    };
    named_bar_sync(pp ? 4 + wg : 1 + wg, pp ? 256 : 128);
    CT(1)
    mma(0);
    mma(1);
    wgmma_wait<1>();
    load_h(ho, 2);
    put(0);
    mma(2);
    CT(2)
    wgmma_wait<1>();
    load_h(ho, 3);
    put(1);
    mma(3);
    asm volatile("{\n.reg .pred p;\nsetp.ne.u32 p, %1, 0;\n@p bar.arrive %0, 256;\n}\n" ::"r"(5 - wg), "r"((uint32_t)pp) : "memory");
    CT(3)
    uint32_t sk[8];
    asm volatile("ldmatrix.sync.aligned.m8n8.x4.trans.shared.b16 {%0, %1, %2, %3}, [%4];"
                 : "=r"(sk[0]), "=r"(sk[1]), "=r"(sk[2]), "=r"(sk[3])
                 : "r"(ua + so));
    asm volatile("ldmatrix.sync.aligned.m8n8.x4.trans.shared.b16 {%0, %1, %2, %3}, [%4];"
                 : "=r"(sk[4]), "=r"(sk[5]), "=r"(sk[6]), "=r"(sk[7])
                 : "r"(ua + so + 2048));
    mbar_wait(full + 8 * (~n & 1), (((n + 1) >> 1) & 1) ^ (ch + step < end ? 0 : 1));
    named_bar_sync(1 + wg, 128);
    shift_h(C_SLOT - so);
    wgmma_wait<1>();
    put(2);
    uint32_t dep = 0;
#pragma unroll
    for (int i = 0; i < 8; i++) dep |= sk[i] = mul_bf2(sk[i], dsk | (dsk << 16));
    CT(4)
    wgmma_wait<0>();
    put(3);
    named_bar_sync((1 + wg) | (dep & rt_zero), 128);
    CT(5)
    fetch(ch + 2 * step, n & 1);
    if (wtid == 96 && n) note(bar, CNT_Y2 + (((ch - step) & 127) >= 112));
    uint2 q[12];
#pragma unroll
    for (int i = 0; i < 12; i++) {
      if (i >= 3) {
        asm volatile("ld.shared.v2.u32 {%0, %1}, [%2];" : "=r"(q[i].x), "=r"(q[i].y) : "r"(xg[i % 3] + (i / 3) * 768));
      } else {
        q[i] = make_uint2(0, 0);
        asm volatile("{\n.reg .pred p;\nsetp.gt.s32 p, %3, 2;\n@p ld.shared.v2.u32 {%0, %1}, [%2];\n}\n"
                     : "+r"(q[i].x), "+r"(q[i].y)
                     : "r"(xg[i]), "r"(w4 + i));
      }
    }
    load_h(hs - ho, 0);
    load_h(hs - ho, 1);
    CT(6)
    uint32_t* dst = reinterpret_cast<uint32_t*>(g_y2T + (size_t)ch * S_LEN) + 64 * w4 + (lane ^ 28);
#pragma unroll
    for (int f = 0; f < 4; f++) {
#pragma unroll
      for (int k = 0; k < 3; k++) {
        own[4 * f] += bf_lo(q[3 * f + k].x);
        own[4 * f + 1] += bf_hi(q[3 * f + k].x);
        own[4 * f + 2] += bf_lo(q[3 * f + k].y);
        own[4 * f + 3] += bf_hi(q[3 * f + k].y);
      }
#pragma unroll
      for (int i = 0; i < 2; i++) {
        dst[256 * f + 32 * i] = add_bf2(pack_bf16(own[4 * f + 2 * i], own[4 * f + 2 * i + 1]), sk[2 * f + i]);
      }
    }
    CT(7)
  }
  named_bar_sync(1 + wg, 128);
  if (wtid == 96 && wg) { TD(8) }
  if (wtid == 96) cnt_signal_release(CNT_Y2 + (((ch - step) & 127) >= 112), 1);
  if (wtid == 64) note(bar, CNT_DONE);
  if (wtid == 96 && wg) { TD(9) }
}

__device__ __forceinline__ void attn_producer(const Maps& maps, uint32_t sbase, bool after_qkv, bool to_out,
                                              bool dry) {
  const uint32_t bar = sbase + BAR_OFF;
  const uint32_t q_full = bar + B_QFULL, q_empty = bar + B_QEMPTY;
  const uint32_t k_full = bar + B_KFULL, k_empty = bar + B_KEMPTY, v_full = bar + B_VFULL, v_empty = bar + B_VEMPTY;
  int ndrained = after_qkv ? 0 : G_STAGES;
  auto wait = [&](uint32_t b, uint32_t par) {
    if (!dry) mbar_wait_sleep(b, par);
  };
  auto drained = [&](int upto) {
#pragma unroll 1
    for (; ndrained <= upto; ndrained++) wait(bar + B_GEMPTY + 8 * ndrained, 1);
  };
  uint32_t st = 0, ph = 1, vs = 0, vp = 1;
  int pend_j = -1, pend_h = 0;
  int round = -1, m = -1, h = 0;
  bool last = false;
#pragma unroll 1
  for (;; round++) {
    uint32_t nitem = 0;
    const int tpost = m >= 3 ? m - 1 : m;
#pragma unroll 1
    for (int t = m < 0 ? -1 : 0; t <= m; t++) {
      const int j = (t < m && (round & 1)) ? m - 1 - t : t;
      if (t >= 0) {
        drained(1 + st);
        wait(k_empty + 8 * st, ph);
        if (!dry) {
          mbar_expect_tx(k_full + 8 * st, A_TILE);
          tma_load_3d(sbase + A_K_OFF + st * A_TILE, &maps.k, k_full + 8 * st, 0, j * 128, h * 2);
        }
        if (++st == 2) { st = 0; ph ^= 1; }
      }
      if (pend_j >= 0) {
        drained(3);
        wait(v_empty + 8 * vs, vp);
        if (!dry) {
          mbar_expect_tx(v_full + 8 * vs, A_TILE);
          tma_load_3d(sbase + A_V_OFF + vs * A_TILE, &maps.v, v_full + 8 * vs, 0, pend_j * 128, pend_h * 2);
        }
        if (++vs == 2) { vs = 0; vp ^= 1; }
      }
      pend_j = j;
      pend_h = h;
      if (t == tpost && !last) {
        nitem = dry ? 1 : item_of(maps, round + 1);
        if (round == (dry ? 0 : 3) || blockIdx.x >= 128) {
          nitem = A_ITEMS;
          cnt_wait(CNT_PREP, dry ? 0 : 260);
          if (to_out) {
            cnt_wait(CNT_CTX, dry ? 0 : A_ITEMS);
            asm volatile("cp.async.bulk.prefetch.L2.global [%0], 4096;" ::"l"(maps.ssm_k + (size_t)conv_first(maps) * S_LEN));
            if (!dry)
              asm volatile("cp.async.bulk.prefetch.L2.global [%0], 4096;" ::"l"(g_kvT + (size_t)conv_first(maps) * S_LEN));
          }
        }
        const uint32_t qs = (round + 1) & 1;
        wait(q_empty + 8 * qs, (((round + 1) >> 1) & 1) ^ 1);
        if (round == 1 && after_qkv) wait(bar + B_QDONE, 0);
        if (round <= 0 && after_qkv) {
          if (!dry) { TD(2) }
          cnt_wait(CNT_KV + round + 1, dry ? 0 : 512);
          if (!dry) { TD(3) }
        }
        if (nitem >= A_ITEMS || (round < 0 && after_qkv && !dry)) {
          if (!dry) mbar_arrive(q_full + 8 * qs);
        } else {
          drained(qs);
          if (!dry) {
            mbar_expect_tx(q_full + 8 * qs, A_TILE);
            tma_load_3d_hint(sbase + A_Q_OFF + qs * A_TILE, &maps.q, q_full + 8 * qs, 0, item_m(nitem) * 128,
                             item_h(nitem) * 2, policy_evict_first());
          }
        }
      }
    }
    if (last) break;
    last = nitem >= A_ITEMS;
    m = last ? -1 : item_m(nitem);
    h = item_h(nitem);
  }
}

__device__ __forceinline__ uint32_t attn_consumer(const Maps& maps, uint32_t smem0, uint32_t sn,
                                                  float (&rest)[64], bool after_qkv) {
  PHASE_PROLOGUE
  const uint32_t q_full = bar + B_QFULL, q_empty = bar + B_QEMPTY;
  const uint32_t k_full = bar + B_KFULL, k_empty = bar + B_KEMPTY, v_full = bar + B_VFULL;
  float o[64], s[64];
  uint32_t p[32];
  float e[32];
  uint32_t dep = 0;
  constexpr int MIDJ = 5;
  float l0 = 0.f, l1 = 0.f, b0 = 0.f, b1 = 0.f;
  const int sched_own = 4 + wg, sched_other = 5 - wg;
  if (wg == 1) named_bar_arrive(4, 256);

  const uint32_t qd0 = (uint32_t)make_desc(sbase + A_Q_OFF + wg * 8192, 16, 0, 0);
  const uint32_t kd0 = (uint32_t)make_desc(sbase + A_K_OFF, 16, 0, 0);
  const uint32_t vd0 = (uint32_t)make_desc(sbase + A_V_OFF, 16384, 0, 0);
  constexpr uint64_t DHI = DESC_SW128 | ((uint64_t)(1024 >> 4) << 32);
  constexpr uint32_t DST = A_TILE >> 4;
  auto issue_qk = [&](uint32_t qd, uint32_t kd) {
#pragma unroll
    for (int kk = 0; kk < 8; kk++) {
      const uint32_t off = ((kk >> 2) * 16384 + (kk & 3) * 32) >> 4;
      wgmma_m64n128_ss(s, DHI | (qd + off), DHI | (kd + off), kk != 0);
    }
    wgmma_commit();
  };
  auto issue_pv = [&](uint32_t vd, bool accumulate, int nk) {
#pragma unroll
    for (int kk = 0; kk < 8; kk++) {
      if (kk < nk)
        wgmma_m64n128_rs_tb(o, p[4 * kk], p[4 * kk + 1], p[4 * kk + 2], p[4 * kk + 3], DHI | (vd + kk * 128),
                            accumulate || (kk != 0));
    }
    wgmma_commit();
  };
  auto exp_lo = [&](float& a0, float& a1) {
#pragma unroll
    for (int j = 0; j < 8; j++) {
      e[4 * j] = ex2(s[4 * j]);
      e[4 * j + 1] = ex2(s[4 * j + 1]);
      e[4 * j + 2] = ex2(s[4 * j + 2]);
      e[4 * j + 3] = ex2(s[4 * j + 3]);
      a0 += e[4 * j];
      a0 += e[4 * j + 1];
      a1 += e[4 * j + 2];
      a1 += e[4 * j + 3];
      if (j == MIDJ) dep = (__float_as_uint(a0) | __float_as_uint(a1)) & rt_zero;
    }
  };
  auto pack_lo = [&]() {
#pragma unroll
    for (int j = 0; j < 16; j++) p[j] = pack_bf16(e[2 * j], e[2 * j + 1]);
  };
  auto finish_p = [&](float& a0, float& a1) {
    pack_lo();
#pragma unroll
    for (int j = 8; j < 16; j++) {
      const float e0 = ex2(s[4 * j]), e1 = ex2(s[4 * j + 1]), e2 = ex2(s[4 * j + 2]), e3 = ex2(s[4 * j + 3]);
      a0 += e0;
      a0 += e1;
      a1 += e2;
      a1 += e3;
      p[2 * j] = pack_bf16(e0, e1);
      p[2 * j + 1] = pack_bf16(e2, e3);
      if (j == 8 + MIDJ) dep = __float_as_uint(a0) & rt_zero;
    }
  };
  auto quad_sum = [&](float t) {
    t += __shfl_xor_sync(0xffffffffu, t, 1);
    return t + __shfl_xor_sync(0xffffffffu, t, 2);
  };
  auto write_o = [&](float i0, float i1) {
    st_wait(bar, wg, sn - 1);
    const int st_row = warp * 16 + (lane & 7) + ((lane >> 3) & 1) * 8;
    const uint32_t so = sbase + A_O_OFF + wg * 16384 + st_row * 128;
#pragma unroll
    for (int j = 0; j < 16; j += 2)
      stmatrix_x4(so + (j >> 3) * 8192 + ((((j & 7) + (lane >> 4)) ^ (lane & 7)) << 4),
                  pack_bf16(o[4 * j] * i0, o[4 * j + 1] * i0), pack_bf16(o[4 * j + 2] * i1, o[4 * j + 3] * i1),
                  pack_bf16(o[4 * j + 4] * i0, o[4 * j + 5] * i0), pack_bf16(o[4 * j + 6] * i1, o[4 * j + 7] * i1));
  };
  auto store_o = [&](uint32_t r, int kind) {
    const uint32_t it = item_of(maps, r);
    st_post(bar, wg, wtid, sn, kind, (INPLACE & 1) || kind != ST_BOX2Q ? &maps.o : &maps.c[0], sbase + A_O_OFF + wg * 16384, item_h(it) * 128,
            item_m(it) * 128 + wg * 64, CNT_CTX + (r >> 1));
    sn++;
  };
  auto mask_half = [&](float* sh) {
    const int u = warp * 16 + (lane >> 2) - (lane & 3) * 2;
#pragma unroll
    for (int j = 0; j < 8; j++) {
      if (8 * j > u) sh[4 * j] = -INFINITY;
      if (8 * j + 1 > u) sh[4 * j + 1] = -INFINITY;
      if (8 * j - 8 > u) sh[4 * j + 2] = -INFINITY;
      if (8 * j - 7 > u) sh[4 * j + 3] = -INFINITY;
    }
  };
  ST(0)
  mbar_wait(q_full, 0);
  if (blockIdx.x >= 128) {
    mbar_arrive_if(bar + B_OFREE + 8 * wg, wtid == 0);
    return sn;
  }
  mbar_wait(k_full, 0);
  named_bar_sync(sched_own, 256);
  wgmma_fence();
  issue_qk(qd0, kd0);
  named_bar_arrive(sched_other, 256);
  fence_regs(rest);
#pragma unroll
  for (int i = 0; i < 64; i++) o[i] = rest[i] * Q_SCALE;
  fence_regs(o);
  wgmma_wait<0>();
  fence_regs(s);
  mbar_arrive_if(k_empty, wtid == 32);
  uint32_t g = 0;
  uint32_t rnd = 0;
  int rem = item_m(item_of(maps, 0));
  uint32_t first = 1;
  uint32_t fl = 0;
#define redo (fl & 1)
#define shifted (fl & 2)
  float d0 = 0.f, d1 = 0.f;
  float pi0 = 1.f, pi1 = 1.f;
  ST(1)
  for (;;) {
    if (shifted) {
#pragma unroll
      for (int j = 0; j < 16; j++) {
        s[4 * j] -= d0;
        s[4 * j + 1] -= d0;
        s[4 * j + 2] -= d1;
        s[4 * j + 3] -= d1;
      }
    }
    if (rem == 0 && !redo) {
      mbar_arrive_if(q_empty + 8 * (rnd & 1), wtid == 96);
      rnd++;
      if (wg == 0) mask_half(s);
      else mask_half(s + 32);
    }
    for (;;) {
      const bool kill = rem == 0 && wg == 0;
      const uint32_t kd = kd0 + ((g + 1) & 1) * DST, vd = vd0 + (g & 1) * DST;
      float a0 = 0.f, a1 = 0.f;
      exp_lo(a0, a1);
      fence_regs(e);
      const uint32_t kb = k_full + 8 * ((g + 1) & 1);
      const uint32_t kpar = ((((g + 1) >> 1) & 1) ^ (g == A_STEPS - 1 ? 1u : 0u)) | dep;
      if (!mbar_try(kb, kpar)) mbar_wait(kb, kpar | ((__float_as_uint(a0) | __float_as_uint(a1)) & rt_zero));
      wgmma_wait<0>();
      fence_regs(o);
      if (kill) {
        mbar_arrive_if(kb + (B_VEMPTY - B_KFULL), wtid == 64 && !redo && g > 0);
        fence_regs(e);
        pack_lo();
#pragma unroll
        for (int j = 16; j < 32; j++) asm volatile("mov.u32 %0, 0;" : "=r"(p[j]));
        goto check;
      }
#pragma unroll
      for (int i = 32; i < 64; i++) asm volatile("" : "+f"(s[i])::"memory");
      mbar_arrive_if(kb + (B_VEMPTY - B_KFULL), wtid == 64 && !redo && g > 0);
      finish_p(a0, a1);
      if (__any_sync(0xffffffffu, !(mbar_try(v_full + 8 * (g & 1), ((g >> 1) & 1) | dep) &
                                    mbar_try(q_full + 8 * (rnd & 1), ((rnd >> 1) & 1) | dep)) ||
                                      !(a0 + a1 < 1.0995116e12f) || !(fminf(a0, a1) > (first ? 9.094947e-13f : -1.f)))) {
      check:
        bool bad = !(a0 + a1 < 1.0995116e12f);
        if (first) bad |= !(fminf(quad_sum(a0), quad_sum(a1)) > 9.094947e-13f);
        if (!redo && __any_sync(0xffffffffu, bad)) {
          d0 = d1 = first ? -INFINITY : 0.f;
#pragma unroll
          for (int j = 0; j < 16; j++) {
            if (j < 8 || !kill) {
              d0 = fmaxf(d0, fmaxf(s[4 * j], s[4 * j + 1]));
              d1 = fmaxf(d1, fmaxf(s[4 * j + 2], s[4 * j + 3]));
            }
          }
#pragma unroll
          for (int x = 1; x <= 2; x++) {
            d0 = fmaxf(d0, __shfl_xor_sync(0xffffffffu, d0, x));
            d1 = fmaxf(d1, __shfl_xor_sync(0xffffffffu, d1, x));
          }
          b0 += d0;
          b1 += d1;
          if (!first) {
            const float al0 = ex2(-d0), al1 = ex2(-d1);
            l0 *= al0;
            l1 *= al1;
#pragma unroll
            for (int j = 0; j < 16; j++) {
              o[4 * j] *= al0;
              o[4 * j + 1] *= al0;
              o[4 * j + 2] *= al1;
              o[4 * j + 3] *= al1;
            }
          }
          fl = 3;
          break;
        }
        mbar_wait(v_full + 8 * (g & 1), (g >> 1) & 1);
        mbar_wait(q_full + 8 * (rnd & 1), (rnd >> 1) & 1);
      }
      named_bar_sync(sched_own, 256);
      if (g == A_STEPS - 1) {
        if (first) write_o(pi0, pi1);
        fence_regs(o);
        wgmma_fence();
        issue_pv(vd, !first, 8);
        named_bar_arrive(sched_other, 256);
        if (first) store_o(rnd - 2, ST_BOX2);
        pi0 = rcp(quad_sum(l0 + a0));
        pi1 = rcp(quad_sum(l1 + a1));
        goto done;
      }
      wgmma_fence();
      issue_qk(qd0 + (rnd & 1) * DST, kd);
      if (first) write_o(pi0, pi1);
      fence_regs(o);
      if (kill) {
        wgmma_fence();
        issue_pv(vd, !first, 4);
      } else {
        wgmma_fence();
        issue_pv(vd, !first, 8);
      }
      named_bar_arrive(sched_other, 256);
      fl &= 2;
      l0 += a0;
      l1 += a1;
      if (rem == 0 || first) {
        if (first && (g > 0 || after_qkv)) store_o(g ? rnd - (rem == 0 ? 2 : 1) : 2, g ? ST_BOX2 : ST_BOX2Q);
        first = rem == 0;
        if (first) {
          pi0 = rcp(quad_sum(l0));
          pi1 = rcp(quad_sum(l1));
          l0 = l1 = b0 = b1 = 0.f;
          fl = 0;
          rem = item_m(item_of(maps, rnd)) + 1;
        }
      }
      rem--;
      g++;
      wgmma_wait<1>();
      fence_regs(s);
      mbar_arrive_if(kb + (B_KEMPTY - B_KFULL), wtid == 32);
      ST(g + 1)
      if (rem == 0 || shifted) {
        d0 = b0;
        d1 = b1;
        break;
      }
    }
  }
done:
#undef redo
#undef shifted
  wgmma_wait<0>();
  fence_regs(o);
  write_o(pi0, pi1);
  store_o(3, ST_BOX2L);
  ST(35)
  return sn;
}

constexpr int O_STAGES = 5;
constexpr int O_STAGE_BYTES = 32768;
constexpr int O_Y_OFF = 5 * 32768;
constexpr int O_X_OFF = 6 * 32768 + 2048;
constexpr int O_NK = HDIM / 64;

__device__ __forceinline__ uint32_t out_stage(uint32_t st) { return ((0x43120u >> (4 * st)) & 7) * O_STAGE_BYTES; }

__device__ __forceinline__ void out_producer(const Maps& maps, uint32_t sbase, bool after_attn, bool dry) {
  const uint32_t bar = sbase + BAR_OFF;
  const uint32_t rank = blockIdx.x & 1;
  const int m_tile = maps.id[blockIdx.x][2] & 15, n_tile = maps.id[blockIdx.x][2] >> 4;
  uint32_t stage = 0, phase = 0;
  const int kx = dry ? 0 : 17 + (blockIdx.x >> 1) % 12;
#pragma unroll 1
  for (int ki = 0; ki < (dry ? 1 : O_NK); ki++) {
    const int kt = (ki & 14) * 4 + ((A_ORDER >> ((ki >> 4) * 4)) & 3) * 2 + (ki & 1);
    const uint32_t fb = bar + B_OFULL + 8 * stage, eb = bar + B_OEMPTY + 8 * stage;
    const uint32_t sa = sbase + out_stage(stage);
    if (ki < O_STAGES) {
      constexpr uint32_t LASTB = B_KEMPTY | ((B_QEMPTY + 8) << 8) | ((B_KEMPTY + 8) << 16) | (B_VEMPTY << 24);
      if (ki > 0 && after_attn) mbar_wait_sleep(bar + ((LASTB >> (8 * ki - 8)) & 255), ki == 2);
      mbar_arrive_cluster_if(eb, 0, !dry);
      mbar_arrive_cluster_if(eb, 1, !dry);
    }
    if (ki == (dry ? 0 : 16)) cnt_wait(CNT_CTX + 1, dry ? 0 : A_ITEMS);
    if (ki == kx) {
      if (after_attn && !dry) {
        mbar_wait_sleep(bar + B_OFREE, 0);
        mbar_wait_sleep(bar + B_OFREE + 8, 0);
      }
      if (!dry) {
        mbar_expect_tx(bar + B_OY, 32768);
        tma_load_4d(sbase + O_X_OFF, &maps.ox, bar + B_OY, n_tile * 128, m_tile);
        tma_load_4d(sbase + O_X_OFF + 16384, &maps.ox, bar + B_OY, n_tile * 128 + 64, m_tile);
      }
    }
    if (!dry) {
      mbar_wait_sleep(eb, phase);
      mbar_expect_tx(fb, O_STAGE_BYTES);
      tma_load_2d_mc(sa + 16384 + rank * 8192, &maps.ob, fb, n_tile * 128 + rank * 64, kt * 64, (uint16_t)3);
      tma_load_4d(sa, &maps.oa, fb, kt * 64, m_tile);
    }
    if (++stage == O_STAGES) { stage = 0; phase ^= 1; }
  }
  if (!dry) mbar_wait_sleep(bar + B_OY2, 0);
}

__device__ __forceinline__ void out_side(const Maps& maps, uint32_t smem0, const float (&gv)[4]) {
  PHASE_PROLOGUE
  const int m_tile = maps.id[blockIdx.x][2] & 15, n_tile = maps.id[blockIdx.x][2] >> 4;
  const int w4 = __shfl_sync(0xffffffffu, warp, 0);
  if (w4 == 0) {
    if (elect_one()) {
      mbar_expect_tx(bar + B_OY, 32768 - 4096);
      TD(10)
      GS(0)
      cnt_wait(CNT_Y2, DM - 128);
      GS(1)
      TD(7)
      for (const uint32_t t = clock(); (uint32_t)clock() - t < (blockIdx.x & 14) * 200;) __nanosleep(32);
      TD(11)
      GS(2)
      fence_proxy_async();
      tma_load_2d(sbase + O_Y_OFF, &maps.y, bar + B_OY, m_tile * 128, n_tile * 128);
      tma_load_2d(sbase + O_Y_OFF + 16384, &maps.y, bar + B_OY, m_tile * 128 + 64, n_tile * 128);
    }
  }
  mbar_wait_sleep(bar + B_OY, 0);
  const int st_row = warp * 16 + (lane & 7) + ((lane >> 3) & 1) * 8;
  const int mrow = (lane & 7) + ((lane >> 4) & 1) * 8;
  const int mchunk = warp * 2 + ((lane >> 3) & 1);
  const uint32_t xrow = sbase + O_X_OFF + st_row * 128;
  const uint32_t yrow = sbase + O_Y_OFF + mrow * 128 + ((mchunk ^ (lane & 7)) << 4);
  uint32_t y[7][4], x[7][4], om[4];
#pragma unroll
  for (int i = 0; i < 4; i++) om[i] = pack_bf16(1.0f - gv[i], 1.0f - gv[i]);
  auto xa = [&](int h, int i) { return xrow + h * 8192 + (i >> 2) * 16384 + ((((i & 3) * 2 + (lane >> 4)) ^ (lane & 7)) << 4); };
  auto load = [&](int r, int h, int i) {
    ldsm4t(y[r], yrow + h * 16384 + i * 2048);
    asm volatile("ldmatrix.sync.aligned.m8n8.x4.shared.b16 {%0, %1, %2, %3}, [%4];"
                 : "=r"(x[r][0]), "=r"(x[r][1]), "=r"(x[r][2]), "=r"(x[r][3])
                 : "r"(xa(h, i)));
  };
  auto store = [&](int r, int h, int i, uint32_t om0, uint32_t om1) {
    stmatrix_x4(xa(h, i), mul_bf2(om0, mul_bf2(x[r][0], y[r][0])), mul_bf2(om1, mul_bf2(x[r][1], y[r][1])),
                mul_bf2(om0, mul_bf2(x[r][2], y[r][2])), mul_bf2(om1, mul_bf2(x[r][3], y[r][3])));
  };
  if (wtid == 0) { TD(12) GS(3) }
#pragma unroll 1
  for (int h = 0; h < 2; h++) {
#pragma unroll
    for (int i = 0; i < 7; i++) load(i, h, i);
#pragma unroll
    for (int i = 0; i < 7; i++) store(i, h, i, h ? om[2] : om[0], h ? om[3] : om[1]);
  }
  if (wtid == 0) { TD(4) GS(4) }
  if (w4 == 0) {
    if (elect_one()) {
      mbar_expect_tx(bar + B_OY2, 4096);
      cnt_wait(CNT_Y2 + 1, 128);
      GS(5)
      for (int i = 0; i < 2; i++)
        tma_load_2d(sbase + O_Y_OFF + i * 16384 + 112 * 128, &maps.y2, bar + B_OY2, m_tile * 128 + i * 64,
                    n_tile * 128 + 112);
    }
  }
  mbar_wait_sleep(bar + B_OY2, 0);
#pragma unroll
  for (int h = 0; h < 2; h++) load(h, h, 7);
#pragma unroll
  for (int h = 0; h < 2; h++) store(h, h, 7, om[2 * h], om[2 * h + 1]);
  __syncwarp();
  mbar_arrive_if(bar + B_OY + 8, lane == 0);
  if (wtid == 0) { TD(13) GS(6) }
#pragma unroll
  for (int i = 0; i < 4; i++) {
    const int h = i >> 1, c = i & 1;
    named_bar_sync(6 + i, 256);
    if (elect_one()) {
      fence_proxy_async();
      tma_store_4d(&maps.oc, sbase + O_X_OFF + c * 16384 + h * 8192 + w4 * 2048, n_tile * 128 + c * 64, 2 * w4,
                   2 * m_tile + h);
      tma_store_commit();
    }
  }
}

__device__ __forceinline__ void out_gemm(const Maps& maps, uint32_t smem0) {
  PHASE_PROLOGUE
  const int m_tile = maps.id[blockIdx.x][2] & 15;
  float acc[2][64];
  undef_regs(acc[0]);
  undef_regs(acc[1]);
  uint32_t stage = 0, phase = 0, prev_stage = 0;
  GT(gti++)
  const float* gp = g_gate + m_tile * 128 + warp * 2 + (lane >> 2) * 8;
  const float gv[4] = {__ldcg(gp), __ldcg(gp + 1), __ldcg(gp + 64), __ldcg(gp + 65)};
  if (wg == 1) {
    out_side(maps, smem0, gv);
    return;
  }
  constexpr uint64_t DHI = DESC_SW128 | ((uint64_t)(1024 >> 4) << 32);
#pragma unroll 1
  for (int kt = 0; kt < O_NK - 1; kt++) {
    uint32_t da = (uint32_t)make_desc(sbase + out_stage(stage), 16, 0, 0);
    uint32_t db = (uint32_t)make_desc(sbase + out_stage(stage) + 16384, 8192, 0, 0);
    asm volatile("" : "+r"(da), "+r"(db));
    mbar_wait(bar + B_OFULL + 8 * stage, phase);
    GT(gti++)
    constexpr int OWAIT = 2;
#pragma unroll
    for (int kk = 0; kk < 4; kk++) {
      wgmma_wait<OWAIT>();
      if (kk == OWAIT)
        mbar_arrive_cluster_if(bar + B_OEMPTY + 8 * prev_stage, wtid >> 6,
                               (wtid & 63) == 32 && kt > 0 && kt - 1 + O_STAGES < O_NK);
      wgmma_fence();
      wgmma_m64n128_ss_tb(acc[0], DHI | (da + kk * 2), DHI | (db + kk * 128), (kt | kk) != 0);
      wgmma_m64n128_ss_tb(acc[1], DHI | (da + 512 + kk * 2), DHI | (db + kk * 128), (kt | kk) != 0);
      wgmma_commit();
    }
    prev_stage = stage;
    if (++stage == O_STAGES) { stage = 0; phase ^= 1; }
  }
  {
    const uint32_t da = (uint32_t)make_desc(sbase + out_stage((O_NK - 1) % O_STAGES), 16, 0, 0);
    const uint32_t db = (uint32_t)make_desc(sbase + out_stage((O_NK - 1) % O_STAGES) + 16384, 8192, 0, 0);
    mbar_wait(bar + B_OFULL + 8 * ((O_NK - 1) % O_STAGES), ((O_NK - 1) / O_STAGES) & 1);
    GT(gti++)
#pragma unroll
    for (int h = 0; h < 2; h++) {
      wgmma_fence();
#pragma unroll
      for (int kk = 0; kk < 4; kk++)
        wgmma_m64n128_ss_tb(acc[h], DHI | (da + h * 512 + kk * 2), DHI | (db + kk * 128), 1);
      wgmma_commit();
    }
  }
  if (tid == 0) { TD(14) }
  const int st_row = warp * 16 + (lane & 7) + ((lane >> 3) & 1) * 8;
  const uint32_t rowa = sbase + O_X_OFF + st_row * 128;
  auto oa = [&](int i) { return rowa + (i >> 3) * 8192 + (i & 4) * 4096 + ((((i & 3) * 2 + (lane >> 4)) ^ (st_row & 7)) << 4); };
  uint32_t b[16][4];
  mbar_wait(bar + B_OY + 8, 0);
#pragma unroll
  for (int i = 0; i < 16; i++)
    asm volatile("ldmatrix.sync.aligned.m8n8.x4.shared.b16 {%0, %1, %2, %3}, [%4];"
                 : "=r"(b[i][0]), "=r"(b[i][1]), "=r"(b[i][2]), "=r"(b[i][3])
                 : "r"(oa(i)));
  uint32_t gg[4];
#pragma unroll
  for (int i = 0; i < 4; i++) gg[i] = pack_bf16(gv[i], gv[i]);
#pragma unroll
  for (int i = 0; i < 16; i++) {
    const int h = i >> 3;
    if (i == 0) wgmma_wait<1>();
    if (i == 8) wgmma_wait<0>();
    if (i % 8 == 0) fence_regs(acc[h]);
    const float* a = acc[h] + 8 * (i & 7);
    const uint32_t gg0 = gg[2 * h], gg1 = gg[2 * h + 1];
    stmatrix_x4(oa(i), fma_bf2(gg0, pack_bf16(a[0], a[1]), b[i][0]), fma_bf2(gg1, pack_bf16(a[2], a[3]), b[i][1]),
                fma_bf2(gg0, pack_bf16(a[4], a[5]), b[i][2]), fma_bf2(gg1, pack_bf16(a[6], a[7]), b[i][3]));
    if (i % 4 == 3) named_bar_arrive(6 + i / 4, 256);
  }
  GT(gti++)
}

__device__ __noinline__ void leave_kernel(int mask) {
  if (!(mask & 4)) return;
  if (atomicAdd(g_cnt + CNT_DONE * 32, 1u) == 2 * gridDim.x - 1) {
    for (int i = 0; i < CNT_N; i++) g_cnt[i * 32] = 0;
  }
}

__device__ __noinline__ void side_jobs(const Maps& maps, uint32_t sbase) {
  const int w12 = __shfl_sync(0xffffffffu, threadIdx.x >> 5, 0);
  gate_rows(maps, sbase, (blockIdx.x - 128) * 12 + w12, w12, threadIdx.x & 31);
  fence_proxy_async();
  __syncthreads();
  if (threadIdx.x == 320) cnt_signal_release(CNT_PREP, 1);
}

__global__ void __launch_bounds__(384, 1) fused_kernel(int mask, const __grid_constant__ Maps maps) {
  extern __shared__ __align__(1024) uint8_t smem_raw[];
  {
    const uint32_t sbase = __shfl_sync(0xffffffffu, smem_u32(smem_raw), 0);
    const uint32_t bar = sbase + BAR_OFF;
    const int tid = threadIdx.x;
    const bool do_qkv = (mask & 1) && blockIdx.x < 128;
    TL(0, 0) LT(0, 0)
    if (__shfl_sync(0xffffffffu, tid >> 5, 0) == 1 && do_qkv) {
      if (elect_one()) {
        for (int i = 0; i < G_STAGES; i++) mbar_init(bar + B_GFULL + 8 * i, 1);
        fence_barrier_init();
        qkv_producer(maps, sbase, true);
      }
    }
    if (tid == 0) {
      for (int i = 0; i < G_STAGES; i++) {
        mbar_init(bar + B_GEMPTY + 8 * i, 2);
        mbar_init(bar + B_SFULL + 8 * i, 4);
        mbar_init(bar + B_SFREE + 8 * i, 1);
      }
      for (int i = 0; i < 2; i++) {
        mbar_init(bar + B_OFREE + 8 * i, 1);
        mbar_init(bar + B_QFULL + 8 * i, 1);
        mbar_init(bar + B_QEMPTY + 8 * i, 2);
        mbar_init(bar + B_KFULL + 8 * i, 1);
        mbar_init(bar + B_KEMPTY + 8 * i, 2);
        mbar_init(bar + B_VFULL + 8 * i, 1);
        mbar_init(bar + B_VEMPTY + 8 * i, 2);
      }
      for (int i = 0; i < O_STAGES; i++) {
        mbar_init(bar + B_OFULL + 8 * i, 1);
        mbar_init(bar + B_OEMPTY + 8 * i, 2);
      }
      mbar_init(bar + B_OY, 2);
      mbar_init(bar + B_OY2, 1);
      mbar_init(bar + B_OY + 8, 4);
      mbar_init(bar + B_QDONE, 2);
      for (int i = 0; i < 8; i++) mbar_init(bar + B_CFULL + 8 * i, 1);
      for (int i = 0; i < CNT_N; i++) asm volatile("st.shared.u32 [%0], 0;" ::"r"(bar + B_PEND + 4 * i) : "memory");
      fence_barrier_init();
    }
    __syncthreads();
    asm volatile("barrier.cluster.arrive.relaxed.aligned;" ::: "memory");
    if ((mask & 1) && blockIdx.x >= 128) side_jobs(maps, sbase);
  }
  uint32_t smem0 = smem_u32(smem_raw);
  PHASE_PROLOGUE
  const bool do_qkv = (mask & 1) && blockIdx.x < 128, do_out = (mask & 4) && blockIdx.x < 128;
  TL(0, 1)

  if (wg != 2) {
    reg_alloc<232>();
    uint32_t sn = 0;
    float o[64];
    if (do_qkv) {
      sn = qkv_consumer(maps, smem_u32(smem_raw), mask & 2, o);
    } else {
      undef_regs(o);
    }
    TL(0, 2) TL(1, 0) TL(1, 1) LT(1, 0)
    asm volatile("barrier.cluster.wait.acquire.aligned;" ::: "memory");
    if (mask & 2) {
      sn = attn_consumer(maps, smem_u32(smem_raw), sn, o, mask & 1);
      TL(2, 0) LT(2, 0)
      if ((mask & 4) && blockIdx.x < 128 && __shfl_sync(0xffffffffu, threadIdx.x, 0) < 128) {
        named_bar_arrive(3, 256);
      } else {
        named_bar_sync(3, 256);
        const uint32_t b2 = blockIdx.x * 2 + (threadIdx.x >> 7);
        const bool fused = mask & 4, mainc = blockIdx.x < 128;
        const uint32_t first = __shfl_sync(0xffffffffu, !fused ? b2 : mainc ? conv_first(maps) : (b2 - 255) * 128 - C_SIDE, 0);
        conv_consumer(maps, smem_u32(smem_raw), first, !fused ? 264 : mainc ? 16 : 1,
                      !fused ? DM : (first | 127) + 1 - (mainc ? C_SIDE : 0));
      }
      TL(1, 2) TL(2, 1) TL(2, 2)
    }
    TL(3, 0) TL(3, 1)
    if ((mask & 4) && blockIdx.x < 128) out_gemm(maps, smem_u32(smem_raw));
    if (!(mask & 2) || blockIdx.x >= 128) {
      uint32_t smem0 = smem_u32(smem_raw);
      PHASE_PROLOGUE
      st_wait(bar, wg, sn - 2);
      st_post(bar, wg, wtid, sn, ST_END, nullptr, 0, 0, 0, -1);
    }
    tma_store_wait_read<0>();
    TL2(3, 2) LT(3, 128)
  } else {
    reg_dealloc<40>();
    asm volatile("barrier.cluster.wait.acquire.aligned;" ::: "memory");
    const int w = __shfl_sync(0xffffffffu, tid >> 5, 0) - 8;
    if (w < 2) {
      if (do_qkv) prep_agent(maps, sbase, w, lane);
      if (elect_one()) store_agent(bar, w);
    } else {
      if (elect_one()) {
        const bool dry = w == 2;
        if (do_qkv && !dry) qkv_producer(maps, sbase, false);
        if (mask & 2) attn_producer(maps, sbase, do_qkv, do_out, dry);
        if (do_out) out_producer(maps, sbase, mask & 2, dry);
        if (dry) { TD(5) }
      }
      __syncwarp();
      if (w == 2) publisher(bar, tid & 31, !(mask & 2) ? 2 : do_out ? 3 : 4);
      if ((tid & 31) == 0) leave_kernel(mask);
    }
  }
}

typedef CUresult (*PFN_tmapEncode)(CUtensorMap*, CUtensorMapDataType, cuuint32_t, void*, const cuuint64_t*,
                                   const cuuint64_t*, const cuuint32_t*, const cuuint32_t*, CUtensorMapInterleave,
                                   CUtensorMapSwizzle, CUtensorMapL2promotion, CUtensorMapFloatOOBfill);
static PFN_tmapEncode s_encode = nullptr;

static void make_map_2d(CUtensorMap* m, const void* ptr, int rows, int cols, int box_rows) {
  cuuint64_t dims[2] = {(cuuint64_t)cols, (cuuint64_t)rows};
  cuuint64_t strides[1] = {(cuuint64_t)cols * 2};
  cuuint32_t box[2] = {64, (cuuint32_t)box_rows};
  cuuint32_t es[2] = {1, 1};
  s_encode(m, CU_TENSOR_MAP_DATA_TYPE_BFLOAT16, 2, const_cast<void*>(ptr), dims, strides, box, es,
           CU_TENSOR_MAP_INTERLEAVE_NONE, CU_TENSOR_MAP_SWIZZLE_128B, CU_TENSOR_MAP_L2_PROMOTION_L2_256B,
           CU_TENSOR_MAP_FLOAT_OOB_FILL_NONE);
}
static void make_map_3d(CUtensorMap* m, const void* ptr, int rows, int cols, int box_rows, int box_chunks) {
  cuuint64_t dims[3] = {64, (cuuint64_t)rows, (cuuint64_t)(cols / 64)};
  cuuint64_t strides[2] = {(cuuint64_t)cols * 2, 128};
  cuuint32_t box[3] = {64, (cuuint32_t)box_rows, (cuuint32_t)box_chunks};
  cuuint32_t es[3] = {1, 1, 1};
  s_encode(m, CU_TENSOR_MAP_DATA_TYPE_BFLOAT16, 3, const_cast<void*>(ptr), dims, strides, box, es,
           CU_TENSOR_MAP_INTERLEAVE_NONE, CU_TENSOR_MAP_SWIZZLE_128B, CU_TENSOR_MAP_L2_PROMOTION_L2_256B,
           CU_TENSOR_MAP_FLOAT_OOB_FILL_NONE);
}

static void make_map_4d(CUtensorMap* m, const void* ptr, int rows, int cols, int b2, int groups) {
  cuuint64_t dims[4] = {(cuuint64_t)cols, 8, 8, (cuuint64_t)(rows / 64)};
  cuuint64_t strides[3] = {(cuuint64_t)cols * 16, (cuuint64_t)cols * 2, (cuuint64_t)cols * 128};
  cuuint32_t box[4] = {64, 8, (cuuint32_t)b2, (cuuint32_t)groups};
  cuuint32_t es[4] = {1, 1, 1, 1};
  s_encode(m, CU_TENSOR_MAP_DATA_TYPE_BFLOAT16, 4, const_cast<void*>(ptr), dims, strides, box, es,
           CU_TENSOR_MAP_INTERLEAVE_NONE, CU_TENSOR_MAP_SWIZZLE_128B, CU_TENSOR_MAP_L2_PROMOTION_L2_256B,
           CU_TENSOR_MAP_FLOAT_OOB_FILL_NONE);
}

static cudaLaunchConfig_t fused_cfg(cudaLaunchAttribute* at) {
  cudaLaunchConfig_t cfg = {};
  cfg.gridDim = dim3(132);
  cfg.blockDim = dim3(384);
  cfg.dynamicSmemBytes = SMEM_BYTES;
  cfg.stream = cudaStreamPerThread;
  at[0].id = cudaLaunchAttributeClusterDimension;
  at[0].val.clusterDim.x = 2;
  at[0].val.clusterDim.y = 1;
  at[0].val.clusterDim.z = 1;
  cfg.attrs = at;
  cfg.numAttrs = 1;
  return cfg;
}

extern "C" void kernel_launch(void* const* d_in, const int* in_sizes, int n_in, void* d_out, int out_size) {
  const bf16* x = (const bf16*)d_in[0];
  const bf16* ckv = (const bf16*)d_in[1];
  const bf16* wq = (const bf16*)d_in[2];
  const bf16* wuk = (const bf16*)d_in[3];
  const bf16* wuv = (const bf16*)d_in[4];
  const bf16* wo = (const bf16*)d_in[5];
  const bf16* bk = (const bf16*)d_in[7];
  const bf16* bv = (const bf16*)d_in[8];
  const bf16* shift_k = (const bf16*)d_in[9];
  const bf16* ssm_k = (const bf16*)d_in[10];
  const bf16* ssm_D = (const bf16*)d_in[11];
  const bf16* gate_w = (const bf16*)d_in[12];
  bf16* out = (bf16*)d_out;

  static void *pq = nullptr, *pk = nullptr, *pv = nullptr, *pctx = nullptr, *pb = nullptr;
  static int max_clusters = 0;
  if (!s_encode) {
    void* fn = nullptr;
    cudaDriverEntryPointQueryResult qres;
    cudaGetDriverEntryPoint("cuTensorMapEncodeTiled", &fn, cudaEnableDefault, &qres);
    s_encode = (PFN_tmapEncode)fn;
    cudaGetSymbolAddress(&pq, g_q);
    cudaGetSymbolAddress(&pk, g_k);
    cudaGetSymbolAddress(&pv, g_v);
    cudaGetSymbolAddress(&pctx, g_ctx);
    cudaGetSymbolAddress(&pb, g_y2T);
    cudaFuncSetAttribute(fused_kernel, cudaFuncAttributeMaxDynamicSharedMemorySize, SMEM_BYTES);
    cudaLaunchAttribute at[1];
    cudaLaunchConfig_t cfg = fused_cfg(at);
    if (cudaOccupancyMaxActiveClusters(&max_clusters, fused_kernel, &cfg) != cudaSuccess) max_clusters = 0;
  }

  Maps all = {};
  make_map_2d(&all.a[0], x, S_LEN, DM, 128);
  make_map_2d(&all.a[1], ckv, S_LEN, DC, 128);
  make_map_3d(&all.b[0], wq, DM, HDIM, 64, 4);
  make_map_3d(&all.b[1], wuk, DC, HDIM, 64, 4);
  make_map_3d(&all.b[2], wuv, DC, HDIM, 64, 4);
  make_map_2d(&all.c[0], pq, S_LEN, HDIM, 64);
  make_map_2d(&all.c[1], pk, S_LEN, HDIM, 64);
  make_map_2d(&all.c[2], pv, S_LEN, HDIM, 64);
  make_map_3d(&all.q, pq, S_LEN, HDIM, 128, 2);
  make_map_3d(&all.k, pk, S_LEN, HDIM, 128, 2);
  make_map_3d(&all.v, pv, S_LEN, HDIM, 128, 2);
  make_map_2d(&all.o, pctx, S_LEN, HDIM, 64);
  all.ssm_k = ssm_k;
  all.ssm_D = ssm_D;
  make_map_4d(&all.oa, pctx, S_LEN, HDIM, 8, 2);
  make_map_4d(&all.ox, x, S_LEN, DM, 8, 2);
  make_map_2d(&all.ob, wo, HDIM, DM, 64);
  make_map_4d(&all.oc, out, S_LEN, DM, 2, 1);
  make_map_2d(&all.y, pb, DM, S_LEN, 112);
  make_map_2d(&all.y2, pb, DM, S_LEN, 16);

  make_map_2d(&all.bk, bk, S_LEN, DM, 35);
  make_map_2d(&all.bv, bv, S_LEN, DM, 32);
  for (int b = 0; b < 128; b++) {
    const int c = b >> 1, r = b & 1;
    const int G = c < 4 ? 0 : c < 36 ? (c - 4) % 8 : 1 + (c - 36) % 7;
    const int i = c < 4 ? 4 + c : c < 36 ? (c - 4) / 8 : 4 + (c - 36) / 7;
    all.id[b][0] = r + 2 * (i & 1) + 4 * (G & 3) + 16 * (i >> 1) + 64 * (G >> 2);
    all.id[b][1] = r + 2 * i + 16 * G;
    all.id[b][2] = r + 2 * G + 16 * i;
  }
  all.shift_k = shift_k;
  all.x = x;
  all.gate_w = gate_w;
  cudaLaunchAttribute at[1];
  cudaLaunchConfig_t cfg = fused_cfg(at);
  if (max_clusters >= 66) {
    cudaLaunchKernelEx(&cfg, fused_kernel, 7, all);
  } else {
    for (int m = 1; m <= 4; m <<= 1) cudaLaunchKernelEx(&cfg, fused_kernel, m, all);
  }
}
```

```cpp
#include <cuda_runtime.h>
#include <cuda_bf16.h>
#include <cuda.h>
#include <stdint.h>

typedef __nv_bfloat16 bf16;
#define INPLACE 3

constexpr int S_LEN = 2048;
constexpr int DM = 1024;
constexpr int NH = 32;
constexpr int HD = 128;
constexpr int DC = 512;
constexpr int HDIM = NH * HD;

__device__ __align__(1024) bf16 g_q[S_LEN * HDIM];
__device__ __align__(1024) bf16 g_k[S_LEN * HDIM];
__device__ __align__(1024) bf16 g_v[S_LEN * HDIM];
#define g_ctx g_q
__device__ __align__(1024) bf16 g_kvT[DM * S_LEN];
#define g_y2T g_kvT
__device__ __align__(1024) float g_gate[S_LEN];
enum { CNT_KV = 0, CNT_PREP = CNT_KV + 2, CNT_CTX, CNT_Y2 = CNT_CTX + 2, CNT_DONE = CNT_Y2 + 2, CNT_N };
__device__ unsigned int g_cnt[CNT_N * 32];

#define TL(k, i)
#define TL2(k, i)
#define TD(i)
#define LT(i, thr)
#define PT_DECL
#define PT
#define CLK_DECL
#define CLK_SAMPLE
#define CLK_END
#define CT(i)
#define GT(i)
#define GS(i)
#define GA(i)
#define ST(i)

__device__ __forceinline__ uint32_t smem_u32(const void* p) { return (uint32_t)__cvta_generic_to_shared(p); }

__device__ __forceinline__ void mbar_init(uint32_t bar, uint32_t count) {
  asm volatile("mbarrier.init.shared::cta.b64 [%0], %1;" ::"r"(bar), "r"(count));
}
__device__ __forceinline__ void mbar_expect_tx(uint32_t bar, uint32_t bytes) {
  asm volatile("mbarrier.arrive.expect_tx.shared::cta.b64 _, [%0], %1;" ::"r"(bar), "r"(bytes) : "memory");
}
__device__ __forceinline__ void mbar_arrive(uint32_t bar) {
  asm volatile("mbarrier.arrive.shared::cta.b64 _, [%0];" ::"r"(bar) : "memory");
}
__device__ __forceinline__ void mbar_wait(uint32_t bar, uint32_t parity) {
  uint32_t done;
  uint32_t spins = 0;
  do {
    asm volatile(
        "{\n.reg .pred p;\n"
        "mbarrier.try_wait.parity.shared::cta.b64 p, [%1], %2;\n"
        "selp.u32 %0, 1, 0, p;\n}\n"
        : "=r"(done)
        : "r"(bar), "r"(parity)
        : "memory");
    if (++spins > (1u << 22)) break;
  } while (!done);
}
__device__ __forceinline__ bool mbar_try(uint32_t bar, uint32_t parity) {
  uint32_t done;
  asm volatile(
      "{\n.reg .pred p;\n"
      "mbarrier.try_wait.parity.shared::cta.b64 p, [%1], %2;\n"
      "selp.u32 %0, 1, 0, p;\n}\n"
      : "=r"(done)
      : "r"(bar), "r"(parity)
      : "memory");
  return done != 0;
}
__device__ __forceinline__ bool elect_one() {
  uint32_t pred;
  asm volatile("{\n.reg .pred p;\nelect.sync _|p, 0xffffffff;\nselp.u32 %0, 1, 0, p;\n}\n" : "=r"(pred));
  return pred != 0;
}
__device__ __forceinline__ void mbar_arrive_if(uint32_t bar, bool pred) {
  asm volatile(
      "{\n.reg .pred p;\nsetp.ne.b32 p, %1, 0;\n"
      "@p mbarrier.arrive.shared::cta.b64 _, [%0];\n}\n" ::"r"(bar),
      "r"((uint32_t)pred)
      : "memory");
}
__device__ __forceinline__ void mbar_wait_sleep(uint32_t bar, uint32_t parity) {
  uint32_t done;
  uint32_t spins = 0;
  do {
    asm volatile(
        "{\n.reg .pred p;\n"
        "mbarrier.try_wait.parity.shared::cta.b64 p, [%1], %2, %3;\n"
        "selp.u32 %0, 1, 0, p;\n}\n"
        : "=r"(done)
        : "r"(bar), "r"(parity), "r"(20000u)
        : "memory");
    if (++spins > (1u << 16)) break;
  } while (!done);
}
__device__ __forceinline__ void fence_barrier_init() {
  asm volatile("fence.mbarrier_init.release.cluster;" ::: "memory");
}
__device__ __forceinline__ void fence_proxy_async() {
  asm volatile("fence.proxy.async.shared::cta;" ::: "memory");
}
__device__ __forceinline__ void named_bar_sync(int id, int nthreads) {
  asm volatile("bar.sync %0, %1;" ::"r"(id), "r"(nthreads) : "memory");
}
__device__ __forceinline__ void named_bar_arrive(int id, int nthreads) {
  asm volatile("bar.arrive %0, %1;" ::"r"(id), "r"(nthreads) : "memory");
}
__device__ __forceinline__ void tma_load_2d(uint32_t dst, const CUtensorMap* m, uint32_t bar, int c0, int c1) {
  asm volatile(
      "cp.async.bulk.tensor.2d.shared::cluster.global.mbarrier::complete_tx::bytes [%0], [%1, {%3, %4}], [%2];" ::"r"(dst),
      "l"(reinterpret_cast<uint64_t>(m)), "r"(bar), "r"(c0), "r"(c1)
      : "memory");
}
__device__ __forceinline__ void tma_load_3d(uint32_t dst, const CUtensorMap* m, uint32_t bar, int c0, int c1, int c2) {
  asm volatile(
      "cp.async.bulk.tensor.3d.shared::cluster.global.mbarrier::complete_tx::bytes [%0], [%1, {%3, %4, %5}], [%2];" ::"r"(dst),
      "l"(reinterpret_cast<uint64_t>(m)), "r"(bar), "r"(c0), "r"(c1), "r"(c2)
      : "memory");
}
__device__ __forceinline__ void tma_store_2d(const CUtensorMap* m, uint32_t src, int c0, int c1) {
  asm volatile("cp.async.bulk.tensor.2d.global.shared::cta.bulk_group [%0, {%2, %3}], [%1];" ::"l"(
                   reinterpret_cast<uint64_t>(m)),
               "r"(src), "r"(c0), "r"(c1)
               : "memory");
}
__device__ __forceinline__ void tma_load_4d(uint32_t dst, const CUtensorMap* m, uint32_t bar, int c0, int tile) {
  asm volatile(
      "cp.async.bulk.tensor.4d.shared::cluster.global.mbarrier::complete_tx::bytes [%0], [%1, {%3, %4, %4, %5}], [%2];" ::"r"(dst),
      "l"(reinterpret_cast<uint64_t>(m)), "r"(bar), "r"(c0), "r"(0), "r"(2 * tile)
      : "memory");
}
__device__ __forceinline__ void tma_store_4d(const CUtensorMap* m, uint32_t src, int c0, int c2, int group) {
  asm volatile("cp.async.bulk.tensor.4d.global.shared::cta.bulk_group [%0, {%2, %3, %4, %5}], [%1];" ::"l"(
                   reinterpret_cast<uint64_t>(m)),
               "r"(src), "r"(c0), "r"(0), "r"(c2), "r"(group)
               : "memory");
}
__device__ __forceinline__ void bulk_load(uint32_t dst, const void* src, uint32_t bytes, uint32_t bar) {
  asm volatile("cp.async.bulk.shared::cluster.global.mbarrier::complete_tx::bytes [%0], [%1], %2, [%3];" ::"r"(dst),
               "l"(src), "r"(bytes), "r"(bar)
               : "memory");
}
__device__ __forceinline__ void tma_load_2d_mc(uint32_t dst, const CUtensorMap* m, uint32_t bar, int c0, int c1,
                                               uint16_t mask) {
  asm volatile(
      "cp.async.bulk.tensor.2d.shared::cluster.global.mbarrier::complete_tx::bytes.multicast::cluster [%0], [%1, {%3, "
      "%4}], [%2], %5;" ::"r"(dst),
      "l"(reinterpret_cast<uint64_t>(m)), "r"(bar), "r"(c0), "r"(c1), "h"(mask)
      : "memory");
}
__device__ __forceinline__ void mbar_arrive_cluster_if(uint32_t bar, uint32_t cta, bool pred) {
  asm volatile(
      "{\n.reg .b32 ra;\n.reg .pred p;\nsetp.ne.b32 p, %2, 0;\n"
      "mapa.shared::cluster.u32 ra, %0, %1;\n"
      "@p mbarrier.arrive.shared::cluster.b64 _, [ra];\n}\n" ::"r"(bar),
      "r"(cta), "r"((uint32_t)pred)
      : "memory");
}
__device__ __forceinline__ uint64_t policy_evict_first() {
  uint64_t pol;
  asm volatile("createpolicy.fractional.L2::evict_first.b64 %0, 1.0;" : "=l"(pol));
  return pol;
}
__device__ __forceinline__ void tma_load_2d_hint(uint32_t dst, const CUtensorMap* m, uint32_t bar, int c0, int c1,
                                                 uint64_t pol) {
  asm volatile(
      "cp.async.bulk.tensor.2d.shared::cluster.global.mbarrier::complete_tx::bytes.L2::cache_hint [%0], [%1, {%3, %4}], "
      "[%2], %5;" ::"r"(dst),
      "l"(reinterpret_cast<uint64_t>(m)), "r"(bar), "r"(c0), "r"(c1), "l"(pol)
      : "memory");
}
__device__ __forceinline__ void tma_load_3d_hint(uint32_t dst, const CUtensorMap* m, uint32_t bar, int c0, int c1,
                                                 int c2, uint64_t pol) {
  asm volatile(
      "cp.async.bulk.tensor.3d.shared::cluster.global.mbarrier::complete_tx::bytes.L2::cache_hint [%0], [%1, {%3, %4, "
      "%5}], [%2], %6;" ::"r"(dst),
      "l"(reinterpret_cast<uint64_t>(m)), "r"(bar), "r"(c0), "r"(c1), "r"(c2), "l"(pol)
      : "memory");
}
__device__ __forceinline__ void bulk_load_hint(uint32_t dst, const void* src, uint32_t bytes, uint32_t bar, uint64_t pol) {
  asm volatile(
      "cp.async.bulk.shared::cluster.global.mbarrier::complete_tx::bytes.L2::cache_hint [%0], [%1], %2, [%3], %4;" ::"r"(dst),
      "l"(src), "r"(bytes), "r"(bar), "l"(pol)
      : "memory");
}
__device__ __forceinline__ void cnt_signal_release(int which, uint32_t n) {
  asm volatile("red.release.gpu.global.add.u32 [%0], %1;" ::"l"(g_cnt + which * 32), "r"(n) : "memory");
}
__device__ __forceinline__ void cnt_wait(int which, uint32_t target) {
  uint32_t v, spins = 0;
  while (true) {
    asm volatile("ld.acquire.gpu.global.u32 %0, [%1];" : "=r"(v) : "l"(g_cnt + which * 32) : "memory");
    if (v >= target || ++spins > (1u << 18)) break;
    __nanosleep(64);
  }
  asm volatile("fence.proxy.async.global;" ::: "memory");
}
__device__ __forceinline__ void tma_store_commit() { asm volatile("cp.async.bulk.commit_group;" ::: "memory"); }
template <int N>
__device__ __forceinline__ void tma_store_wait_read() {
  asm volatile("cp.async.bulk.wait_group.read %0;" ::"n"(N) : "memory");
}
template <int N>
__device__ __forceinline__ void tma_store_wait() {
  asm volatile("cp.async.bulk.wait_group %0;" ::"n"(N) : "memory");
}
__device__ __forceinline__ void wgmma_fence() { asm volatile("wgmma.fence.sync.aligned;" ::: "memory"); }
__device__ __forceinline__ void wgmma_commit() { asm volatile("wgmma.commit_group.sync.aligned;" ::: "memory"); }
template <int N>
__device__ __forceinline__ void wgmma_wait() {
  asm volatile("wgmma.wait_group.sync.aligned %0;" ::"n"(N) : "memory");
}
template <int R>
__device__ __forceinline__ void reg_alloc() { asm volatile("setmaxnreg.inc.sync.aligned.u32 %0;" ::"n"(R)); }
template <int R>
__device__ __forceinline__ void reg_dealloc() { asm volatile("setmaxnreg.dec.sync.aligned.u32 %0;" ::"n"(R)); }

__device__ __forceinline__ void stmatrix_x4(uint32_t addr, uint32_t r0, uint32_t r1, uint32_t r2, uint32_t r3) {
  asm volatile("stmatrix.sync.aligned.m8n8.x4.shared.b16 [%0], {%1, %2, %3, %4};" ::"r"(addr), "r"(r0), "r"(r1),
               "r"(r2), "r"(r3)
               : "memory");
}
__device__ __forceinline__ uint32_t pack_bf16(float lo, float hi) {
  uint32_t r;
  asm("cvt.rn.bf16x2.f32 %0, %1, %2;" : "=r"(r) : "f"(hi), "f"(lo));
  return r;
}
__device__ __forceinline__ float bf16_round(float x) { return __bfloat162float(__float2bfloat16_rn(x)); }
__device__ __forceinline__ float bf_lo(uint32_t v) { return __uint_as_float(v << 16); }
__device__ __forceinline__ float bf_hi(uint32_t v) { return __uint_as_float(v & 0xffff0000u); }
__device__ __forceinline__ uint4 lds128(uint32_t a) {
  uint4 v;
  asm volatile("ld.shared.v4.u32 {%0, %1, %2, %3}, [%4];" : "=r"(v.x), "=r"(v.y), "=r"(v.z), "=r"(v.w) : "r"(a));
  return v;
}
__device__ __forceinline__ void sts128(uint32_t a, uint4 v) {
  asm volatile("st.shared.v4.u32 [%0], {%1, %2, %3, %4};" ::"r"(a), "r"(v.x), "r"(v.y), "r"(v.z), "r"(v.w) : "memory");
}
__device__ __forceinline__ uint32_t mul_bf2(uint32_t a, uint32_t b) {
  uint32_t r;
  asm("mul.rn.bf16x2 %0, %1, %2;" : "=r"(r) : "r"(a), "r"(b));
  return r;
}
__device__ __forceinline__ uint32_t add_bf2(uint32_t a, uint32_t b) {
  uint32_t r;
  asm("add.rn.bf16x2 %0, %1, %2;" : "=r"(r) : "r"(a), "r"(b));
  return r;
}
__device__ __forceinline__ float ex2(float x) {
  float y;
  asm("ex2.approx.ftz.f32 %0, %1;" : "=f"(y) : "f"(x));
  return y;
}
__device__ __forceinline__ float rcp(float x) {
  float y;
  asm("rcp.approx.ftz.f32 %0, %1;" : "=f"(y) : "f"(x));
  return y;
}
template <int N>
__device__ __forceinline__ void fence_regs(float (&r)[N]) {
#pragma unroll
  for (int i = 0; i < N; i++) asm volatile("" : "+f"(r[i])::"memory");
}

template <int N>
__device__ __forceinline__ void undef_regs(float (&r)[N]) {
#pragma unroll
  for (int i = 0; i < N; i++) asm volatile("" : "=f"(r[i]));
}
template <int N>
__device__ __forceinline__ void fence_regs_u(uint32_t (&r)[N]) {
#pragma unroll
  for (int i = 0; i < N; i++) asm volatile("" : "+r"(r[i])::"memory");
}

constexpr uint64_t DESC_SW128 = 1ull << 62;
__device__ __forceinline__ uint64_t make_desc(uint32_t addr, uint32_t lbo_bytes, uint32_t sbo_bytes, uint64_t swz) {
  return (uint64_t)((addr & 0x3FFFF) >> 4) | ((uint64_t)((lbo_bytes & 0x3FFFF) >> 4) << 16) |
         ((uint64_t)((sbo_bytes & 0x3FFFF) >> 4) << 32) | swz;
}

__device__ __forceinline__ uint64_t desc_add(uint64_t d, uint32_t off16) {
  return (d & 0xFFFFFFFF00000000ull) | (uint64_t)((uint32_t)d + off16);
}

__device__ __forceinline__ void wgmma_m64n256_ss_tb(float (&d)[128], uint64_t da, uint64_t db, int sd) {
  asm volatile(
    "{\n.reg .pred p;\nsetp.ne.b32 p, %130, 0;\n"
    "wgmma.mma_async.sync.aligned.m64n256k16.f32.bf16.bf16 "
    "{%0, %1, %2, %3, %4, %5, %6, %7, %8, %9, %10, %11, %12, %13, %14, %15, %16, %17, %18, %19, %20, %21, %22, %23, %24, %25, %26, %27, %28, %29, %30, %31, %32, %33, %34, %35, %36, %37, %38, %39, %40, %41, %42, %43, %44, %45, %46, %47, %48, %49, %50, %51, %52, %53, %54, %55, %56, %57, %58, %59, %60, %61, %62, %63, %64, %65, %66, %67, %68, %69, %70, %71, %72, %73, %74, %75, %76, %77, %78, %79, %80, %81, %82, %83, %84, %85, %86, %87, %88, %89, %90, %91, %92, %93, %94, %95, %96, %97, %98, %99, %100, %101, %102, %103, %104, %105, %106, %107, %108, %109, %110, %111, %112, %113, %114, %115, %116, %117, %118, %119, %120, %121, %122, %123, %124, %125, %126, %127}, %128, %129, p, 1, 1, 0, 1;\n}\n"
    : "+f"(d[0]), "+f"(d[1]), "+f"(d[2]), "+f"(d[3]), "+f"(d[4]), "+f"(d[5]), "+f"(d[6]), "+f"(d[7]), "+f"(d[8]), "+f"(d[9]), "+f"(d[10]), "+f"(d[11]), "+f"(d[12]), "+f"(d[13]), "+f"(d[14]), "+f"(d[15]), "+f"(d[16]), "+f"(d[17]), "+f"(d[18]), "+f"(d[19]), "+f"(d[20]), "+f"(d[21]), "+f"(d[22]), "+f"(d[23]), "+f"(d[24]), "+f"(d[25]), "+f"(d[26]), "+f"(d[27]), "+f"(d[28]), "+f"(d[29]), "+f"(d[30]), "+f"(d[31]), "+f"(d[32]), "+f"(d[33]), "+f"(d[34]), "+f"(d[35]), "+f"(d[36]), "+f"(d[37]), "+f"(d[38]), "+f"(d[39]), "+f"(d[40]), "+f"(d[41]), "+f"(d[42]), "+f"(d[43]), "+f"(d[44]), "+f"(d[45]), "+f"(d[46]), "+f"(d[47]), "+f"(d[48]), "+f"(d[49]), "+f"(d[50]), "+f"(d[51]), "+f"(d[52]), "+f"(d[53]), "+f"(d[54]), "+f"(d[55]), "+f"(d[56]), "+f"(d[57]), "+f"(d[58]), "+f"(d[59]), "+f"(d[60]), "+f"(d[61]), "+f"(d[62]), "+f"(d[63]), "+f"(d[64]), "+f"(d[65]), "+f"(d[66]), "+f"(d[67]), "+f"(d[68]), "+f"(d[69]), "+f"(d[70]), "+f"(d[71]), "+f"(d[72]), "+f"(d[73]), "+f"(d[74]), "+f"(d[75]), "+f"(d[76]), "+f"(d[77]), "+f"(d[78]), "+f"(d[79]), "+f"(d[80]), "+f"(d[81]), "+f"(d[82]), "+f"(d[83]), "+f"(d[84]), "+f"(d[85]), "+f"(d[86]), "+f"(d[87]), "+f"(d[88]), "+f"(d[89]), "+f"(d[90]), "+f"(d[91]), "+f"(d[92]), "+f"(d[93]), "+f"(d[94]), "+f"(d[95]), "+f"(d[96]), "+f"(d[97]), "+f"(d[98]), "+f"(d[99]), "+f"(d[100]), "+f"(d[101]), "+f"(d[102]), "+f"(d[103]), "+f"(d[104]), "+f"(d[105]), "+f"(d[106]), "+f"(d[107]), "+f"(d[108]), "+f"(d[109]), "+f"(d[110]), "+f"(d[111]), "+f"(d[112]), "+f"(d[113]), "+f"(d[114]), "+f"(d[115]), "+f"(d[116]), "+f"(d[117]), "+f"(d[118]), "+f"(d[119]), "+f"(d[120]), "+f"(d[121]), "+f"(d[122]), "+f"(d[123]), "+f"(d[124]), "+f"(d[125]), "+f"(d[126]), "+f"(d[127])
    : "l"(da), "l"(db), "r"(sd));
}

__device__ __forceinline__ void wgmma_m64n128_ss(float (&d)[64], uint64_t da, uint64_t db, int sd) {
  asm volatile(
    "{\n.reg .pred p;\nsetp.ne.b32 p, %66, 0;\n"
    "wgmma.mma_async.sync.aligned.m64n128k16.f32.bf16.bf16 "
    "{%0, %1, %2, %3, %4, %5, %6, %7, %8, %9, %10, %11, %12, %13, %14, %15, %16, %17, %18, %19, %20, %21, %22, %23, %24, %25, %26, %27, %28, %29, %30, %31, %32, %33, %34, %35, %36, %37, %38, %39, %40, %41, %42, %43, %44, %45, %46, %47, %48, %49, %50, %51, %52, %53, %54, %55, %56, %57, %58, %59, %60, %61, %62, %63}, %64, %65, p, 1, 1, 0, 0;\n}\n"
    : "+f"(d[0]), "+f"(d[1]), "+f"(d[2]), "+f"(d[3]), "+f"(d[4]), "+f"(d[5]), "+f"(d[6]), "+f"(d[7]), "+f"(d[8]), "+f"(d[9]), "+f"(d[10]), "+f"(d[11]), "+f"(d[12]), "+f"(d[13]), "+f"(d[14]), "+f"(d[15]), "+f"(d[16]), "+f"(d[17]), "+f"(d[18]), "+f"(d[19]), "+f"(d[20]), "+f"(d[21]), "+f"(d[22]), "+f"(d[23]), "+f"(d[24]), "+f"(d[25]), "+f"(d[26]), "+f"(d[27]), "+f"(d[28]), "+f"(d[29]), "+f"(d[30]), "+f"(d[31]), "+f"(d[32]), "+f"(d[33]), "+f"(d[34]), "+f"(d[35]), "+f"(d[36]), "+f"(d[37]), "+f"(d[38]), "+f"(d[39]), "+f"(d[40]), "+f"(d[41]), "+f"(d[42]), "+f"(d[43]), "+f"(d[44]), "+f"(d[45]), "+f"(d[46]), "+f"(d[47]), "+f"(d[48]), "+f"(d[49]), "+f"(d[50]), "+f"(d[51]), "+f"(d[52]), "+f"(d[53]), "+f"(d[54]), "+f"(d[55]), "+f"(d[56]), "+f"(d[57]), "+f"(d[58]), "+f"(d[59]), "+f"(d[60]), "+f"(d[61]), "+f"(d[62]), "+f"(d[63])
    : "l"(da), "l"(db), "r"(sd));
}

__device__ __forceinline__ void wgmma_m64n128_ss_tb(float (&d)[64], uint64_t da, uint64_t db, int sd) {
  asm volatile(
    "{\n.reg .pred p;\nsetp.ne.b32 p, %66, 0;\n"
    "wgmma.mma_async.sync.aligned.m64n128k16.f32.bf16.bf16 "
    "{%0, %1, %2, %3, %4, %5, %6, %7, %8, %9, %10, %11, %12, %13, %14, %15, %16, %17, %18, %19, %20, %21, %22, %23, %24, %25, %26, %27, %28, %29, %30, %31, %32, %33, %34, %35, %36, %37, %38, %39, %40, %41, %42, %43, %44, %45, %46, %47, %48, %49, %50, %51, %52, %53, %54, %55, %56, %57, %58, %59, %60, %61, %62, %63}, %64, %65, p, 1, 1, 0, 1;\n}\n"
    : "+f"(d[0]), "+f"(d[1]), "+f"(d[2]), "+f"(d[3]), "+f"(d[4]), "+f"(d[5]), "+f"(d[6]), "+f"(d[7]), "+f"(d[8]), "+f"(d[9]), "+f"(d[10]), "+f"(d[11]), "+f"(d[12]), "+f"(d[13]), "+f"(d[14]), "+f"(d[15]), "+f"(d[16]), "+f"(d[17]), "+f"(d[18]), "+f"(d[19]), "+f"(d[20]), "+f"(d[21]), "+f"(d[22]), "+f"(d[23]), "+f"(d[24]), "+f"(d[25]), "+f"(d[26]), "+f"(d[27]), "+f"(d[28]), "+f"(d[29]), "+f"(d[30]), "+f"(d[31]), "+f"(d[32]), "+f"(d[33]), "+f"(d[34]), "+f"(d[35]), "+f"(d[36]), "+f"(d[37]), "+f"(d[38]), "+f"(d[39]), "+f"(d[40]), "+f"(d[41]), "+f"(d[42]), "+f"(d[43]), "+f"(d[44]), "+f"(d[45]), "+f"(d[46]), "+f"(d[47]), "+f"(d[48]), "+f"(d[49]), "+f"(d[50]), "+f"(d[51]), "+f"(d[52]), "+f"(d[53]), "+f"(d[54]), "+f"(d[55]), "+f"(d[56]), "+f"(d[57]), "+f"(d[58]), "+f"(d[59]), "+f"(d[60]), "+f"(d[61]), "+f"(d[62]), "+f"(d[63])
    : "l"(da), "l"(db), "r"(sd));
}

__device__ __forceinline__ void wgmma_m64n128_rs_tb(float* d, uint32_t a0, uint32_t a1, uint32_t a2, uint32_t a3, uint64_t db, int sd) {
  asm volatile(
    "{\n.reg .pred p;\nsetp.ne.b32 p, %69, 0;\n"
    "wgmma.mma_async.sync.aligned.m64n128k16.f32.bf16.bf16 "
    "{%0, %1, %2, %3, %4, %5, %6, %7, %8, %9, %10, %11, %12, %13, %14, %15, %16, %17, %18, %19, %20, %21, %22, %23, %24, %25, %26, %27, %28, %29, %30, %31, %32, %33, %34, %35, %36, %37, %38, %39, %40, %41, %42, %43, %44, %45, %46, %47, %48, %49, %50, %51, %52, %53, %54, %55, %56, %57, %58, %59, %60, %61, %62, %63}, {%64, %65, %66, %67}, %68, p, 1, 1, 1;\n}\n"
    : "+f"(d[0]), "+f"(d[1]), "+f"(d[2]), "+f"(d[3]), "+f"(d[4]), "+f"(d[5]), "+f"(d[6]), "+f"(d[7]), "+f"(d[8]), "+f"(d[9]), "+f"(d[10]), "+f"(d[11]), "+f"(d[12]), "+f"(d[13]), "+f"(d[14]), "+f"(d[15]), "+f"(d[16]), "+f"(d[17]), "+f"(d[18]), "+f"(d[19]), "+f"(d[20]), "+f"(d[21]), "+f"(d[22]), "+f"(d[23]), "+f"(d[24]), "+f"(d[25]), "+f"(d[26]), "+f"(d[27]), "+f"(d[28]), "+f"(d[29]), "+f"(d[30]), "+f"(d[31]), "+f"(d[32]), "+f"(d[33]), "+f"(d[34]), "+f"(d[35]), "+f"(d[36]), "+f"(d[37]), "+f"(d[38]), "+f"(d[39]), "+f"(d[40]), "+f"(d[41]), "+f"(d[42]), "+f"(d[43]), "+f"(d[44]), "+f"(d[45]), "+f"(d[46]), "+f"(d[47]), "+f"(d[48]), "+f"(d[49]), "+f"(d[50]), "+f"(d[51]), "+f"(d[52]), "+f"(d[53]), "+f"(d[54]), "+f"(d[55]), "+f"(d[56]), "+f"(d[57]), "+f"(d[58]), "+f"(d[59]), "+f"(d[60]), "+f"(d[61]), "+f"(d[62]), "+f"(d[63])
    : "r"(a0), "r"(a1), "r"(a2), "r"(a3), "l"(db), "r"(sd));
}

__device__ __forceinline__ void wgmma_m64n64_rs(float (&d)[32], const uint32_t* a, uint64_t db, int sd) {
  asm volatile(
    "{\n.reg .pred p;\nsetp.ne.b32 p, %37, 0;\n"
    "wgmma.mma_async.sync.aligned.m64n64k16.f32.bf16.bf16 "
    "{%0, %1, %2, %3, %4, %5, %6, %7, %8, %9, %10, %11, %12, %13, %14, %15, %16, %17, %18, %19, %20, %21, %22, %23, %24, %25, %26, %27, %28, %29, %30, %31}, {%32, %33, %34, %35}, %36, p, 1, 1, 0;\n}\n"
    : "+f"(d[0]), "+f"(d[1]), "+f"(d[2]), "+f"(d[3]), "+f"(d[4]), "+f"(d[5]), "+f"(d[6]), "+f"(d[7]), "+f"(d[8]), "+f"(d[9]), "+f"(d[10]), "+f"(d[11]), "+f"(d[12]), "+f"(d[13]), "+f"(d[14]), "+f"(d[15]), "+f"(d[16]), "+f"(d[17]), "+f"(d[18]), "+f"(d[19]), "+f"(d[20]), "+f"(d[21]), "+f"(d[22]), "+f"(d[23]), "+f"(d[24]), "+f"(d[25]), "+f"(d[26]), "+f"(d[27]), "+f"(d[28]), "+f"(d[29]), "+f"(d[30]), "+f"(d[31])
    : "r"(a[0]), "r"(a[1]), "r"(a[2]), "r"(a[3]), "l"(db), "r"(sd));
}

constexpr int G_STAGES = 4;
constexpr int G_A_BYTES = 128 * 64 * 2;
constexpr int G_B_BYTES = 256 * 64 * 2;
constexpr int G_STAGE_BYTES = G_A_BYTES + G_B_BYTES;
constexpr int G_STG_OFF = G_STAGES * G_STAGE_BYTES;
constexpr int BAR_OFF = G_STG_OFF + 32768 + 2048;
constexpr int SMEM_BYTES = BAR_OFF + 1024;
constexpr int B_GFULL = 0, B_GEMPTY = 32, B_OY2 = 64, B_PFULL = 224;
constexpr int B_KFULL = 80, B_KEMPTY = 96, B_VFULL = 112, B_VEMPTY = 128, B_QFULL = 144, B_QEMPTY = 160,
              B_QDONE = 184;
constexpr int B_CFULL = 192;
constexpr int B_OFREE = 256, B_OFULL = 272, B_OEMPTY = 320, B_OY = 368;
constexpr int B_SFULL = 392, B_SFREE = 424, B_PEND = 456, B_SCMD = 512;

#define PHASE_PROLOGUE                                                                \
  uint32_t tid, rt_zero;                                                              \
  asm volatile("mov.u32 %0, %%tid.x;" : "=r"(tid));                                   \
  asm volatile("mov.u32 %0, %%nctaid.y;" : "=r"(rt_zero));                            \
  asm volatile("" : "+r"(smem0));                                                     \
  rt_zero = __shfl_sync(0xffffffffu, rt_zero >> 8, 0);   \
  const uint32_t sbase = __shfl_sync(0xffffffffu, smem0, 0);                          \
  const uint32_t bar = sbase + BAR_OFF;                                               \
  const int wg = __shfl_sync(0xffffffffu, tid >> 7, 0);                               \
  const int warp = (tid >> 5) & 3, lane = tid & 31, wtid = tid & 127;                 \
  (void)rt_zero; (void)bar; (void)warp; (void)lane; (void)wtid;

enum { ST_END = 0, ST_BOX1, ST_BOX2, ST_BOX2Q, ST_BOX2L };
__device__ __forceinline__ void st_post(uint32_t bar, int wg, int wtid, uint32_t n, int kind, const void* dst,
                                        uint32_t src, int c0, int c1, int sig) {
  if (wtid == 0) {
    const uint32_t c = bar + B_SCMD + wg * 64 + (n & 1) * 32;
    const uint64_t d = reinterpret_cast<uint64_t>(dst);
    sts128(c, make_uint4(kind, src, c0, c1));
    sts128(c + 16, make_uint4((uint32_t)d, (uint32_t)(d >> 32), sig, 0));
  }
  fence_proxy_async();
  __syncwarp();
  mbar_arrive_if(bar + B_SFULL + wg * 16 + (n & 1) * 8, (wtid & 31) == 0);
}
__device__ __forceinline__ void st_wait(uint32_t bar, int wg, uint32_t n) {
  const uint32_t b = bar + B_SFREE + wg * 16 + (n & 1) * 8;
  if (!mbar_try(b, ~(n >> 1) & 1)) mbar_wait(b, ~(n >> 1) & 1);
}
__device__ __forceinline__ void note(uint32_t bar, uint32_t cnt) {
  asm volatile("red.release.cta.shared.add.u32 [%0], 1;" ::"r"(bar + B_PEND + 4 * cnt) : "memory");
}
__device__ __forceinline__ void store_agent(uint32_t bar, int wg) {
  mbar_arrive(bar + B_SFREE + wg * 16);
  mbar_arrive(bar + B_SFREE + wg * 16 + 8);
  for (uint32_t n = 0;; n++) {
    mbar_wait_sleep(bar + B_SFULL + wg * 16 + (n & 1) * 8, (n >> 1) & 1);
    const uint4 c = lds128(bar + B_SCMD + wg * 64 + (n & 1) * 32);
    const uint4 d = lds128(bar + B_SCMD + wg * 64 + (n & 1) * 32 + 16);
    if (c.x == ST_END) break;
    const CUtensorMap* dst = reinterpret_cast<const CUtensorMap*>((uint64_t)d.x | ((uint64_t)d.y << 32));
    tma_store_2d(dst, c.y, c.z, c.w);
    if (c.x >= ST_BOX2) tma_store_2d(dst, c.y + 8192, c.z + 64, c.w);
    tma_store_commit();
    tma_store_wait_read<0>();
    mbar_arrive(bar + B_SFREE + wg * 16 + (n & 1) * 8);
    if (c.x == ST_BOX2L) mbar_arrive(bar + B_OFREE + 8 * wg);
    if ((int)d.z >= 0) {
      tma_store_wait<0>();
      if (d.z == 0) { TD(6) }
      asm volatile("fence.proxy.async.global;" ::: "memory");
      if (c.x == ST_BOX2Q) mbar_arrive(bar + B_QDONE);
      else note(bar, d.z);
      if (c.x == ST_BOX2L) break;
    }
  }
  note(bar, CNT_DONE);
}

struct Maps {
  const bf16 *shift_k, *x, *gate_w, *ssm_k, *ssm_D;
  uint8_t id[128][4];
  CUtensorMap a[2];
  CUtensorMap b[3];
  CUtensorMap c[3];
  CUtensorMap bk, bv;
  CUtensorMap q, k, v, o;
  CUtensorMap oa, ob, oc, ox;
  CUtensorMap y, y2;
};

constexpr int P_SLOT = 67 * 128, P_V = 35 * 128, P_TAPS = 2 * P_SLOT;
__device__ __forceinline__ void ldsm4t(uint32_t (&r)[4], uint32_t a) {
  asm volatile("ldmatrix.sync.aligned.m8n8.x4.trans.shared.b16 {%0, %1, %2, %3}, [%4];"
               : "=r"(r[0]), "=r"(r[1]), "=r"(r[2]), "=r"(r[3])
               : "r"(a));
}
__device__ __forceinline__ uint32_t fma_bf2(uint32_t a, uint32_t b, uint32_t c) {
  uint32_t r;
  asm("fma.rn.bf16x2 %0, %1, %2, %3;" : "=r"(r) : "r"(a), "r"(b), "r"(c));
  return r;
}
__device__ __forceinline__ void prep_agent(const Maps& maps, uint32_t sbase, int w, int lane) {
  const uint32_t bar = sbase + BAR_OFF, pb = bar + B_PFULL + w * 16;
  const int d0 = (blockIdx.x >> 3) * 64, t0 = (blockIdx.x & 7) * 256 + w * 128;
  mbar_wait_sleep(bar + B_GFULL + 8 * (G_STAGES - 1), 0);
#pragma unroll 1
  for (int i = -1; i < 4; i++) {
    GA(82 + 2 * i)
    if (i >= 0) mbar_wait_sleep(pb + (i & 1) * 8, i >> 1);
    GA(83 + 2 * i)
    const uint32_t so = sbase + G_STG_OFF + w * (P_TAPS + 512) + (i & 1) * P_SLOT;
    if (i < 3 && elect_one()) {
      const uint32_t b = pb + (~i & 1) * 8, dst = so + (i & 1 ? -P_SLOT : P_SLOT);
      mbar_expect_tx(b, i < 0 ? P_SLOT + 512 : P_SLOT);
      const uint64_t pol = policy_evict_first();
      tma_load_2d_hint(dst, &maps.bk, b, d0, t0 + 32 * i + 29, pol);
      tma_load_2d_hint(dst + P_V, &maps.bv, b, d0, t0 + 32 * i + 32, pol);
      if (i < 0) bulk_load(sbase + G_STG_OFF + P_TAPS, maps.shift_k + d0 * 4, 512, b);
    }
    if (i < 0) continue;
    uint32_t ak[4];
#pragma unroll
    for (int r = 0; r < 4; r++) {
      const uint32_t a = so / 128 + r + 4 * (lane & 6) + (((((lane >> 2) ^ lane) & 6) + (lane & 1)) ^ 7);
      ak[r] = a * 128 + (a & 7) * 16;
    }
    bf16* dst = g_kvT + (size_t)(d0 + (lane >> 2)) * S_LEN + t0 + ((lane & 3) + 4 * i) * 8;
#pragma unroll 1
    for (int cg = 0; cg < 128; cg += 16) {
      uint32_t t01, t23, k[4][4], v[4];
      asm volatile("ld.shared.v2.u32 {%0, %1}, [%2];"
                   : "=r"(t01), "=r"(t23)
                   : "r"(sbase + G_STG_OFF + P_TAPS + cg * 4 + (lane >> 2) * 8));
#pragma unroll
      for (int r = 0; r < 4; r++) ldsm4t(k[r], ak[r] ^ cg);
      ldsm4t(v, (ak[3] ^ cg) + 4096);
      const uint32_t w0 = __byte_perm(t01, 0, 0x1010), w1 = __byte_perm(t01, 0, 0x3232);
      const uint32_t w2 = __byte_perm(t23, 0, 0x1010), w3 = __byte_perm(t23, 0, 0x3232);
#pragma unroll
      for (int j = 0; j < 4; j++)
        v[j] = mul_bf2(fma_bf2(k[3][j], w0, fma_bf2(k[2][j], w1, fma_bf2(k[1][j], w2, mul_bf2(k[0][j], w3)))), v[j]);
      const bool s1 = lane & 1, s2 = lane & 2;
      const uint32_t a0 = s1 ? v[1] : v[0], a1 = s1 ? v[0] : v[1], a2 = s1 ? v[3] : v[2], a3 = s1 ? v[2] : v[3];
      *reinterpret_cast<uint4*>(dst) = make_uint4(s2 ? a2 : a0, s2 ? a3 : a1, s2 ? a0 : a2, s2 ? a1 : a3);
      dst += 8 * S_LEN;
    }
    fence_proxy_async();
    __syncwarp();
  }
  GA(90)
  if (lane == 0) note(bar, CNT_PREP);
  __syncwarp();
  GA(91)
}

__device__ __forceinline__ void qkv_tile(const Maps& maps, int it, int& which, int& m_tile, int& n_tile) {
  const bool q = it == 0 || it >= 5;
  const int b = maps.id[blockIdx.x][it >= 5];
  which = q ? 0 : 2 - (it & 1);
  m_tile = b & 15;
  n_tile = (b >> 4) * 2 + ((0x19 >> it) & 1);
}

constexpr int G_NTILES = 6;
__device__ __forceinline__ void qkv_producer(const Maps& maps, uint32_t sbase, bool first) {
  const uint32_t bar = sbase + BAR_OFF;
  uint32_t stage = 0, phase = 0;
#pragma unroll 1
  for (int it = 0; it < (first ? 1 : G_NTILES); it++) {
    int which, m_tile, n_tile;
    qkv_tile(maps, it, which, m_tile, n_tile);
    const CUtensorMap* ma = &maps.a[which == 0 ? 0 : 1];
    const CUtensorMap* mb = &maps.b[which];
    const int nk = first ? G_STAGES : which == 0 ? 16 : 8;
#pragma unroll 1
    for (int kt = (it == 0 && !first) ? G_STAGES : 0; kt < nk; kt++) {
      if (!first) mbar_wait_sleep(bar + B_GEMPTY + 8 * stage, phase);
      const uint32_t fb = bar + B_GFULL + 8 * stage;
      const uint32_t sa = sbase + stage * G_STAGE_BYTES;
      mbar_expect_tx(fb, G_STAGE_BYTES);
      tma_load_2d(sa, ma, fb, kt * 64, m_tile * 128);
      tma_load_3d(sa + G_A_BYTES, mb, fb, 0, kt * 64, n_tile * 4);
      if (++stage == G_STAGES) { stage = 0; phase ^= 1; }
      {
        const int b = maps.id[blockIdx.x][1];
        if (it == 2 && kt == (b & 7))
          asm volatile("cp.async.bulk.prefetch.tensor.3d.L2.global.tile [%0, {%1, %2, %3}];" ::"l"(&maps.b[1 + (b >> 6)]),
                       "r"(0), "r"(((b >> 3) & 7) * 64), "r"((b & 7) * 8 + 4)
                       : "memory");
        if (it == 3 && kt == (b & 7))
          asm volatile("cp.async.bulk.prefetch.tensor.3d.L2.global.tile [%0, {%1, %2, %3}];" ::"l"(&maps.b[0]), "r"(0),
                       "r"((b & 15) * 64), "r"((b >> 4) * 8)
                       : "memory");
      }
    }
  }
}

__device__ __noinline__ void publisher(uint32_t bar, int lane, uint32_t nsrc) {
  uint32_t done = 0;
  CLK_DECL
#pragma unroll 1
  for (uint32_t spins = 0; done < nsrc && spins < (1u << 20); spins++) {
    CLK_SAMPLE
    uint32_t v = 0;
    if (lane < CNT_N)
      asm volatile("atom.acquire.cta.shared.exch.b32 %0, [%1], 0;" : "=r"(v) : "r"(bar + B_PEND + 4 * lane) : "memory");
    done += __shfl_sync(0xffffffffu, v, CNT_DONE);
    if (lane == CNT_DONE) v = 0;
    if (done == nsrc && lane < CNT_DONE) {
      uint32_t w;
      asm volatile("atom.acquire.cta.shared.exch.b32 %0, [%1], 0;" : "=r"(w) : "r"(bar + B_PEND + 4 * lane) : "memory");
      v += w;
    }
    if (v && lane == 0) { TD(0) }
    if (v) cnt_signal_release(lane, v);
    if (v && lane == 0) { TD(1) }
    if (!__any_sync(0xffffffffu, v != 0)) __nanosleep(200);
  }
  CLK_END
  __threadfence();
  __syncwarp();
}

__device__ __forceinline__ void gate_rows(const Maps& maps, uint32_t sbase, int w48, int w12, int lane) {
  const uint32_t buf = sbase + w12 * 16384, gb = sbase + BAR_OFF + 768 + w12 * 16;
  if (lane == 0) {
    mbar_init(gb, 1);
    mbar_init(gb + 8, 1);
    fence_barrier_init();
    for (int i = 0; i < 2; i++) {
      mbar_expect_tx(gb + 8 * i, 8192);
      bulk_load(buf + i * 8192, maps.x + (size_t)(w48 + 48 * i) * 4 * DM, 8192, gb + 8 * i);
    }
  }
  __syncwarp();
  uint4 wv[4];
#pragma unroll
  for (int i = 0; i < 4; i++) wv[i] = __ldg(reinterpret_cast<const uint4*>(maps.gate_w + (i * 32 + lane) * 8));
  int it = 0;
#pragma unroll 1
  for (int row = w48 * 4; row < S_LEN; row += 48 * 4, it++) {
    mbar_wait(gb + 8 * (it & 1), (it >> 1) & 1);
    uint4 xv[4][4];
#pragma unroll
    for (int r = 0; r < 4; r++)
#pragma unroll
      for (int i = 0; i < 4; i++) xv[r][i] = lds128(buf + (it & 1) * 8192 + r * 2048 + (i * 32 + lane) * 16);
    float d[2][4];
#pragma unroll
    for (int pr = 0; pr < 2; pr++) {
      d[pr][0] = d[pr][1] = d[pr][2] = d[pr][3] = 0.f;
      auto acc = [&](uint32_t a0, uint32_t a2, uint32_t b0, uint32_t b2, uint32_t w0, uint32_t w2) {
        asm volatile(
            "mma.sync.aligned.m16n8k16.row.col.f32.bf16.bf16.f32 {%0, %1, %2, %3}, {%4, %5, %6, %7}, {%8, %8}, "
            "{%0, %1, %2, %3};"
            : "+f"(d[pr][0]), "+f"(d[pr][1]), "+f"(d[pr][2]), "+f"(d[pr][3])
            : "r"(mul_bf2(a0, w0)), "r"(mul_bf2(b0, w0)), "r"(mul_bf2(a2, w2)), "r"(mul_bf2(b2, w2)), "r"(0x3f803f80u));
      };
#pragma unroll
      for (int i = 0; i < 4; i++) {
        acc(xv[2 * pr][i].x, xv[2 * pr][i].y, xv[2 * pr + 1][i].x, xv[2 * pr + 1][i].y, wv[i].x, wv[i].y);
        acc(xv[2 * pr][i].z, xv[2 * pr][i].w, xv[2 * pr + 1][i].z, xv[2 * pr + 1][i].w, wv[i].z, wv[i].w);
      }
    }
    float sum = (lane & 2) ? ((lane & 1) ? d[1][2] : d[1][0]) : ((lane & 1) ? d[0][2] : d[0][0]);
#pragma unroll
    for (int off = 16; off >= 4; off >>= 1) sum += __shfl_xor_sync(0xffffffffu, sum, off);
    if (lane < 4) g_gate[row + lane] = bf16_round(rcp(1.0f + __expf(-bf16_round(sum))));
    if (lane == 0 && row + 2 * 48 * 4 < S_LEN) {
      mbar_expect_tx(gb + 8 * (it & 1), 8192);
      bulk_load(buf + (it & 1) * 8192, maps.x + (size_t)(row + 2 * 48 * 4) * DM, 8192, gb + 8 * (it & 1));
    }
  }
}

constexpr float Q_SCALE = 0.08838834764831845f * 1.4426950408889634f;
__device__ __forceinline__ uint32_t qkv_consumer(const Maps& maps, uint32_t smem0, bool fused, float (&rest)[64]) {
  PHASE_PROLOGUE
  constexpr int NTILES = G_NTILES;
  float acc[128];
  uint32_t stage = 0, phase = 0;
  const uint32_t stg = sbase + G_STG_OFF + wg * 18432;
  const int st_row = warp * 16 + (lane & 7) + ((lane >> 3) & 1) * 8;
  const int st_cb = lane >> 4;
  uint32_t pend[64];
  const CUtensorMap* pend_map = nullptr;
  int pend_c0 = 0, pend_c1 = 0;
  uint32_t sn = 0;
  auto put_box = [&](uint32_t buf, const uint32_t* v) {
#pragma unroll
    for (int jp = 0; jp < 4; jp++) {
      const int chunk = jp * 2 + st_cb;
      const uint32_t addr = buf + st_row * 128 + ((chunk ^ (st_row & 7)) << 4);
      stmatrix_x4(addr, v[jp * 4], v[jp * 4 + 1], v[jp * 4 + 2], v[jp * 4 + 3]);
    }
  };
  GT(gti++)
#pragma unroll 1
  for (int it = 0; it <= NTILES; it++) {
    int which, m_tile, n_tile;
    qkv_tile(maps, it, which, m_tile, n_tile);
    const int nk = (which == 0 && it < NTILES) ? 16 : 8;
    uint32_t prev_stage = 0;
#pragma unroll 1
    for (int kt = 0; kt < nk; kt++) {
      if (it < NTILES) {
        mbar_wait((bar + B_GFULL) + 8 * stage, phase);
        GT(gti++)
        const uint64_t da0 = make_desc(sbase + stage * G_STAGE_BYTES + wg * 8192, 16, 1024, DESC_SW128);
        const uint64_t db0 = make_desc(sbase + stage * G_STAGE_BYTES + G_A_BYTES, 8192, 1024, DESC_SW128);
        wgmma_fence();
#pragma unroll
        for (int kk = 0; kk < 4; kk++) {
          wgmma_m64n256_ss_tb(acc, desc_add(da0, kk * 2), desc_add(db0, kk * 128), (kt | kk) != 0);
        }
        wgmma_commit();
      }
      const uint32_t when = it == 0 ? 0 : it == 5 ? 0x922 << wg : wg ? 0xAA : 0x55;
      if ((when >> kt) & 1) {
        const int c = __popc(when & ~(~0u << kt));
        st_wait(bar, wg, sn - 2);
        const uint32_t buf = stg + (c & 1) * 8192;
        switch (c) {
          case 0: put_box(buf, pend); break;
          case 1: put_box(buf, pend + 16); break;
          case 2: put_box(buf, pend + 32); break;
          default: put_box(buf, pend + 48); break;
        }
        st_post(bar, wg, wtid, sn, ST_BOX1, pend_map, buf, pend_c0 + c * 64, pend_c1, (c == 3 && it > 1) ? CNT_KV + (it > 3) : -1);
        sn++;
      }
      if (it < NTILES) {
        wgmma_wait<1>();
        mbar_arrive_if((bar + B_GEMPTY) + 8 * prev_stage, wtid == 32 && kt > 0);
        prev_stage = stage;
        if (++stage == G_STAGES) { stage = 0; phase ^= 1; }
      }
    }
    wgmma_wait<0>();
    fence_regs(acc);
    if (it == NTILES) break;
    GT(gti++)
    mbar_arrive_if((bar + B_GEMPTY) + 8 * prev_stage, wtid == 32);
    if (it == NTILES - 1 && fused) break;
    if (which == 0) {
#pragma unroll
      for (int j = 0; j < 128; j++) acc[j] *= Q_SCALE;
    }
#pragma unroll
    for (int j = 0; j < 64; j++) pend[j] = pack_bf16(acc[2 * j], acc[2 * j + 1]);
    pend_map = &maps.c[which];
    pend_c0 = n_tile * 256;
    pend_c1 = m_tile * 128 + wg * 64;
  }
  mbar_wait(bar + B_GEMPTY, 1);
#pragma unroll
  for (int j = 0; j < 32; j++) pend[j] = pack_bf16(acc[2 * j] * Q_SCALE, acc[2 * j + 1] * Q_SCALE);
  put_box(sbase + wg * 8192, pend);
  put_box(sbase + 16384 + wg * 8192, pend + 16);
  fence_proxy_async();
#pragma unroll
  for (int j = 0; j < 64; j++) rest[j] = acc[64 + j];
  GT(gti++)
  return sn;
}

constexpr int A_TILE = 128 * 128 * 2;
constexpr int A_Q_OFF = 0;
constexpr int A_K_OFF = 2 * A_TILE;
constexpr int A_V_OFF = 4 * A_TILE;
constexpr int A_O_OFF = 6 * A_TILE;
constexpr int A_ITEMS = NH * (S_LEN / 128);

constexpr uint32_t A_ORDER = 0x3120, A_STEPS = 34;
__device__ __forceinline__ int item_m(uint32_t it) { return it & 15; }
__device__ __forceinline__ int item_h(uint32_t it) { return it >> 4; }

constexpr int C_H0 = 16, C_U = C_H0 + 4096 + 112, C_SLOT = C_U + 4096;
constexpr int C_H1 = 2 * C_SLOT + 80;
constexpr int C_X_OFF = C_H1 + 4096 + 48;

__device__ __forceinline__ uint32_t item_of(const Maps& maps, uint32_t r) {
  const uint32_t b = maps.id[blockIdx.x & 127][1];
  return (b >> 4) * 64 + ((A_ORDER >> (4 * r)) & 3) * 16 + ((b ^ ((r & 1) * 15)) & 15);
}

constexpr uint32_t C_SIDE = 48;
__device__ __forceinline__ uint32_t conv_first(const Maps& maps) {
  const uint32_t b = maps.id[blockIdx.x & 127][1];
  return (b >> 4) * 128 + (b & 15);
}

__device__ __forceinline__ void conv_consumer(const Maps& maps, uint32_t smem0, uint32_t first, uint32_t step,
                                              uint32_t end) {
  PHASE_PROLOGUE
  const uint32_t full = bar + B_CFULL + wg * 16;
  const uint32_t ca = sbase + (wg ? A_V_OFF + A_TILE : A_Q_OFF);
  const int w4 = __shfl_sync(0xffffffffu, warp, 0);
  auto fetch = [&](uint32_t c, uint32_t slot) {
    if (w4 == 2 && c < end) {
      if (elect_one()) {
        const uint32_t sb = ca + slot * C_SLOT, fb = full + 8 * slot;
        const uint64_t pol = policy_evict_first();
        mbar_expect_tx(fb, 2 * 4096);
        bulk_load_hint(sb + C_H0, maps.ssm_k + (size_t)c * S_LEN, 4096, fb, pol);
        bulk_load_hint(sb + C_U, g_kvT + (size_t)c * S_LEN, 4096, fb, pol);
      }
    }
  };
  auto shift_h = [&](uint32_t so) {
    const uint32_t a = ca + so + C_H0 + wtid * 16;
#pragma unroll
    for (int i = 0; i < 2; i++) {
      uint32_t p;
      const uint4 v = lds128(a + i * 2048);
      asm volatile("ld.shared.u32 %0, [%1];" : "=r"(p) : "r"(a + i * 2048 - 4));
      sts128(ca + C_H1 + wtid * 16 + i * 2048, make_uint4(__byte_perm(p, v.x, 0x5432), __byte_perm(v.x, v.y, 0x5432),
                                                      __byte_perm(v.y, v.z, 0x5432), __byte_perm(v.z, v.w, 0x5432)));
    }
  };
  if (wtid == 96 && wg) { TD(15) }
  fetch(first, 0);
  if (wtid < 17)
    sts128(ca + (wtid >> 3) * C_SLOT + (wtid & 7 ? 4096 + (wtid & 7) * 16 : (wtid & 16) * 4), make_uint4(0, 0, 0, 0));
  fence_proxy_async();
  const uint32_t ha = ca + ((lane & 4) ? C_H1 : C_H0) + 4 * ((lane & 3) - (lane >> 3)) + w4 * 256;
  const uint32_t ua = ca + C_U + w4 * 256 + (lane >> 4) * 1024 + (lane & 15) * 16;
  const uint32_t xa = ca + C_X_OFF + lane * 8, xw = xa + w4 * 3072;
  uint32_t xg[3];
#pragma unroll
  for (int k = 0; k < 3; k++) {
    const int w = (w4 + k + 1) & 3;
    xg[k] = xa + (w * 12 + w4 - w - (w < w4 ? 1 : 0)) * 256;
  }
  const bool pp = step != 16;
  uint32_t h[2][16];
  const uint32_t hs = (lane & 4) ? 0 : C_SLOT;
  auto load_h = [&](uint32_t so, int a) {
#pragma unroll
    for (int i = 0; i < 16; i++)
      asm volatile("ld.shared.u32 %0, [%1];"
                   : "=r"(h[a & 1][i])
                   : "r"(ha + so + 1024 * a + 32 * (i >> 2) + (i & 1) * 128 + (~i & 2) * 8));
  };
  mbar_wait(full, 0);
  named_bar_sync(1 + wg, 128);
  shift_h(0);
  named_bar_sync(1 + wg, 128);
  fetch(first + step, 1);
  load_h(0, 0);
  load_h(0, 1);
  mbar_wait(bar + B_OFREE, 0);
  mbar_wait(bar + B_OFREE + 8, 0);
  uint32_t n = 0, ch = first;
  for (; ch < end; n++, ch += step) {
    CT(0)
    const uint32_t so = (n & 1) * C_SLOT, ho = (n & 1) * hs;
    uint32_t db = (uint32_t)make_desc(ca + so + C_U - 16, 16, 0, 0);
    asm volatile("" : "+r"(db));
    uint32_t dsk = __ldg(reinterpret_cast<const unsigned short*>(maps.ssm_D) + (ch | (lane & rt_zero)));
    float d[4][32], own[16];
    auto mma = [&](int a) {
      wgmma_fence();
#pragma unroll
      for (int c = a; c < 4; c++)
#pragma unroll
        for (int b = 0; b < 4; b++)
          wgmma_m64n64_rs(d[c], &h[a & 1][4 * b], (8ull << 32) | (db + 64 * (c - a) - 2 * b), (a | b) != 0);
      wgmma_commit();
    };
    auto put = [&](int c) {
      fence_regs(d[c]);
#pragma unroll
      for (int e = 0; e < 2; e++) {
        if (c == 0) asm volatile("mov.b32 %0, %1;" : "=f"(own[e]) : "f"(d[c][e]));
        else own[4 * c + e] += d[c][e];
        own[4 * c + 2 + e] = d[c][4 + e] + d[c][2 + e];
        if (c < 3) asm volatile("mov.b32 %0, %1;" : "=f"(own[4 * c + 4 + e]) : "f"(d[c][30 + e]));
      }
#pragma unroll
      for (int j = 1; j < 4; j++)
        asm volatile("{\n.reg .pred p;\nsetp.lt.s32 p, %3, 4;\n@p st.shared.v2.u32 [%0], {%1, %2};\n}\n" ::"r"(
                         xw + (3 * c + j - 1) * 256),
                     "r"(pack_bf16(d[c][8 * j] + d[c][8 * j - 2], d[c][8 * j + 1] + d[c][8 * j - 1])),
                     "r"(pack_bf16(d[c][8 * j + 4] + d[c][8 * j + 2], d[c][8 * j + 5] + d[c][8 * j + 3])),
                     "r"(c < 3 ? 0 : w4 + j)
                     : "memory");
    };
    named_bar_sync(pp ? 4 + wg : 1 + wg, pp ? 256 : 128);
    CT(1)
    mma(0);
    mma(1);
    wgmma_wait<1>();
    load_h(ho, 2);
    put(0);
    mma(2);
    CT(2)
    wgmma_wait<1>();
    load_h(ho, 3);
    put(1);
    mma(3);
    asm volatile("{\n.reg .pred p;\nsetp.ne.u32 p, %1, 0;\n@p bar.arrive %0, 256;\n}\n" ::"r"(5 - wg), "r"((uint32_t)pp) : "memory");
    CT(3)
    uint32_t sk[8];
    asm volatile("ldmatrix.sync.aligned.m8n8.x4.trans.shared.b16 {%0, %1, %2, %3}, [%4];"
                 : "=r"(sk[0]), "=r"(sk[1]), "=r"(sk[2]), "=r"(sk[3])
                 : "r"(ua + so));
    asm volatile("ldmatrix.sync.aligned.m8n8.x4.trans.shared.b16 {%0, %1, %2, %3}, [%4];"
                 : "=r"(sk[4]), "=r"(sk[5]), "=r"(sk[6]), "=r"(sk[7])
                 : "r"(ua + so + 2048));
    mbar_wait(full + 8 * (~n & 1), (((n + 1) >> 1) & 1) ^ (ch + step < end ? 0 : 1));
    named_bar_sync(1 + wg, 128);
    shift_h(C_SLOT - so);
    wgmma_wait<1>();
    put(2);
    uint32_t dep = 0;
#pragma unroll
    for (int i = 0; i < 8; i++) dep |= sk[i] = mul_bf2(sk[i], dsk | (dsk << 16));
    CT(4)
    wgmma_wait<0>();
    put(3);
    named_bar_sync((1 + wg) | (dep & rt_zero), 128);
    CT(5)
    fetch(ch + 2 * step, n & 1);
    if (wtid == 96 && n) note(bar, CNT_Y2 + (((ch - step) & 127) >= 112));
    uint2 q[12];
#pragma unroll
    for (int i = 0; i < 12; i++) {
      if (i >= 3) {
        asm volatile("ld.shared.v2.u32 {%0, %1}, [%2];" : "=r"(q[i].x), "=r"(q[i].y) : "r"(xg[i % 3] + (i / 3) * 768));
      } else {
        q[i] = make_uint2(0, 0);
        asm volatile("{\n.reg .pred p;\nsetp.gt.s32 p, %3, 2;\n@p ld.shared.v2.u32 {%0, %1}, [%2];\n}\n"
                     : "+r"(q[i].x), "+r"(q[i].y)
                     : "r"(xg[i]), "r"(w4 + i));
      }
    }
    load_h(hs - ho, 0);
    load_h(hs - ho, 1);
    CT(6)
    uint32_t* dst = reinterpret_cast<uint32_t*>(g_y2T + (size_t)ch * S_LEN) + 64 * w4 + (lane ^ 28);
#pragma unroll
    for (int f = 0; f < 4; f++) {
#pragma unroll
      for (int k = 0; k < 3; k++) {
        own[4 * f] += bf_lo(q[3 * f + k].x);
        own[4 * f + 1] += bf_hi(q[3 * f + k].x);
        own[4 * f + 2] += bf_lo(q[3 * f + k].y);
        own[4 * f + 3] += bf_hi(q[3 * f + k].y);
      }
#pragma unroll
      for (int i = 0; i < 2; i++) {
        dst[256 * f + 32 * i] = add_bf2(pack_bf16(own[4 * f + 2 * i], own[4 * f + 2 * i + 1]), sk[2 * f + i]);
      }
    }
    CT(7)
  }
  named_bar_sync(1 + wg, 128);
  if (wtid == 96 && wg) { TD(8) }
  if (wtid == 96) cnt_signal_release(CNT_Y2 + (((ch - step) & 127) >= 112), 1);
  if (wtid == 64) note(bar, CNT_DONE);
  if (wtid == 96 && wg) { TD(9) }
}

__device__ __forceinline__ void attn_producer(const Maps& maps, uint32_t sbase, bool after_qkv, bool to_out,
                                              bool dry) {
  const uint32_t bar = sbase + BAR_OFF;
  const uint32_t q_full = bar + B_QFULL, q_empty = bar + B_QEMPTY;
  const uint32_t k_full = bar + B_KFULL, k_empty = bar + B_KEMPTY, v_full = bar + B_VFULL, v_empty = bar + B_VEMPTY;
  int ndrained = after_qkv ? 0 : G_STAGES;
  auto wait = [&](uint32_t b, uint32_t par) {
    if (!dry) mbar_wait_sleep(b, par);
  };
  auto drained = [&](int upto) {
#pragma unroll 1
    for (; ndrained <= upto; ndrained++) wait(bar + B_GEMPTY + 8 * ndrained, 1);
  };
  uint32_t st = 0, ph = 1, vs = 0, vp = 1;
  int pend_j = -1, pend_h = 0;
  int round = -1, m = -1, h = 0;
  PT_DECL
  bool last = false;
#pragma unroll 1
  for (;; round++) {
    uint32_t nitem = 0;
    const int tpost = m >= 3 ? m - 1 : m;
#pragma unroll 1
    for (int t = m < 0 ? -1 : 0; t <= m; t++) {
      const int j = (t < m && (round & 1)) ? m - 1 - t : t;
      if (t >= 0) {
        drained(1 + st);
        wait(k_empty + 8 * st, ph);
        if (!dry) {
          PT
          mbar_expect_tx(k_full + 8 * st, A_TILE);
          tma_load_3d(sbase + A_K_OFF + st * A_TILE, &maps.k, k_full + 8 * st, 0, j * 128, h * 2);
        }
        if (++st == 2) { st = 0; ph ^= 1; }
      }
      if (pend_j >= 0) {
        drained(3);
        wait(v_empty + 8 * vs, vp);
        if (!dry) {
          mbar_expect_tx(v_full + 8 * vs, A_TILE);
          tma_load_3d(sbase + A_V_OFF + vs * A_TILE, &maps.v, v_full + 8 * vs, 0, pend_j * 128, pend_h * 2);
        }
        if (++vs == 2) { vs = 0; vp ^= 1; }
      }
      pend_j = j;
      pend_h = h;
      if (t == tpost && !last) {
        nitem = dry ? 1 : item_of(maps, round + 1);
        if (round == (dry ? 0 : 3) || blockIdx.x >= 128) {
          nitem = A_ITEMS;
          cnt_wait(CNT_PREP, dry ? 0 : 260);
          if (to_out) {
            cnt_wait(CNT_CTX, dry ? 0 : A_ITEMS);
            asm volatile("cp.async.bulk.prefetch.L2.global [%0], 4096;" ::"l"(maps.ssm_k + (size_t)conv_first(maps) * S_LEN));
            if (!dry)
              asm volatile("cp.async.bulk.prefetch.L2.global [%0], 4096;" ::"l"(g_kvT + (size_t)conv_first(maps) * S_LEN));
          }
        }
        const uint32_t qs = (round + 1) & 1;
        wait(q_empty + 8 * qs, (((round + 1) >> 1) & 1) ^ 1);
        if (round == 1 && after_qkv) wait(bar + B_QDONE, 0);
        if (round <= 0 && after_qkv) {
          if (!dry) { TD(2) }
          cnt_wait(CNT_KV + round + 1, dry ? 0 : 512);
          if (!dry) { TD(3) }
        }
        if (nitem >= A_ITEMS || (round < 0 && after_qkv && !dry)) {
          if (!dry) mbar_arrive(q_full + 8 * qs);
        } else {
          drained(qs);
          if (!dry) {
            mbar_expect_tx(q_full + 8 * qs, A_TILE);
            tma_load_3d_hint(sbase + A_Q_OFF + qs * A_TILE, &maps.q, q_full + 8 * qs, 0, item_m(nitem) * 128,
                             item_h(nitem) * 2, policy_evict_first());
          }
        }
      }
    }
    if (last) break;
    last = nitem >= A_ITEMS;
    m = last ? -1 : item_m(nitem);
    h = item_h(nitem);
  }
}

__device__ __forceinline__ uint32_t attn_consumer(const Maps& maps, uint32_t smem0, uint32_t sn,
                                                  float (&rest)[64], bool after_qkv) {
  PHASE_PROLOGUE
  const uint32_t q_full = bar + B_QFULL, q_empty = bar + B_QEMPTY;
  const uint32_t k_full = bar + B_KFULL, k_empty = bar + B_KEMPTY, v_full = bar + B_VFULL;
  float o[64], s[64];
  uint32_t p[32];
  float e[32];
  uint32_t dep = 0;
  constexpr int MIDJ = 5;
  float l0 = 0.f, l1 = 0.f, b0 = 0.f, b1 = 0.f;
  const int sched_own = 4 + wg, sched_other = 5 - wg;
  if (wg == 1) named_bar_arrive(4, 256);

  const uint32_t qd0 = (uint32_t)make_desc(sbase + A_Q_OFF + wg * 8192, 16, 0, 0);
  const uint32_t kd0 = (uint32_t)make_desc(sbase + A_K_OFF, 16, 0, 0);
  const uint32_t vd0 = (uint32_t)make_desc(sbase + A_V_OFF, 16384, 0, 0);
  constexpr uint64_t DHI = DESC_SW128 | ((uint64_t)(1024 >> 4) << 32);
  constexpr uint32_t DST = A_TILE >> 4;
  auto issue_qk = [&](uint32_t qd, uint32_t kd) {
#pragma unroll
    for (int kk = 0; kk < 8; kk++) {
      const uint32_t off = ((kk >> 2) * 16384 + (kk & 3) * 32) >> 4;
      wgmma_m64n128_ss(s, DHI | (qd + off), DHI | (kd + off), kk != 0);
    }
    wgmma_commit();
  };
  auto issue_pv = [&](uint32_t vd, bool accumulate, int nk) {
#pragma unroll
    for (int kk = 0; kk < 8; kk++) {
      if (kk < nk)
        wgmma_m64n128_rs_tb(o, p[4 * kk], p[4 * kk + 1], p[4 * kk + 2], p[4 * kk + 3], DHI | (vd + kk * 128),
                            accumulate || (kk != 0));
    }
    wgmma_commit();
  };
  auto exp_lo = [&](float& a0, float& a1) {
#pragma unroll
    for (int j = 0; j < 8; j++) {
      e[4 * j] = ex2(s[4 * j]);
      e[4 * j + 1] = ex2(s[4 * j + 1]);
      e[4 * j + 2] = ex2(s[4 * j + 2]);
      e[4 * j + 3] = ex2(s[4 * j + 3]);
      a0 += e[4 * j];
      a0 += e[4 * j + 1];
      a1 += e[4 * j + 2];
      a1 += e[4 * j + 3];
      if (j == MIDJ) dep = (__float_as_uint(a0) | __float_as_uint(a1)) & rt_zero;
    }
  };
  auto pack_lo = [&]() {
#pragma unroll
    for (int j = 0; j < 16; j++) p[j] = pack_bf16(e[2 * j], e[2 * j + 1]);
  };
  auto finish_p = [&](float& a0, float& a1) {
    pack_lo();
#pragma unroll
    for (int j = 8; j < 16; j++) {
      const float e0 = ex2(s[4 * j]), e1 = ex2(s[4 * j + 1]), e2 = ex2(s[4 * j + 2]), e3 = ex2(s[4 * j + 3]);
      a0 += e0;
      a0 += e1;
      a1 += e2;
      a1 += e3;
      p[2 * j] = pack_bf16(e0, e1);
      p[2 * j + 1] = pack_bf16(e2, e3);
      if (j == 8 + MIDJ) dep = __float_as_uint(a0) & rt_zero;
    }
  };
  auto quad_sum = [&](float t) {
    t += __shfl_xor_sync(0xffffffffu, t, 1);
    return t + __shfl_xor_sync(0xffffffffu, t, 2);
  };
  auto write_o = [&](float i0, float i1) {
    st_wait(bar, wg, sn - 1);
    const int st_row = warp * 16 + (lane & 7) + ((lane >> 3) & 1) * 8;
    const uint32_t so = sbase + A_O_OFF + wg * 16384 + st_row * 128;
#pragma unroll
    for (int j = 0; j < 16; j += 2)
      stmatrix_x4(so + (j >> 3) * 8192 + ((((j & 7) + (lane >> 4)) ^ (lane & 7)) << 4),
                  pack_bf16(o[4 * j] * i0, o[4 * j + 1] * i0), pack_bf16(o[4 * j + 2] * i1, o[4 * j + 3] * i1),
                  pack_bf16(o[4 * j + 4] * i0, o[4 * j + 5] * i0), pack_bf16(o[4 * j + 6] * i1, o[4 * j + 7] * i1));
  };
  auto store_o = [&](uint32_t r, int kind) {
    const uint32_t it = item_of(maps, r);
    st_post(bar, wg, wtid, sn, kind, (INPLACE & 1) || kind != ST_BOX2Q ? &maps.o : &maps.c[0], sbase + A_O_OFF + wg * 16384, item_h(it) * 128,
            item_m(it) * 128 + wg * 64, CNT_CTX + (r >> 1));
    sn++;
  };
  auto mask_half = [&](float* sh) {
    const int u = warp * 16 + (lane >> 2) - (lane & 3) * 2;
#pragma unroll
    for (int j = 0; j < 8; j++) {
      if (8 * j > u) sh[4 * j] = -INFINITY;
      if (8 * j + 1 > u) sh[4 * j + 1] = -INFINITY;
      if (8 * j - 8 > u) sh[4 * j + 2] = -INFINITY;
      if (8 * j - 7 > u) sh[4 * j + 3] = -INFINITY;
    }
  };
  ST(0)
  mbar_wait(q_full, 0);
  if (blockIdx.x >= 128) {
    mbar_arrive_if(bar + B_OFREE + 8 * wg, wtid == 0);
    return sn;
  }
  mbar_wait(k_full, 0);
  named_bar_sync(sched_own, 256);
  wgmma_fence();
  issue_qk(qd0, kd0);
  named_bar_arrive(sched_other, 256);
  fence_regs(rest);
#pragma unroll
  for (int i = 0; i < 64; i++) o[i] = rest[i] * Q_SCALE;
  fence_regs(o);
  wgmma_wait<0>();
  fence_regs(s);
  mbar_arrive_if(k_empty, wtid == 32);
  uint32_t g = 0;
  uint32_t rnd = 0;
  int rem = item_m(item_of(maps, 0));
  uint32_t first = 1;
  uint32_t fl = 0;
#define redo (fl & 1)
#define shifted (fl & 2)
  float d0 = 0.f, d1 = 0.f;
  float pi0 = 1.f, pi1 = 1.f;
  ST(1)
  for (;;) {
    if (shifted) {
#pragma unroll
      for (int j = 0; j < 16; j++) {
        s[4 * j] -= d0;
        s[4 * j + 1] -= d0;
        s[4 * j + 2] -= d1;
        s[4 * j + 3] -= d1;
      }
    }
    if (rem == 0 && !redo) {
      mbar_arrive_if(q_empty + 8 * (rnd & 1), wtid == 96);
      rnd++;
      if (wg == 0) mask_half(s);
      else mask_half(s + 32);
    }
    for (;;) {
      const bool kill = rem == 0 && wg == 0;
      const uint32_t kd = kd0 + ((g + 1) & 1) * DST, vd = vd0 + (g & 1) * DST;
      float a0 = 0.f, a1 = 0.f;
      exp_lo(a0, a1);
      fence_regs(e);
      const uint32_t kb = k_full + 8 * ((g + 1) & 1);
      const uint32_t kpar = ((((g + 1) >> 1) & 1) ^ (g == A_STEPS - 1 ? 1u : 0u)) | dep;
      if (!mbar_try(kb, kpar)) mbar_wait(kb, kpar | ((__float_as_uint(a0) | __float_as_uint(a1)) & rt_zero));
      wgmma_wait<0>();
      fence_regs(o);
      if (kill) {
        mbar_arrive_if(kb + (B_VEMPTY - B_KFULL), wtid == 64 && !redo && g > 0);
        fence_regs(e);
        pack_lo();
#pragma unroll
        for (int j = 16; j < 32; j++) asm volatile("mov.u32 %0, 0;" : "=r"(p[j]));
        goto check;
      }
#pragma unroll
      for (int i = 32; i < 64; i++) asm volatile("" : "+f"(s[i])::"memory");
      mbar_arrive_if(kb + (B_VEMPTY - B_KFULL), wtid == 64 && !redo && g > 0);
      finish_p(a0, a1);
      if (__any_sync(0xffffffffu, !(mbar_try(v_full + 8 * (g & 1), ((g >> 1) & 1) | dep) &
                                    mbar_try(q_full + 8 * (rnd & 1), ((rnd >> 1) & 1) | dep)) ||
                                      !(a0 + a1 < 1.0995116e12f) || !(fminf(a0, a1) > (first ? 9.094947e-13f : -1.f)))) {
      check:
        bool bad = !(a0 + a1 < 1.0995116e12f);
        if (first) bad |= !(fminf(quad_sum(a0), quad_sum(a1)) > 9.094947e-13f);
        if (!redo && __any_sync(0xffffffffu, bad)) {
          d0 = d1 = first ? -INFINITY : 0.f;
#pragma unroll
          for (int j = 0; j < 16; j++) {
            if (j < 8 || !kill) {
              d0 = fmaxf(d0, fmaxf(s[4 * j], s[4 * j + 1]));
              d1 = fmaxf(d1, fmaxf(s[4 * j + 2], s[4 * j + 3]));
            }
          }
#pragma unroll
          for (int x = 1; x <= 2; x++) {
            d0 = fmaxf(d0, __shfl_xor_sync(0xffffffffu, d0, x));
            d1 = fmaxf(d1, __shfl_xor_sync(0xffffffffu, d1, x));
          }
          b0 += d0;
          b1 += d1;
          if (!first) {
            const float al0 = ex2(-d0), al1 = ex2(-d1);
            l0 *= al0;
            l1 *= al1;
#pragma unroll
            for (int j = 0; j < 16; j++) {
              o[4 * j] *= al0;
              o[4 * j + 1] *= al0;
              o[4 * j + 2] *= al1;
              o[4 * j + 3] *= al1;
            }
          }
          fl = 3;
          break;
        }
        mbar_wait(v_full + 8 * (g & 1), (g >> 1) & 1);
        mbar_wait(q_full + 8 * (rnd & 1), (rnd >> 1) & 1);
      }
      named_bar_sync(sched_own, 256);
      if (g == A_STEPS - 1) {
        if (first) write_o(pi0, pi1);
        fence_regs(o);
        wgmma_fence();
        issue_pv(vd, !first, 8);
        named_bar_arrive(sched_other, 256);
        if (first) store_o(rnd - 2, ST_BOX2);
        pi0 = rcp(quad_sum(l0 + a0));
        pi1 = rcp(quad_sum(l1 + a1));
        goto done;
      }
      wgmma_fence();
      issue_qk(qd0 + (rnd & 1) * DST, kd);
      if (first) write_o(pi0, pi1);
      fence_regs(o);
      if (kill) {
        wgmma_fence();
        issue_pv(vd, !first, 4);
      } else {
        wgmma_fence();
        issue_pv(vd, !first, 8);
      }
      named_bar_arrive(sched_other, 256);
      fl &= 2;
      l0 += a0;
      l1 += a1;
      if (rem == 0 || first) {
        if (first && (g > 0 || after_qkv)) store_o(g ? rnd - (rem == 0 ? 2 : 1) : 2, g ? ST_BOX2 : ST_BOX2Q);
        first = rem == 0;
        if (first) {
          pi0 = rcp(quad_sum(l0));
          pi1 = rcp(quad_sum(l1));
          l0 = l1 = b0 = b1 = 0.f;
          fl = 0;
          rem = item_m(item_of(maps, rnd)) + 1;
        }
      }
      rem--;
      g++;
      wgmma_wait<1>();
      fence_regs(s);
      mbar_arrive_if(kb + (B_KEMPTY - B_KFULL), wtid == 32);
      ST(g + 1)
      if (rem == 0 || shifted) {
        d0 = b0;
        d1 = b1;
        break;
      }
    }
  }
done:
#undef redo
#undef shifted
  wgmma_wait<0>();
  fence_regs(o);
  write_o(pi0, pi1);
  store_o(3, ST_BOX2L);
  ST(35)
  return sn;
}

constexpr int O_STAGES = 5;
constexpr int O_STAGE_BYTES = 32768;
constexpr int O_Y_OFF = 5 * 32768;
constexpr int O_X_OFF = 6 * 32768 + 2048;
constexpr int O_NK = HDIM / 64;

__device__ __forceinline__ uint32_t out_stage(uint32_t st) { return ((0x43120u >> (4 * st)) & 7) * O_STAGE_BYTES; }

__device__ __forceinline__ void out_producer(const Maps& maps, uint32_t sbase, bool after_attn, bool dry) {
  const uint32_t bar = sbase + BAR_OFF;
  const uint32_t rank = blockIdx.x & 1;
  const int m_tile = maps.id[blockIdx.x][2] & 15, n_tile = maps.id[blockIdx.x][2] >> 4;
  uint32_t stage = 0, phase = 0;
  const int kx = dry ? 0 : 17 + (blockIdx.x >> 1) % 12;
#pragma unroll 1
  for (int ki = 0; ki < (dry ? 1 : O_NK); ki++) {
    const int kt = (ki & 14) * 4 + ((A_ORDER >> ((ki >> 4) * 4)) & 3) * 2 + (ki & 1);
    const uint32_t fb = bar + B_OFULL + 8 * stage, eb = bar + B_OEMPTY + 8 * stage;
    const uint32_t sa = sbase + out_stage(stage);
    if (ki < O_STAGES) {
      constexpr uint32_t LASTB = B_KEMPTY | ((B_QEMPTY + 8) << 8) | ((B_KEMPTY + 8) << 16) | (B_VEMPTY << 24);
      if (ki > 0 && after_attn) mbar_wait_sleep(bar + ((LASTB >> (8 * ki - 8)) & 255), ki == 2);
      mbar_arrive_cluster_if(eb, 0, !dry);
      mbar_arrive_cluster_if(eb, 1, !dry);
    }
    if (ki == (dry ? 0 : 16)) cnt_wait(CNT_CTX + 1, dry ? 0 : A_ITEMS);
    if (ki == kx) {
      if (after_attn && !dry) {
        mbar_wait_sleep(bar + B_OFREE, 0);
        mbar_wait_sleep(bar + B_OFREE + 8, 0);
      }
      if (!dry) {
        mbar_expect_tx(bar + B_OY, 32768);
        tma_load_4d(sbase + O_X_OFF, &maps.ox, bar + B_OY, n_tile * 128, m_tile);
        tma_load_4d(sbase + O_X_OFF + 16384, &maps.ox, bar + B_OY, n_tile * 128 + 64, m_tile);
      }
    }
    if (!dry) {
      mbar_wait_sleep(eb, phase);
      mbar_expect_tx(fb, O_STAGE_BYTES);
      tma_load_2d_mc(sa + 16384 + rank * 8192, &maps.ob, fb, n_tile * 128 + rank * 64, kt * 64, (uint16_t)3);
      tma_load_4d(sa, &maps.oa, fb, kt * 64, m_tile);
    }
    if (++stage == O_STAGES) { stage = 0; phase ^= 1; }
  }
  if (!dry) mbar_wait_sleep(bar + B_OY2, 0);
}

__device__ __forceinline__ void out_side(const Maps& maps, uint32_t smem0, const float (&gv)[4]) {
  PHASE_PROLOGUE
  const int m_tile = maps.id[blockIdx.x][2] & 15, n_tile = maps.id[blockIdx.x][2] >> 4;
  const int w4 = __shfl_sync(0xffffffffu, warp, 0);
  if (w4 == 0) {
    if (elect_one()) {
      mbar_expect_tx(bar + B_OY, 32768 - 4096);
      TD(10)
      GS(0)
      cnt_wait(CNT_Y2, DM - 128);
      GS(1)
      TD(7)
      for (const uint32_t t = clock(); (uint32_t)clock() - t < (blockIdx.x & 14) * 200;) __nanosleep(32);
      TD(11)
      GS(2)
      fence_proxy_async();
      tma_load_2d(sbase + O_Y_OFF, &maps.y, bar + B_OY, m_tile * 128, n_tile * 128);
      tma_load_2d(sbase + O_Y_OFF + 16384, &maps.y, bar + B_OY, m_tile * 128 + 64, n_tile * 128);
    }
  }
  mbar_wait_sleep(bar + B_OY, 0);
  const int st_row = warp * 16 + (lane & 7) + ((lane >> 3) & 1) * 8;
  const int mrow = (lane & 7) + ((lane >> 4) & 1) * 8;
  const int mchunk = warp * 2 + ((lane >> 3) & 1);
  const uint32_t xrow = sbase + O_X_OFF + st_row * 128;
  const uint32_t yrow = sbase + O_Y_OFF + mrow * 128 + ((mchunk ^ (lane & 7)) << 4);
  uint32_t y[7][4], x[7][4], om[4];
#pragma unroll
  for (int i = 0; i < 4; i++) om[i] = pack_bf16(1.0f - gv[i], 1.0f - gv[i]);
  auto xa = [&](int h, int i) { return xrow + h * 8192 + (i >> 2) * 16384 + ((((i & 3) * 2 + (lane >> 4)) ^ (lane & 7)) << 4); };
  auto load = [&](int r, int h, int i) {
    ldsm4t(y[r], yrow + h * 16384 + i * 2048);
    asm volatile("ldmatrix.sync.aligned.m8n8.x4.shared.b16 {%0, %1, %2, %3}, [%4];"
                 : "=r"(x[r][0]), "=r"(x[r][1]), "=r"(x[r][2]), "=r"(x[r][3])
                 : "r"(xa(h, i)));
  };
  auto store = [&](int r, int h, int i, uint32_t om0, uint32_t om1) {
    stmatrix_x4(xa(h, i), mul_bf2(om0, mul_bf2(x[r][0], y[r][0])), mul_bf2(om1, mul_bf2(x[r][1], y[r][1])),
                mul_bf2(om0, mul_bf2(x[r][2], y[r][2])), mul_bf2(om1, mul_bf2(x[r][3], y[r][3])));
  };
  if (wtid == 0) { TD(12) GS(3) }
#pragma unroll 1
  for (int h = 0; h < 2; h++) {
#pragma unroll
    for (int i = 0; i < 7; i++) load(i, h, i);
#pragma unroll
    for (int i = 0; i < 7; i++) store(i, h, i, h ? om[2] : om[0], h ? om[3] : om[1]);
  }
  if (wtid == 0) { TD(4) GS(4) }
  if (w4 == 0) {
    if (elect_one()) {
      mbar_expect_tx(bar + B_OY2, 4096);
      cnt_wait(CNT_Y2 + 1, 128);
      GS(5)
      for (int i = 0; i < 2; i++)
        tma_load_2d(sbase + O_Y_OFF + i * 16384 + 112 * 128, &maps.y2, bar + B_OY2, m_tile * 128 + i * 64,
                    n_tile * 128 + 112);
    }
  }
  mbar_wait_sleep(bar + B_OY2, 0);
#pragma unroll
  for (int h = 0; h < 2; h++) load(h, h, 7);
#pragma unroll
  for (int h = 0; h < 2; h++) store(h, h, 7, om[2 * h], om[2 * h + 1]);
  __syncwarp();
  mbar_arrive_if(bar + B_OY + 8, lane == 0);
  if (wtid == 0) { TD(13) GS(6) }
#pragma unroll
  for (int i = 0; i < 4; i++) {
    const int h = i >> 1, c = i & 1;
    named_bar_sync(6 + i, 256);
    if (elect_one()) {
      fence_proxy_async();
      tma_store_4d(&maps.oc, sbase + O_X_OFF + c * 16384 + h * 8192 + w4 * 2048, n_tile * 128 + c * 64, 2 * w4,
                   2 * m_tile + h);
      tma_store_commit();
    }
  }
}

__device__ __forceinline__ void out_gemm(const Maps& maps, uint32_t smem0) {
  PHASE_PROLOGUE
  const int m_tile = maps.id[blockIdx.x][2] & 15;
  float acc[2][64];
  undef_regs(acc[0]);
  undef_regs(acc[1]);
  uint32_t stage = 0, phase = 0, prev_stage = 0;
  GT(gti++)
  const float* gp = g_gate + m_tile * 128 + warp * 2 + (lane >> 2) * 8;
  const float gv[4] = {__ldcg(gp), __ldcg(gp + 1), __ldcg(gp + 64), __ldcg(gp + 65)};
  if (wg == 1) {
    out_side(maps, smem0, gv);
    return;
  }
  constexpr uint64_t DHI = DESC_SW128 | ((uint64_t)(1024 >> 4) << 32);
#pragma unroll 1
  for (int kt = 0; kt < O_NK - 1; kt++) {
    uint32_t da = (uint32_t)make_desc(sbase + out_stage(stage), 16, 0, 0);
    uint32_t db = (uint32_t)make_desc(sbase + out_stage(stage) + 16384, 8192, 0, 0);
    asm volatile("" : "+r"(da), "+r"(db));
    mbar_wait(bar + B_OFULL + 8 * stage, phase);
    GT(gti++)
    constexpr int OWAIT = 2;
#pragma unroll
    for (int kk = 0; kk < 4; kk++) {
      wgmma_wait<OWAIT>();
      if (kk == OWAIT)
        mbar_arrive_cluster_if(bar + B_OEMPTY + 8 * prev_stage, wtid >> 6,
                               (wtid & 63) == 32 && kt > 0 && kt - 1 + O_STAGES < O_NK);
      wgmma_fence();
      wgmma_m64n128_ss_tb(acc[0], DHI | (da + kk * 2), DHI | (db + kk * 128), (kt | kk) != 0);
      wgmma_m64n128_ss_tb(acc[1], DHI | (da + 512 + kk * 2), DHI | (db + kk * 128), (kt | kk) != 0);
      wgmma_commit();
    }
    prev_stage = stage;
    if (++stage == O_STAGES) { stage = 0; phase ^= 1; }
  }
  {
    const uint32_t da = (uint32_t)make_desc(sbase + out_stage((O_NK - 1) % O_STAGES), 16, 0, 0);
    const uint32_t db = (uint32_t)make_desc(sbase + out_stage((O_NK - 1) % O_STAGES) + 16384, 8192, 0, 0);
    mbar_wait(bar + B_OFULL + 8 * ((O_NK - 1) % O_STAGES), ((O_NK - 1) / O_STAGES) & 1);
    GT(gti++)
#pragma unroll
    for (int h = 0; h < 2; h++) {
      wgmma_fence();
#pragma unroll
      for (int kk = 0; kk < 4; kk++)
        wgmma_m64n128_ss_tb(acc[h], DHI | (da + h * 512 + kk * 2), DHI | (db + kk * 128), 1);
      wgmma_commit();
    }
  }
  if (tid == 0) { TD(14) }
  const int st_row = warp * 16 + (lane & 7) + ((lane >> 3) & 1) * 8;
  const uint32_t rowa = sbase + O_X_OFF + st_row * 128;
  auto oa = [&](int i) { return rowa + (i >> 3) * 8192 + (i & 4) * 4096 + ((((i & 3) * 2 + (lane >> 4)) ^ (st_row & 7)) << 4); };
  uint32_t b[16][4];
  mbar_wait(bar + B_OY + 8, 0);
#pragma unroll
  for (int i = 0; i < 16; i++)
    asm volatile("ldmatrix.sync.aligned.m8n8.x4.shared.b16 {%0, %1, %2, %3}, [%4];"
                 : "=r"(b[i][0]), "=r"(b[i][1]), "=r"(b[i][2]), "=r"(b[i][3])
                 : "r"(oa(i)));
  uint32_t gg[4];
#pragma unroll
  for (int i = 0; i < 4; i++) gg[i] = pack_bf16(gv[i], gv[i]);
#pragma unroll
  for (int i = 0; i < 16; i++) {
    const int h = i >> 3;
    if (i == 0) wgmma_wait<1>();
    if (i == 8) wgmma_wait<0>();
    if (i % 8 == 0) fence_regs(acc[h]);
    const float* a = acc[h] + 8 * (i & 7);
    const uint32_t gg0 = gg[2 * h], gg1 = gg[2 * h + 1];
    stmatrix_x4(oa(i), fma_bf2(gg0, pack_bf16(a[0], a[1]), b[i][0]), fma_bf2(gg1, pack_bf16(a[2], a[3]), b[i][1]),
                fma_bf2(gg0, pack_bf16(a[4], a[5]), b[i][2]), fma_bf2(gg1, pack_bf16(a[6], a[7]), b[i][3]));
    if (i % 4 == 3) named_bar_arrive(6 + i / 4, 256);
  }
  GT(gti++)
}

__device__ __noinline__ void leave_kernel(int mask) {
  if (!(mask & 4)) return;
  if (atomicAdd(g_cnt + CNT_DONE * 32, 1u) == 2 * gridDim.x - 1) {
    for (int i = 0; i < CNT_N; i++) g_cnt[i * 32] = 0;
  }
}

__device__ __noinline__ void side_jobs(const Maps& maps, uint32_t sbase) {
  const int w12 = __shfl_sync(0xffffffffu, threadIdx.x >> 5, 0);
  gate_rows(maps, sbase, (blockIdx.x - 128) * 12 + w12, w12, threadIdx.x & 31);
  fence_proxy_async();
  __syncthreads();
  if (threadIdx.x == 320) cnt_signal_release(CNT_PREP, 1);
}

__global__ void __launch_bounds__(384, 1) fused_kernel(int mask, const __grid_constant__ Maps maps) {
  extern __shared__ __align__(1024) uint8_t smem_raw[];
  {
    const uint32_t sbase = __shfl_sync(0xffffffffu, smem_u32(smem_raw), 0);
    const uint32_t bar = sbase + BAR_OFF;
    const int tid = threadIdx.x;
    const bool do_qkv = (mask & 1) && blockIdx.x < 128;
    TL(0, 0) LT(0, 0)
    if (__shfl_sync(0xffffffffu, tid >> 5, 0) == 1 && do_qkv) {
      if (elect_one()) {
        for (int i = 0; i < G_STAGES; i++) mbar_init(bar + B_GFULL + 8 * i, 1);
        fence_barrier_init();
        qkv_producer(maps, sbase, true);
      }
    }
    if (tid == 0) {
      for (int i = 0; i < G_STAGES; i++) {
        mbar_init(bar + B_GEMPTY + 8 * i, 2);
        mbar_init(bar + B_SFULL + 8 * i, 4);
        mbar_init(bar + B_SFREE + 8 * i, 1);
      }
      for (int i = 0; i < 2; i++) {
        mbar_init(bar + B_OFREE + 8 * i, 1);
        mbar_init(bar + B_QFULL + 8 * i, 1);
        mbar_init(bar + B_QEMPTY + 8 * i, 2);
        mbar_init(bar + B_KFULL + 8 * i, 1);
        mbar_init(bar + B_KEMPTY + 8 * i, 2);
        mbar_init(bar + B_VFULL + 8 * i, 1);
        mbar_init(bar + B_VEMPTY + 8 * i, 2);
      }
      for (int i = 0; i < O_STAGES; i++) {
        mbar_init(bar + B_OFULL + 8 * i, 1);
        mbar_init(bar + B_OEMPTY + 8 * i, 2);
      }
      mbar_init(bar + B_OY, 2);
      mbar_init(bar + B_OY2, 1);
      mbar_init(bar + B_OY + 8, 4);
      mbar_init(bar + B_QDONE, 2);
      for (int i = 0; i < 8; i++) mbar_init(bar + B_CFULL + 8 * i, 1);
      for (int i = 0; i < CNT_N; i++) asm volatile("st.shared.u32 [%0], 0;" ::"r"(bar + B_PEND + 4 * i) : "memory");
      fence_barrier_init();
    }
    __syncthreads();
    asm volatile("barrier.cluster.arrive.relaxed.aligned;" ::: "memory");
    if ((mask & 1) && blockIdx.x >= 128) side_jobs(maps, sbase);
  }
  uint32_t smem0 = smem_u32(smem_raw);
  PHASE_PROLOGUE
  const bool do_qkv = (mask & 1) && blockIdx.x < 128, do_out = (mask & 4) && blockIdx.x < 128;
  TL(0, 1)

  if (wg != 2) {
    reg_alloc<232>();
    uint32_t sn = 0;
    float o[64];
    if (do_qkv) {
      sn = qkv_consumer(maps, smem_u32(smem_raw), mask & 2, o);
    } else {
      undef_regs(o);
    }
    TL(0, 2) TL(1, 0) TL(1, 1) LT(1, 0)
    asm volatile("barrier.cluster.wait.acquire.aligned;" ::: "memory");
    if (mask & 2) {
      sn = attn_consumer(maps, smem_u32(smem_raw), sn, o, mask & 1);
      TL(2, 0) LT(2, 0)
      if ((mask & 4) && blockIdx.x < 128 && __shfl_sync(0xffffffffu, threadIdx.x, 0) < 128) {
        named_bar_arrive(3, 256);
      } else {
        named_bar_sync(3, 256);
        const uint32_t b2 = blockIdx.x * 2 + (threadIdx.x >> 7);
        const bool fused = mask & 4, mainc = blockIdx.x < 128;
        const uint32_t first = __shfl_sync(0xffffffffu, !fused ? b2 : mainc ? conv_first(maps) : (b2 - 255) * 128 - C_SIDE, 0);
        conv_consumer(maps, smem_u32(smem_raw), first, !fused ? 264 : mainc ? 16 : 1,
                      !fused ? DM : (first | 127) + 1 - (mainc ? C_SIDE : 0));
      }
      TL(1, 2) TL(2, 1) TL(2, 2)
    }
    TL(3, 0) TL(3, 1)
    if ((mask & 4) && blockIdx.x < 128) out_gemm(maps, smem_u32(smem_raw));
    if (!(mask & 2) || blockIdx.x >= 128) {
      uint32_t smem0 = smem_u32(smem_raw);
      PHASE_PROLOGUE
      st_wait(bar, wg, sn - 2);
      st_post(bar, wg, wtid, sn, ST_END, nullptr, 0, 0, 0, -1);
    }
    tma_store_wait_read<0>();
    TL2(3, 2) LT(3, 128)
  } else {
    reg_dealloc<40>();
    asm volatile("barrier.cluster.wait.acquire.aligned;" ::: "memory");
    const int w = __shfl_sync(0xffffffffu, tid >> 5, 0) - 8;
    if (w < 2) {
      if (do_qkv) prep_agent(maps, sbase, w, lane);
      if (elect_one()) store_agent(bar, w);
    } else {
      if (elect_one()) {
        const bool dry = w == 2;
        if (do_qkv && !dry) qkv_producer(maps, sbase, false);
        if (mask & 2) attn_producer(maps, sbase, do_qkv, do_out, dry);
        if (do_out) out_producer(maps, sbase, mask & 2, dry);
        if (dry) { TD(5) }
      }
      __syncwarp();
      if (w == 2) publisher(bar, tid & 31, !(mask & 2) ? 2 : do_out ? 3 : 4);
      if ((tid & 31) == 0) leave_kernel(mask);
    }
  }
}

typedef CUresult (*PFN_tmapEncode)(CUtensorMap*, CUtensorMapDataType, cuuint32_t, void*, const cuuint64_t*,
                                   const cuuint64_t*, const cuuint32_t*, const cuuint32_t*, CUtensorMapInterleave,
                                   CUtensorMapSwizzle, CUtensorMapL2promotion, CUtensorMapFloatOOBfill);
static PFN_tmapEncode s_encode = nullptr;

static void make_map_2d(CUtensorMap* m, const void* ptr, int rows, int cols, int box_rows) {
  cuuint64_t dims[2] = {(cuuint64_t)cols, (cuuint64_t)rows};
  cuuint64_t strides[1] = {(cuuint64_t)cols * 2};
  cuuint32_t box[2] = {64, (cuuint32_t)box_rows};
  cuuint32_t es[2] = {1, 1};
  s_encode(m, CU_TENSOR_MAP_DATA_TYPE_BFLOAT16, 2, const_cast<void*>(ptr), dims, strides, box, es,
           CU_TENSOR_MAP_INTERLEAVE_NONE, CU_TENSOR_MAP_SWIZZLE_128B, CU_TENSOR_MAP_L2_PROMOTION_L2_256B,
           CU_TENSOR_MAP_FLOAT_OOB_FILL_NONE);
}
static void make_map_3d(CUtensorMap* m, const void* ptr, int rows, int cols, int box_rows, int box_chunks) {
  cuuint64_t dims[3] = {64, (cuuint64_t)rows, (cuuint64_t)(cols / 64)};
  cuuint64_t strides[2] = {(cuuint64_t)cols * 2, 128};
  cuuint32_t box[3] = {64, (cuuint32_t)box_rows, (cuuint32_t)box_chunks};
  cuuint32_t es[3] = {1, 1, 1};
  s_encode(m, CU_TENSOR_MAP_DATA_TYPE_BFLOAT16, 3, const_cast<void*>(ptr), dims, strides, box, es,
           CU_TENSOR_MAP_INTERLEAVE_NONE, CU_TENSOR_MAP_SWIZZLE_128B, CU_TENSOR_MAP_L2_PROMOTION_L2_256B,
           CU_TENSOR_MAP_FLOAT_OOB_FILL_NONE);
}

static void make_map_4d(CUtensorMap* m, const void* ptr, int rows, int cols, int b2, int groups) {
  cuuint64_t dims[4] = {(cuuint64_t)cols, 8, 8, (cuuint64_t)(rows / 64)};
  cuuint64_t strides[3] = {(cuuint64_t)cols * 16, (cuuint64_t)cols * 2, (cuuint64_t)cols * 128};
  cuuint32_t box[4] = {64, 8, (cuuint32_t)b2, (cuuint32_t)groups};
  cuuint32_t es[4] = {1, 1, 1, 1};
  s_encode(m, CU_TENSOR_MAP_DATA_TYPE_BFLOAT16, 4, const_cast<void*>(ptr), dims, strides, box, es,
           CU_TENSOR_MAP_INTERLEAVE_NONE, CU_TENSOR_MAP_SWIZZLE_128B, CU_TENSOR_MAP_L2_PROMOTION_L2_256B,
           CU_TENSOR_MAP_FLOAT_OOB_FILL_NONE);
}

static cudaLaunchConfig_t fused_cfg(cudaLaunchAttribute* at) {
  cudaLaunchConfig_t cfg = {};
  cfg.gridDim = dim3(132);
  cfg.blockDim = dim3(384);
  cfg.dynamicSmemBytes = SMEM_BYTES;
  cfg.stream = cudaStreamPerThread;
  at[0].id = cudaLaunchAttributeClusterDimension;
  at[0].val.clusterDim.x = 2;
  at[0].val.clusterDim.y = 1;
  at[0].val.clusterDim.z = 1;
  cfg.attrs = at;
  cfg.numAttrs = 1;
  return cfg;
}

extern "C" void kernel_launch(void* const* d_in, const int* in_sizes, int n_in, void* d_out, int out_size) {
  const bf16* x = (const bf16*)d_in[0];
  const bf16* ckv = (const bf16*)d_in[1];
  const bf16* wq = (const bf16*)d_in[2];
  const bf16* wuk = (const bf16*)d_in[3];
  const bf16* wuv = (const bf16*)d_in[4];
  const bf16* wo = (const bf16*)d_in[5];
  const bf16* bk = (const bf16*)d_in[7];
  const bf16* bv = (const bf16*)d_in[8];
  const bf16* shift_k = (const bf16*)d_in[9];
  const bf16* ssm_k = (const bf16*)d_in[10];
  const bf16* ssm_D = (const bf16*)d_in[11];
  const bf16* gate_w = (const bf16*)d_in[12];
  bf16* out = (bf16*)d_out;

  static void *pq = nullptr, *pk = nullptr, *pv = nullptr, *pctx = nullptr, *pb = nullptr;
  static int max_clusters = 0;
  if (!s_encode) {
    void* fn = nullptr;
    cudaDriverEntryPointQueryResult qres;
    cudaGetDriverEntryPoint("cuTensorMapEncodeTiled", &fn, cudaEnableDefault, &qres);
    s_encode = (PFN_tmapEncode)fn;
    cudaGetSymbolAddress(&pq, g_q);
    cudaGetSymbolAddress(&pk, g_k);
    cudaGetSymbolAddress(&pv, g_v);
    cudaGetSymbolAddress(&pctx, g_ctx);
    cudaGetSymbolAddress(&pb, g_y2T);
    cudaFuncSetAttribute(fused_kernel, cudaFuncAttributeMaxDynamicSharedMemorySize, SMEM_BYTES);
    cudaLaunchAttribute at[1];
    cudaLaunchConfig_t cfg = fused_cfg(at);
    if (cudaOccupancyMaxActiveClusters(&max_clusters, fused_kernel, &cfg) != cudaSuccess) max_clusters = 0;
  }

  Maps all = {};
  make_map_2d(&all.a[0], x, S_LEN, DM, 128);
  make_map_2d(&all.a[1], ckv, S_LEN, DC, 128);
  make_map_3d(&all.b[0], wq, DM, HDIM, 64, 4);
  make_map_3d(&all.b[1], wuk, DC, HDIM, 64, 4);
  make_map_3d(&all.b[2], wuv, DC, HDIM, 64, 4);
  make_map_2d(&all.c[0], pq, S_LEN, HDIM, 64);
  make_map_2d(&all.c[1], pk, S_LEN, HDIM, 64);
  make_map_2d(&all.c[2], pv, S_LEN, HDIM, 64);
  make_map_3d(&all.q, pq, S_LEN, HDIM, 128, 2);
  make_map_3d(&all.k, pk, S_LEN, HDIM, 128, 2);
  make_map_3d(&all.v, pv, S_LEN, HDIM, 128, 2);
  make_map_2d(&all.o, pctx, S_LEN, HDIM, 64);
  all.ssm_k = ssm_k;
  all.ssm_D = ssm_D;
  make_map_4d(&all.oa, pctx, S_LEN, HDIM, 8, 2);
  make_map_4d(&all.ox, x, S_LEN, DM, 8, 2);
  make_map_2d(&all.ob, wo, HDIM, DM, 64);
  make_map_4d(&all.oc, out, S_LEN, DM, 2, 1);
  make_map_2d(&all.y, pb, DM, S_LEN, 112);
  make_map_2d(&all.y2, pb, DM, S_LEN, 16);

  make_map_2d(&all.bk, bk, S_LEN, DM, 35);
  make_map_2d(&all.bv, bv, S_LEN, DM, 32);
  for (int b = 0; b < 128; b++) {
    const int c = b >> 1, r = b & 1;
    const int G = c < 4 ? 0 : c < 36 ? (c - 4) % 8 : 1 + (c - 36) % 7;
    const int i = c < 4 ? 4 + c : c < 36 ? (c - 4) / 8 : 4 + (c - 36) / 7;
    all.id[b][0] = r + 2 * (i & 1) + 4 * (G & 3) + 16 * (i >> 1) + 64 * (G >> 2);
    all.id[b][1] = r + 2 * i + 16 * G;
    all.id[b][2] = r + 2 * G + 16 * i;
  }
  all.shift_k = shift_k;
  all.x = x;
  all.gate_w = gate_w;
  cudaLaunchAttribute at[1];
  cudaLaunchConfig_t cfg = fused_cfg(at);
  if (max_clusters >= 66) {
    cudaLaunchKernelEx(&cfg, fused_kernel, 7, all);
  } else {
    for (int m = 1; m <= 4; m <<= 1) cudaLaunchKernelEx(&cfg, fused_kernel, m, all);
  }
}
```

```cpp
#include <cuda_runtime.h>
#include <cuda_bf16.h>
#include <cuda.h>
#include <stdint.h>

typedef __nv_bfloat16 bf16;
#define INPLACE 3

constexpr int S_LEN = 2048;
constexpr int DM = 1024;
constexpr int NH = 32;
constexpr int HD = 128;
constexpr int DC = 512;
constexpr int HDIM = NH * HD;

__device__ __align__(1024) bf16 g_k[S_LEN * HDIM / 2];
__device__ __align__(1024) bf16 g_v[S_LEN * HDIM / 2];
__device__ __align__(1024) bf16 g_ctx[S_LEN * HDIM];
__device__ __align__(1024) bf16 g_kvT[DM * S_LEN];
#define g_y2T g_kvT
__device__ __align__(1024) float g_gate[S_LEN];
enum { CNT_KV = 0, CNT_PREP = 2, CNT_CTX = 4, CNT_Y2 = 6, CNT_DONE = 8, CNT_N };
__device__ unsigned int g_cnt[CNT_N * 32];

#define TL(k, i)
#define TL2(k, i)
#define TD(i)
#define LT(i, thr)
#define PT_DECL
#define PT
#define CLK_DECL
#define CLK_SAMPLE
#define CLK_END
#define CT(i)
#define GT(i)
#define GS(i)
#define GA(i)
#define ST(i)

__device__ __forceinline__ uint32_t smem_u32(const void* p) { return (uint32_t)__cvta_generic_to_shared(p); }

__device__ __forceinline__ void mbar_init(uint32_t bar, uint32_t count) {
  asm volatile("mbarrier.init.shared::cta.b64 [%0], %1;" ::"r"(bar), "r"(count));
}
__device__ __forceinline__ void mbar_expect_tx(uint32_t bar, uint32_t bytes) {
  asm volatile("mbarrier.arrive.expect_tx.shared::cta.b64 _, [%0], %1;" ::"r"(bar), "r"(bytes) : "memory");
}
__device__ __forceinline__ void mbar_arrive(uint32_t bar) {
  asm volatile("mbarrier.arrive.shared::cta.b64 _, [%0];" ::"r"(bar) : "memory");
}
__device__ __forceinline__ void mbar_wait(uint32_t bar, uint32_t parity) {
  uint32_t done;
  uint32_t spins = 0;
  do {
    asm volatile(
        "{\n.reg .pred p;\n"
        "mbarrier.try_wait.parity.shared::cta.b64 p, [%1], %2;\n"
        "selp.u32 %0, 1, 0, p;\n}\n"
        : "=r"(done)
        : "r"(bar), "r"(parity)
        : "memory");
    if (++spins > (1u << 22)) break;
  } while (!done);
}
__device__ __forceinline__ bool mbar_try(uint32_t bar, uint32_t parity) {
  uint32_t done;
  asm volatile(
      "{\n.reg .pred p;\n"
      "mbarrier.try_wait.parity.shared::cta.b64 p, [%1], %2;\n"
      "selp.u32 %0, 1, 0, p;\n}\n"
      : "=r"(done)
      : "r"(bar), "r"(parity)
      : "memory");
  return done != 0;
}
__device__ __forceinline__ bool elect_one() {
  uint32_t pred;
  asm volatile("{\n.reg .pred p;\nelect.sync _|p, 0xffffffff;\nselp.u32 %0, 1, 0, p;\n}\n" : "=r"(pred));
  return pred != 0;
}
__device__ __forceinline__ void mbar_arrive_if(uint32_t bar, bool pred) {
  asm volatile(
      "{\n.reg .pred p;\nsetp.ne.b32 p, %1, 0;\n"
      "@p mbarrier.arrive.shared::cta.b64 _, [%0];\n}\n" ::"r"(bar),
      "r"((uint32_t)pred)
      : "memory");
}
__device__ __forceinline__ void mbar_wait_sleep(uint32_t bar, uint32_t parity) {
  uint32_t done;
  uint32_t spins = 0;
  do {
    asm volatile(
        "{\n.reg .pred p;\n"
        "mbarrier.try_wait.parity.shared::cta.b64 p, [%1], %2, %3;\n"
        "selp.u32 %0, 1, 0, p;\n}\n"
        : "=r"(done)
        : "r"(bar), "r"(parity), "r"(20000u)
        : "memory");
    if (++spins > (1u << 16)) break;
  } while (!done);
}
__device__ __forceinline__ void fence_barrier_init() {
  asm volatile("fence.mbarrier_init.release.cluster;" ::: "memory");
}
__device__ __forceinline__ void fence_proxy_async() {
  asm volatile("fence.proxy.async.shared::cta;" ::: "memory");
}
__device__ __forceinline__ void named_bar_sync(int id, int nthreads) {
  asm volatile("bar.sync %0, %1;" ::"r"(id), "r"(nthreads) : "memory");
}
__device__ __forceinline__ void named_bar_arrive(int id, int nthreads) {
  asm volatile("bar.arrive %0, %1;" ::"r"(id), "r"(nthreads) : "memory");
}
__device__ __forceinline__ void tma_load_2d(uint32_t dst, const CUtensorMap* m, uint32_t bar, int c0, int c1) {
  asm volatile(
      "cp.async.bulk.tensor.2d.shared::cluster.global.mbarrier::complete_tx::bytes [%0], [%1, {%3, %4}], [%2];" ::"r"(dst),
      "l"(reinterpret_cast<uint64_t>(m)), "r"(bar), "r"(c0), "r"(c1)
      : "memory");
}
__device__ __forceinline__ void tma_load_3d(uint32_t dst, const CUtensorMap* m, uint32_t bar, int c0, int c1, int c2) {
  asm volatile(
      "cp.async.bulk.tensor.3d.shared::cluster.global.mbarrier::complete_tx::bytes [%0], [%1, {%3, %4, %5}], [%2];" ::"r"(dst),
      "l"(reinterpret_cast<uint64_t>(m)), "r"(bar), "r"(c0), "r"(c1), "r"(c2)
      : "memory");
}
__device__ __forceinline__ void tma_store_2d(const CUtensorMap* m, uint32_t src, int c0, int c1) {
  asm volatile("cp.async.bulk.tensor.2d.global.shared::cta.bulk_group [%0, {%2, %3}], [%1];" ::"l"(
                   reinterpret_cast<uint64_t>(m)),
               "r"(src), "r"(c0), "r"(c1)
               : "memory");
}
__device__ __forceinline__ void tma_load_4d(uint32_t dst, const CUtensorMap* m, uint32_t bar, int c0, int tile) {
  asm volatile(
      "cp.async.bulk.tensor.4d.shared::cluster.global.mbarrier::complete_tx::bytes [%0], [%1, {%3, %4, %4, %5}], [%2];" ::"r"(dst),
      "l"(reinterpret_cast<uint64_t>(m)), "r"(bar), "r"(c0), "r"(0), "r"(2 * tile)
      : "memory");
}
__device__ __forceinline__ void tma_store_4d(const CUtensorMap* m, uint32_t src, int c0, int c2, int group) {
  asm volatile("cp.async.bulk.tensor.4d.global.shared::cta.bulk_group [%0, {%2, %3, %4, %5}], [%1];" ::"l"(
                   reinterpret_cast<uint64_t>(m)),
               "r"(src), "r"(c0), "r"(0), "r"(c2), "r"(group)
               : "memory");
}
__device__ __forceinline__ void bulk_load(uint32_t dst, const void* src, uint32_t bytes, uint32_t bar) {
  asm volatile("cp.async.bulk.shared::cluster.global.mbarrier::complete_tx::bytes [%0], [%1], %2, [%3];" ::"r"(dst),
               "l"(src), "r"(bytes), "r"(bar)
               : "memory");
}
__device__ __forceinline__ void tma_load_2d_mc(uint32_t dst, const CUtensorMap* m, uint32_t bar, int c0, int c1,
                                               uint16_t mask) {
  asm volatile(
      "cp.async.bulk.tensor.2d.shared::cluster.global.mbarrier::complete_tx::bytes.multicast::cluster [%0], [%1, {%3, "
      "%4}], [%2], %5;" ::"r"(dst),
      "l"(reinterpret_cast<uint64_t>(m)), "r"(bar), "r"(c0), "r"(c1), "h"(mask)
      : "memory");
}
__device__ __forceinline__ void mbar_arrive_cluster_if(uint32_t bar, uint32_t cta, bool pred) {
  asm volatile(
      "{\n.reg .b32 ra;\n.reg .pred p;\nsetp.ne.b32 p, %2, 0;\n"
      "mapa.shared::cluster.u32 ra, %0, %1;\n"
      "@p mbarrier.arrive.shared::cluster.b64 _, [ra];\n}\n" ::"r"(bar),
      "r"(cta), "r"((uint32_t)pred)
      : "memory");
}
__device__ __forceinline__ uint64_t policy_evict_first() {
  uint64_t pol;
  asm volatile("createpolicy.fractional.L2::evict_first.b64 %0, 1.0;" : "=l"(pol));
  return pol;
}
__device__ __forceinline__ void tma_load_2d_hint(uint32_t dst, const CUtensorMap* m, uint32_t bar, int c0, int c1,
                                                 uint64_t pol) {
  asm volatile(
      "cp.async.bulk.tensor.2d.shared::cluster.global.mbarrier::complete_tx::bytes.L2::cache_hint [%0], [%1, {%3, %4}], "
      "[%2], %5;" ::"r"(dst),
      "l"(reinterpret_cast<uint64_t>(m)), "r"(bar), "r"(c0), "r"(c1), "l"(pol)
      : "memory");
}
__device__ __forceinline__ void tma_load_3d_hint(uint32_t dst, const CUtensorMap* m, uint32_t bar, int c0, int c1,
                                                 int c2, uint64_t pol) {
  asm volatile(
      "cp.async.bulk.tensor.3d.shared::cluster.global.mbarrier::complete_tx::bytes.L2::cache_hint [%0], [%1, {%3, %4, "
      "%5}], [%2], %6;" ::"r"(dst),
      "l"(reinterpret_cast<uint64_t>(m)), "r"(bar), "r"(c0), "r"(c1), "r"(c2), "l"(pol)
      : "memory");
}
__device__ __forceinline__ void bulk_load_hint(uint32_t dst, const void* src, uint32_t bytes, uint32_t bar, uint64_t pol) {
  asm volatile(
      "cp.async.bulk.shared::cluster.global.mbarrier::complete_tx::bytes.L2::cache_hint [%0], [%1], %2, [%3], %4;" ::"r"(dst),
      "l"(src), "r"(bytes), "r"(bar), "l"(pol)
      : "memory");
}
__device__ __forceinline__ void cnt_signal_release(int which, uint32_t n) {
  asm volatile("red.release.gpu.global.add.u32 [%0], %1;" ::"l"(g_cnt + which * 32), "r"(n) : "memory");
}
__device__ __forceinline__ void cnt_wait(int which, uint32_t target) {
  uint32_t v, spins = 0;
  while (true) {
    asm volatile("ld.acquire.gpu.global.u32 %0, [%1];" : "=r"(v) : "l"(g_cnt + which * 32) : "memory");
    if (v >= target || ++spins > (1u << 18)) break;
    __nanosleep(64);
  }
  asm volatile("fence.proxy.async.global;" ::: "memory");
}
__device__ __forceinline__ void tma_store_commit() { asm volatile("cp.async.bulk.commit_group;" ::: "memory"); }
template <int N>
__device__ __forceinline__ void tma_store_wait_read() {
  asm volatile("cp.async.bulk.wait_group.read %0;" ::"n"(N) : "memory");
}
template <int N>
__device__ __forceinline__ void tma_store_wait() {
  asm volatile("cp.async.bulk.wait_group %0;" ::"n"(N) : "memory");
}
__device__ __forceinline__ void wgmma_fence() { asm volatile("wgmma.fence.sync.aligned;" ::: "memory"); }
__device__ __forceinline__ void wgmma_commit() { asm volatile("wgmma.commit_group.sync.aligned;" ::: "memory"); }
template <int N>
__device__ __forceinline__ void wgmma_wait() {
  asm volatile("wgmma.wait_group.sync.aligned %0;" ::"n"(N) : "memory");
}
template <int R>
__device__ __forceinline__ void reg_alloc() { asm volatile("setmaxnreg.inc.sync.aligned.u32 %0;" ::"n"(R)); }
template <int R>
__device__ __forceinline__ void reg_dealloc() { asm volatile("setmaxnreg.dec.sync.aligned.u32 %0;" ::"n"(R)); }

__device__ __forceinline__ void stmatrix_x4(uint32_t addr, uint32_t r0, uint32_t r1, uint32_t r2, uint32_t r3) {
  asm volatile("stmatrix.sync.aligned.m8n8.x4.shared.b16 [%0], {%1, %2, %3, %4};" ::"r"(addr), "r"(r0), "r"(r1),
               "r"(r2), "r"(r3)
               : "memory");
}
__device__ __forceinline__ uint32_t pack_bf16(float lo, float hi) {
  uint32_t r;
  asm("cvt.rn.bf16x2.f32 %0, %1, %2;" : "=r"(r) : "f"(hi), "f"(lo));
  return r;
}
__device__ __forceinline__ float bf16_round(float x) { return __bfloat162float(__float2bfloat16_rn(x)); }
__device__ __forceinline__ float bf_lo(uint32_t v) { return __uint_as_float(v << 16); }
__device__ __forceinline__ float bf_hi(uint32_t v) { return __uint_as_float(v & 0xffff0000u); }
__device__ __forceinline__ uint4 lds128(uint32_t a) {
  uint4 v;
  asm volatile("ld.shared.v4.u32 {%0, %1, %2, %3}, [%4];" : "=r"(v.x), "=r"(v.y), "=r"(v.z), "=r"(v.w) : "r"(a));
  return v;
}
__device__ __forceinline__ void sts128(uint32_t a, uint4 v) {
  asm volatile("st.shared.v4.u32 [%0], {%1, %2, %3, %4};" ::"r"(a), "r"(v.x), "r"(v.y), "r"(v.z), "r"(v.w) : "memory");
}
__device__ __forceinline__ uint32_t mul_bf2(uint32_t a, uint32_t b) {
  uint32_t r;
  asm("mul.rn.bf16x2 %0, %1, %2;" : "=r"(r) : "r"(a), "r"(b));
  return r;
}
__device__ __forceinline__ uint32_t add_bf2(uint32_t a, uint32_t b) {
  uint32_t r;
  asm("add.rn.bf16x2 %0, %1, %2;" : "=r"(r) : "r"(a), "r"(b));
  return r;
}
__device__ __forceinline__ float ex2(float x) {
  float y;
  asm("ex2.approx.ftz.f32 %0, %1;" : "=f"(y) : "f"(x));
  return y;
}
__device__ __forceinline__ float rcp(float x) {
  float y;
  asm("rcp.approx.ftz.f32 %0, %1;" : "=f"(y) : "f"(x));
  return y;
}
template <int N>
__device__ __forceinline__ void fence_regs(float (&r)[N]) {
#pragma unroll
  for (int i = 0; i < N; i++) asm volatile("" : "+f"(r[i])::"memory");
}

template <int N>
__device__ __forceinline__ void undef_regs(float (&r)[N]) {
#pragma unroll
  for (int i = 0; i < N; i++) asm volatile("" : "=f"(r[i]));
}
template <int N>
__device__ __forceinline__ void fence_regs_u(uint32_t (&r)[N]) {
#pragma unroll
  for (int i = 0; i < N; i++) asm volatile("" : "+r"(r[i])::"memory");
}

constexpr uint64_t DESC_SW128 = 1ull << 62;
__device__ __forceinline__ uint64_t make_desc(uint32_t addr, uint32_t lbo_bytes, uint32_t sbo_bytes, uint64_t swz) {
  return (uint64_t)((addr & 0x3FFFF) >> 4) | ((uint64_t)((lbo_bytes & 0x3FFFF) >> 4) << 16) |
         ((uint64_t)((sbo_bytes & 0x3FFFF) >> 4) << 32) | swz;
}

__device__ __forceinline__ uint64_t desc_add(uint64_t d, uint32_t off16) {
  return (d & 0xFFFFFFFF00000000ull) | (uint64_t)((uint32_t)d + off16);
}

__device__ __forceinline__ void wgmma_m64n256_ss_tb(float (&d)[128], uint64_t da, uint64_t db, int sd) {
  asm volatile(
    "{\n.reg .pred p;\nsetp.ne.b32 p, %130, 0;\n"
    "wgmma.mma_async.sync.aligned.m64n256k16.f32.bf16.bf16 "
    "{%0, %1, %2, %3, %4, %5, %6, %7, %8, %9, %10, %11, %12, %13, %14, %15, %16, %17, %18, %19, %20, %21, %22, %23, %24, %25, %26, %27, %28, %29, %30, %31, %32, %33, %34, %35, %36, %37, %38, %39, %40, %41, %42, %43, %44, %45, %46, %47, %48, %49, %50, %51, %52, %53, %54, %55, %56, %57, %58, %59, %60, %61, %62, %63, %64, %65, %66, %67, %68, %69, %70, %71, %72, %73, %74, %75, %76, %77, %78, %79, %80, %81, %82, %83, %84, %85, %86, %87, %88, %89, %90, %91, %92, %93, %94, %95, %96, %97, %98, %99, %100, %101, %102, %103, %104, %105, %106, %107, %108, %109, %110, %111, %112, %113, %114, %115, %116, %117, %118, %119, %120, %121, %122, %123, %124, %125, %126, %127}, %128, %129, p, 1, 1, 0, 1;\n}\n"
    : "+f"(d[0]), "+f"(d[1]), "+f"(d[2]), "+f"(d[3]), "+f"(d[4]), "+f"(d[5]), "+f"(d[6]), "+f"(d[7]), "+f"(d[8]), "+f"(d[9]), "+f"(d[10]), "+f"(d[11]), "+f"(d[12]), "+f"(d[13]), "+f"(d[14]), "+f"(d[15]), "+f"(d[16]), "+f"(d[17]), "+f"(d[18]), "+f"(d[19]), "+f"(d[20]), "+f"(d[21]), "+f"(d[22]), "+f"(d[23]), "+f"(d[24]), "+f"(d[25]), "+f"(d[26]), "+f"(d[27]), "+f"(d[28]), "+f"(d[29]), "+f"(d[30]), "+f"(d[31]), "+f"(d[32]), "+f"(d[33]), "+f"(d[34]), "+f"(d[35]), "+f"(d[36]), "+f"(d[37]), "+f"(d[38]), "+f"(d[39]), "+f"(d[40]), "+f"(d[41]), "+f"(d[42]), "+f"(d[43]), "+f"(d[44]), "+f"(d[45]), "+f"(d[46]), "+f"(d[47]), "+f"(d[48]), "+f"(d[49]), "+f"(d[50]), "+f"(d[51]), "+f"(d[52]), "+f"(d[53]), "+f"(d[54]), "+f"(d[55]), "+f"(d[56]), "+f"(d[57]), "+f"(d[58]), "+f"(d[59]), "+f"(d[60]), "+f"(d[61]), "+f"(d[62]), "+f"(d[63]), "+f"(d[64]), "+f"(d[65]), "+f"(d[66]), "+f"(d[67]), "+f"(d[68]), "+f"(d[69]), "+f"(d[70]), "+f"(d[71]), "+f"(d[72]), "+f"(d[73]), "+f"(d[74]), "+f"(d[75]), "+f"(d[76]), "+f"(d[77]), "+f"(d[78]), "+f"(d[79]), "+f"(d[80]), "+f"(d[81]), "+f"(d[82]), "+f"(d[83]), "+f"(d[84]), "+f"(d[85]), "+f"(d[86]), "+f"(d[87]), "+f"(d[88]), "+f"(d[89]), "+f"(d[90]), "+f"(d[91]), "+f"(d[92]), "+f"(d[93]), "+f"(d[94]), "+f"(d[95]), "+f"(d[96]), "+f"(d[97]), "+f"(d[98]), "+f"(d[99]), "+f"(d[100]), "+f"(d[101]), "+f"(d[102]), "+f"(d[103]), "+f"(d[104]), "+f"(d[105]), "+f"(d[106]), "+f"(d[107]), "+f"(d[108]), "+f"(d[109]), "+f"(d[110]), "+f"(d[111]), "+f"(d[112]), "+f"(d[113]), "+f"(d[114]), "+f"(d[115]), "+f"(d[116]), "+f"(d[117]), "+f"(d[118]), "+f"(d[119]), "+f"(d[120]), "+f"(d[121]), "+f"(d[122]), "+f"(d[123]), "+f"(d[124]), "+f"(d[125]), "+f"(d[126]), "+f"(d[127])
    : "l"(da), "l"(db), "r"(sd));
}

__device__ __forceinline__ void wgmma_m64n128_ss(float (&d)[64], uint64_t da, uint64_t db, int sd) {
  asm volatile(
    "{\n.reg .pred p;\nsetp.ne.b32 p, %66, 0;\n"
    "wgmma.mma_async.sync.aligned.m64n128k16.f32.bf16.bf16 "
    "{%0, %1, %2, %3, %4, %5, %6, %7, %8, %9, %10, %11, %12, %13, %14, %15, %16, %17, %18, %19, %20, %21, %22, %23, %24, %25, %26, %27, %28, %29, %30, %31, %32, %33, %34, %35, %36, %37, %38, %39, %40, %41, %42, %43, %44, %45, %46, %47, %48, %49, %50, %51, %52, %53, %54, %55, %56, %57, %58, %59, %60, %61, %62, %63}, %64, %65, p, 1, 1, 0, 0;\n}\n"
    : "+f"(d[0]), "+f"(d[1]), "+f"(d[2]), "+f"(d[3]), "+f"(d[4]), "+f"(d[5]), "+f"(d[6]), "+f"(d[7]), "+f"(d[8]), "+f"(d[9]), "+f"(d[10]), "+f"(d[11]), "+f"(d[12]), "+f"(d[13]), "+f"(d[14]), "+f"(d[15]), "+f"(d[16]), "+f"(d[17]), "+f"(d[18]), "+f"(d[19]), "+f"(d[20]), "+f"(d[21]), "+f"(d[22]), "+f"(d[23]), "+f"(d[24]), "+f"(d[25]), "+f"(d[26]), "+f"(d[27]), "+f"(d[28]), "+f"(d[29]), "+f"(d[30]), "+f"(d[31]), "+f"(d[32]), "+f"(d[33]), "+f"(d[34]), "+f"(d[35]), "+f"(d[36]), "+f"(d[37]), "+f"(d[38]), "+f"(d[39]), "+f"(d[40]), "+f"(d[41]), "+f"(d[42]), "+f"(d[43]), "+f"(d[44]), "+f"(d[45]), "+f"(d[46]), "+f"(d[47]), "+f"(d[48]), "+f"(d[49]), "+f"(d[50]), "+f"(d[51]), "+f"(d[52]), "+f"(d[53]), "+f"(d[54]), "+f"(d[55]), "+f"(d[56]), "+f"(d[57]), "+f"(d[58]), "+f"(d[59]), "+f"(d[60]), "+f"(d[61]), "+f"(d[62]), "+f"(d[63])
    : "l"(da), "l"(db), "r"(sd));
}

__device__ __forceinline__ void wgmma_m64n128_ss_tb(float (&d)[64], uint64_t da, uint64_t db, int sd) {
  asm volatile(
    "{\n.reg .pred p;\nsetp.ne.b32 p, %66, 0;\n"
    "wgmma.mma_async.sync.aligned.m64n128k16.f32.bf16.bf16 "
    "{%0, %1, %2, %3, %4, %5, %6, %7, %8, %9, %10, %11, %12, %13, %14, %15, %16, %17, %18, %19, %20, %21, %22, %23, %24, %25, %26, %27, %28, %29, %30, %31, %32, %33, %34, %35, %36, %37, %38, %39, %40, %41, %42, %43, %44, %45, %46, %47, %48, %49, %50, %51, %52, %53, %54, %55, %56, %57, %58, %59, %60, %61, %62, %63}, %64, %65, p, 1, 1, 0, 1;\n}\n"
    : "+f"(d[0]), "+f"(d[1]), "+f"(d[2]), "+f"(d[3]), "+f"(d[4]), "+f"(d[5]), "+f"(d[6]), "+f"(d[7]), "+f"(d[8]), "+f"(d[9]), "+f"(d[10]), "+f"(d[11]), "+f"(d[12]), "+f"(d[13]), "+f"(d[14]), "+f"(d[15]), "+f"(d[16]), "+f"(d[17]), "+f"(d[18]), "+f"(d[19]), "+f"(d[20]), "+f"(d[21]), "+f"(d[22]), "+f"(d[23]), "+f"(d[24]), "+f"(d[25]), "+f"(d[26]), "+f"(d[27]), "+f"(d[28]), "+f"(d[29]), "+f"(d[30]), "+f"(d[31]), "+f"(d[32]), "+f"(d[33]), "+f"(d[34]), "+f"(d[35]), "+f"(d[36]), "+f"(d[37]), "+f"(d[38]), "+f"(d[39]), "+f"(d[40]), "+f"(d[41]), "+f"(d[42]), "+f"(d[43]), "+f"(d[44]), "+f"(d[45]), "+f"(d[46]), "+f"(d[47]), "+f"(d[48]), "+f"(d[49]), "+f"(d[50]), "+f"(d[51]), "+f"(d[52]), "+f"(d[53]), "+f"(d[54]), "+f"(d[55]), "+f"(d[56]), "+f"(d[57]), "+f"(d[58]), "+f"(d[59]), "+f"(d[60]), "+f"(d[61]), "+f"(d[62]), "+f"(d[63])
    : "l"(da), "l"(db), "r"(sd));
}

__device__ __forceinline__ void wgmma_m64n128_rs_tb(float* d, uint32_t a0, uint32_t a1, uint32_t a2, uint32_t a3, uint64_t db, int sd) {
  asm volatile(
    "{\n.reg .pred p;\nsetp.ne.b32 p, %69, 0;\n"
    "wgmma.mma_async.sync.aligned.m64n128k16.f32.bf16.bf16 "
    "{%0, %1, %2, %3, %4, %5, %6, %7, %8, %9, %10, %11, %12, %13, %14, %15, %16, %17, %18, %19, %20, %21, %22, %23, %24, %25, %26, %27, %28, %29, %30, %31, %32, %33, %34, %35, %36, %37, %38, %39, %40, %41, %42, %43, %44, %45, %46, %47, %48, %49, %50, %51, %52, %53, %54, %55, %56, %57, %58, %59, %60, %61, %62, %63}, {%64, %65, %66, %67}, %68, p, 1, 1, 1;\n}\n"
    : "+f"(d[0]), "+f"(d[1]), "+f"(d[2]), "+f"(d[3]), "+f"(d[4]), "+f"(d[5]), "+f"(d[6]), "+f"(d[7]), "+f"(d[8]), "+f"(d[9]), "+f"(d[10]), "+f"(d[11]), "+f"(d[12]), "+f"(d[13]), "+f"(d[14]), "+f"(d[15]), "+f"(d[16]), "+f"(d[17]), "+f"(d[18]), "+f"(d[19]), "+f"(d[20]), "+f"(d[21]), "+f"(d[22]), "+f"(d[23]), "+f"(d[24]), "+f"(d[25]), "+f"(d[26]), "+f"(d[27]), "+f"(d[28]), "+f"(d[29]), "+f"(d[30]), "+f"(d[31]), "+f"(d[32]), "+f"(d[33]), "+f"(d[34]), "+f"(d[35]), "+f"(d[36]), "+f"(d[37]), "+f"(d[38]), "+f"(d[39]), "+f"(d[40]), "+f"(d[41]), "+f"(d[42]), "+f"(d[43]), "+f"(d[44]), "+f"(d[45]), "+f"(d[46]), "+f"(d[47]), "+f"(d[48]), "+f"(d[49]), "+f"(d[50]), "+f"(d[51]), "+f"(d[52]), "+f"(d[53]), "+f"(d[54]), "+f"(d[55]), "+f"(d[56]), "+f"(d[57]), "+f"(d[58]), "+f"(d[59]), "+f"(d[60]), "+f"(d[61]), "+f"(d[62]), "+f"(d[63])
    : "r"(a0), "r"(a1), "r"(a2), "r"(a3), "l"(db), "r"(sd));
}

__device__ __forceinline__ void wgmma_m64n64_rs(float (&d)[32], const uint32_t* a, uint64_t db, int sd) {
  asm volatile(
    "{\n.reg .pred p;\nsetp.ne.b32 p, %37, 0;\n"
    "wgmma.mma_async.sync.aligned.m64n64k16.f32.bf16.bf16 "
    "{%0, %1, %2, %3, %4, %5, %6, %7, %8, %9, %10, %11, %12, %13, %14, %15, %16, %17, %18, %19, %20, %21, %22, %23, %24, %25, %26, %27, %28, %29, %30, %31}, {%32, %33, %34, %35}, %36, p, 1, 1, 0;\n}\n"
    : "+f"(d[0]), "+f"(d[1]), "+f"(d[2]), "+f"(d[3]), "+f"(d[4]), "+f"(d[5]), "+f"(d[6]), "+f"(d[7]), "+f"(d[8]), "+f"(d[9]), "+f"(d[10]), "+f"(d[11]), "+f"(d[12]), "+f"(d[13]), "+f"(d[14]), "+f"(d[15]), "+f"(d[16]), "+f"(d[17]), "+f"(d[18]), "+f"(d[19]), "+f"(d[20]), "+f"(d[21]), "+f"(d[22]), "+f"(d[23]), "+f"(d[24]), "+f"(d[25]), "+f"(d[26]), "+f"(d[27]), "+f"(d[28]), "+f"(d[29]), "+f"(d[30]), "+f"(d[31])
    : "r"(a[0]), "r"(a[1]), "r"(a[2]), "r"(a[3]), "l"(db), "r"(sd));
}

constexpr int G_STAGES = 4;
constexpr int G_A_BYTES = 128 * 64 * 2;
constexpr int G_B_BYTES = 256 * 64 * 2;
constexpr int G_STAGE_BYTES = G_A_BYTES + G_B_BYTES;
constexpr int G_STG_OFF = G_STAGES * G_STAGE_BYTES;
constexpr int BAR_OFF = G_STG_OFF + 32768 + 2048;
constexpr int SMEM_BYTES = BAR_OFF + 1024;
constexpr int B_GFULL = 0, B_GEMPTY = 32, B_OY2 = 64, B_PFULL = 224;
constexpr int B_KFULL = 80, B_KEMPTY = 96, B_VFULL = 112, B_VEMPTY = 128, B_QFULL = 144, B_QEMPTY = 160,
              B_QPEER = 184;
constexpr int B_CFULL = 192;
constexpr int B_OFREE = 256, B_OFULL = 272, B_OEMPTY = 320, B_OY = 368;
constexpr int B_SFULL = 392, B_SFREE = 424, B_PEND = 456, B_SCMD = 512;

#define PHASE_PROLOGUE                                                                \
  uint32_t tid, rt_zero;                                                              \
  asm volatile("mov.u32 %0, %%tid.x;" : "=r"(tid));                                   \
  asm volatile("mov.u32 %0, %%nctaid.y;" : "=r"(rt_zero));                            \
  asm volatile("" : "+r"(smem0));                                                     \
  rt_zero = __shfl_sync(0xffffffffu, rt_zero >> 8, 0);   \
  const uint32_t sbase = __shfl_sync(0xffffffffu, smem0, 0);                          \
  const uint32_t bar = sbase + BAR_OFF;                                               \
  const int wg = __shfl_sync(0xffffffffu, tid >> 7, 0);                               \
  const int warp = (tid >> 5) & 3, lane = tid & 31, wtid = tid & 127;                 \
  (void)rt_zero; (void)bar; (void)warp; (void)lane; (void)wtid;

constexpr int A_ITEMS = 256;
enum { ST_BOX1, ST_BOX1P, ST_BOX2, ST_BOX2W, ST_BOX2L, ST_PEER };
__device__ __forceinline__ void st_post(uint32_t bar, int wg, int wtid, uint32_t n, int kind, int dst, uint32_t src,
                                        int c0, int c1, int sig) {
  if (wtid == 0) sts128(bar + B_SCMD + wg * 32 + (n & 1) * 16, make_uint4(kind + dst * 8 + sig * 32, src, c0, c1));
  fence_proxy_async();
  __syncwarp();
  mbar_arrive_if(bar + B_SFULL + wg * 16 + (n & 1) * 8, (wtid & 31) == 0);
}
__device__ __forceinline__ void st_wait(uint32_t bar, int wg, uint32_t n) {
  const uint32_t b = bar + B_SFREE + wg * 16 + (n & 1) * 8;
  if (!mbar_try(b, ~(n >> 1) & 1)) mbar_wait(b, ~(n >> 1) & 1);
}
__device__ __forceinline__ void note(uint32_t bar, uint32_t cnt) {
  asm volatile("red.release.cta.shared.add.u32 [%0], 1;" ::"r"(bar + B_PEND + 4 * cnt) : "memory");
}
__device__ __forceinline__ void store_agent(const CUtensorMap* maps, uint32_t bar, int wg, uint32_t n) {
  const uint32_t fr = bar + B_SFREE + wg * 16;
  mbar_arrive(fr + (~n & 1) * 8);
  if (n == 0) mbar_arrive(fr);
  for (;; n++) {
    mbar_wait_sleep(bar + B_SFULL + wg * 16 + (n & 1) * 8, (n >> 1) & 1);
    uint4 c = lds128(bar + B_SCMD + wg * 32 + (n & 1) * 16);
    const CUtensorMap* dst = maps + ((c.x >> 3) & 3);
    const int sig = (int)c.x >> 5;
    c.x &= 7;
    if (c.x == ST_PEER) {
      mbar_wait_sleep(bar + B_QPEER, c.z);
      asm volatile(
          "{\n.reg .b32 d, b;\nmapa.shared::cluster.u32 d, %0, %2;\nmapa.shared::cluster.u32 b, %1, %2;\n"
          "cp.async.bulk.shared::cluster.shared::cta.mbarrier::complete_tx::bytes [d], [%3], 8192, [b];\n"
          "cp.async.bulk.shared::cluster.shared::cta.mbarrier::complete_tx::bytes [d + 16384], [%3 + 8192], 8192, [b];\n}\n" ::"r"(
              bar - BAR_OFF + 32768 + wg * 8192),
          "r"(bar + B_QFULL + 8), "r"(~blockIdx.x & 1), "r"(c.y)
          : "memory");
      mbar_wait_sleep(bar + B_QFULL + 8, 0);
      mbar_arrive_cluster_if(fr + (n & 1) * 8, ~blockIdx.x & 1, true);
      continue;
    }
    tma_store_2d(dst, c.y, c.z, c.w);
    if (c.x >= ST_BOX2) tma_store_2d(dst, c.y + 8192, c.z + 64, c.w);
    tma_store_commit();
    tma_store_wait_read<0>();
    if (c.x != ST_BOX1P) mbar_arrive(fr + (n & 1) * 8);
    if (c.x == ST_BOX2L) mbar_arrive(bar + B_OFREE + 8 * wg);
    if (sig >= 0) {
      tma_store_wait<0>();
      asm volatile("fence.proxy.async.global;" ::: "memory");
      note(bar, sig);
      if (c.x == ST_BOX2W) cnt_wait(CNT_CTX, 2 * A_ITEMS);
      if (c.x == ST_BOX2L) note(bar, CNT_DONE);
      if (c.x == ST_BOX2L || c.x == ST_BOX1P) break;
    }
  }
}

struct Maps {
  const bf16 *shift_k, *x, *gate_w, *ssm_k, *ssm_D;
  uint8_t id[128][4];
  CUtensorMap a[2];
  CUtensorMap b[3];
  CUtensorMap c[3];
  CUtensorMap bk, bv;
  CUtensorMap k, v;
  CUtensorMap oa, ob, oc, ox;
  CUtensorMap y, y2;
};

constexpr int P_SLOT = 67 * 128, P_V = 35 * 128, P_TAPS = 2 * P_SLOT;
__device__ __forceinline__ void ldsm4t(uint32_t (&r)[4], uint32_t a) {
  asm volatile("ldmatrix.sync.aligned.m8n8.x4.trans.shared.b16 {%0, %1, %2, %3}, [%4];"
               : "=r"(r[0]), "=r"(r[1]), "=r"(r[2]), "=r"(r[3])
               : "r"(a));
}
__device__ __forceinline__ uint32_t fma_bf2(uint32_t a, uint32_t b, uint32_t c) {
  uint32_t r;
  asm("fma.rn.bf16x2 %0, %1, %2, %3;" : "=r"(r) : "r"(a), "r"(b), "r"(c));
  return r;
}
__device__ __forceinline__ void agent_warp(const Maps& maps, uint32_t smem0) {
  mbar_wait_sleep(smem0 + BAR_OFF + B_GFULL + 8 * (G_STAGES - 1), 0);
#pragma unroll 1
  for (int j = 0; j < 7; j++) {
    PHASE_PROLOGUE
    const int w = __shfl_sync(0xffffffffu, warp, 0), i = j >> 1;
    const uint32_t pb = bar + B_PFULL + w * 16, sw = sbase + G_STG_OFF + w * (P_TAPS + 512);
    const int d0 = (blockIdx.x >> 4) * 128 + (j < 3 ? 64 : 0), t0 = (blockIdx.x & 15) * 128 + w * 64;
    const bool work = (0x56 >> j) & 1;
    GA(80 + 2 * j)
    if (work) mbar_wait_sleep(pb + (i & 1) * 8, i >> 1);
    GA(81 + 2 * j)
    if (((0x2b >> j) & 1) && elect_one()) {
      const uint32_t l = ((j + 1) >> 1) & 1, b = pb + l * 8, dst = sw + l * P_SLOT;
      mbar_expect_tx(b, work ? P_SLOT : P_SLOT + 512);
      const uint64_t pol = policy_evict_first();
      tma_load_2d_hint(dst, &maps.bk, b, d0, t0 + 32 * l - 3, pol);
      tma_load_2d_hint(dst + P_V, &maps.bv, b, d0, t0 + 32 * l, pol);
      if (!work) bulk_load(sbase + G_STG_OFF + P_TAPS, maps.shift_k + d0 * 4, 512, b);
    }
    if (!work) continue;
    const uint32_t so = sw + (i & 1) * P_SLOT;
    uint32_t ak[4];
#pragma unroll
    for (int r = 0; r < 4; r++) {
      const uint32_t a = so / 128 + r + 4 * (lane & 6) + (((((lane >> 2) ^ lane) & 6) + (lane & 1)) ^ 7);
      ak[r] = a * 128 + (a & 7) * 16;
    }
    bf16* dst = g_kvT + (size_t)(d0 + (lane >> 2)) * S_LEN + t0 + ((lane & 3) + 4 * (i & 1)) * 8;
#pragma unroll 1
    for (int cg = 0; cg < 128; cg += 16) {
      uint32_t t01, t23, k[4][4], v[4];
      asm volatile("ld.shared.v2.u32 {%0, %1}, [%2];"
                   : "=r"(t01), "=r"(t23)
                   : "r"(sbase + G_STG_OFF + P_TAPS + cg * 4 + (lane >> 2) * 8));
#pragma unroll
      for (int r = 0; r < 4; r++) ldsm4t(k[r], ak[r] ^ cg);
      ldsm4t(v, (ak[3] ^ cg) + 4096);
      const uint32_t w0 = __byte_perm(t01, 0, 0x1010), w1 = __byte_perm(t01, 0, 0x3232);
      const uint32_t w2 = __byte_perm(t23, 0, 0x1010), w3 = __byte_perm(t23, 0, 0x3232);
#pragma unroll
      for (int j = 0; j < 4; j++)
        v[j] = mul_bf2(fma_bf2(k[3][j], w0, fma_bf2(k[2][j], w1, fma_bf2(k[1][j], w2, mul_bf2(k[0][j], w3)))), v[j]);
      const bool s1 = lane & 1, s2 = lane & 2;
      const uint32_t a0 = s1 ? v[1] : v[0], a1 = s1 ? v[0] : v[1], a2 = s1 ? v[3] : v[2], a3 = s1 ? v[2] : v[3];
      *reinterpret_cast<uint4*>(dst) = make_uint4(s2 ? a2 : a0, s2 ? a3 : a1, s2 ? a0 : a2, s2 ? a1 : a3);
      dst += 8 * S_LEN;
    }
    fence_proxy_async();
    __syncwarp();
    if (j == 1) continue;
    GA(94)
    if (elect_one()) {
      note(bar, CNT_PREP + (j > 2));
      store_agent(maps.c, bar, w, (0x130800 >> (4 * j - 8)) & 255);
    }
    __syncwarp();
  }
}

__device__ __forceinline__ void qkv_tile(const Maps& maps, int it, int& m_tile, int& group) {
  const int b = maps.id[blockIdx.x][it >> 1];
  m_tile = b & 15;
  group = b >> 4;
}

constexpr int G_NTILES = 3;
__device__ __forceinline__ void qkv_producer(const Maps& maps, uint32_t sbase, int pass, bool first) {
  const uint32_t bar = sbase + BAR_OFF;
  uint32_t stage = 0, phase = pass;
#pragma unroll 1
  for (int it = 0; it < (first ? 1 : G_NTILES); it++) {
    int m_tile, group;
    qkv_tile(maps, it, m_tile, group);
    const CUtensorMap* ma = &maps.a[it >> 1];
    const CUtensorMap* mb = &maps.b[it];
    const int nk = first ? G_STAGES : it == 2 ? 16 : 8;
#pragma unroll 1
    for (int kt = (it == 0 && !first && !pass) ? G_STAGES : 0; kt < nk; kt++) {
      if (pass && it == 0 && kt < G_STAGES) {
        constexpr uint32_t LASTB = (B_QEMPTY + 8) | (B_KEMPTY << 8) | ((B_VEMPTY + 8) << 16) | (B_VEMPTY << 24);
        mbar_wait_sleep(bar + ((LASTB >> (8 * kt)) & 255), kt == 2);
      }
      if (!first) mbar_wait_sleep(bar + B_GEMPTY + 8 * stage, phase);
      const uint32_t fb = bar + B_GFULL + 8 * stage;
      const uint32_t sa = sbase + stage * G_STAGE_BYTES;
      mbar_expect_tx(fb, G_STAGE_BYTES);
      tma_load_2d(sa, ma, fb, kt * 64, m_tile * 128);
      tma_load_3d(sa + G_A_BYTES, mb, fb, 0, kt * 64, group * 8 + pass * 4);
      if (++stage == G_STAGES) { stage = 0; phase ^= 1; }
      {
        const int b = maps.id[blockIdx.x][1];
        if (it == 1 && kt == (b & 7))
          asm volatile("cp.async.bulk.prefetch.tensor.3d.L2.global.tile [%0, {%1, %2, %3}];" ::"l"(&maps.b[2]), "r"(0),
                       "r"((b & 15) * 64), "r"((b >> 4) * 8 + pass * 4)
                       : "memory");
      }
      if (pass && it == 0 && kt == G_STAGES - 1) {
#pragma unroll 1
        for (int i = 0; i < 12; i++) {
          asm volatile("mbarrier.inval.shared::cta.b64 [%0];" ::"r"(bar + B_KFULL + 8 * i) : "memory");
          mbar_init(bar + B_KFULL + 8 * i, 1 + ((i >> 1) & 1));
        }
        fence_proxy_async();
      }
    }
  }
}

__device__ __noinline__ void publisher(uint32_t bar, int lane, uint32_t nsrc) {
  uint32_t done = 0;
  CLK_DECL
#pragma unroll 1
  for (uint32_t spins = 0; done < nsrc && spins < (1u << 20); spins++) {
    CLK_SAMPLE
    uint32_t v = 0;
    if (lane < CNT_N)
      asm volatile("atom.acquire.cta.shared.exch.b32 %0, [%1], 0;" : "=r"(v) : "r"(bar + B_PEND + 4 * lane) : "memory");
    done += __shfl_sync(0xffffffffu, v, CNT_DONE);
    if (lane == CNT_DONE) v = 0;
    if (done == nsrc && lane < CNT_DONE) {
      uint32_t w;
      asm volatile("atom.acquire.cta.shared.exch.b32 %0, [%1], 0;" : "=r"(w) : "r"(bar + B_PEND + 4 * lane) : "memory");
      v += w;
    }
    if (v && lane == 0) { TD(0) }
    if (v) cnt_signal_release(lane, v);
    if (v && lane == 0) { TD(1) }
    if (!__any_sync(0xffffffffu, v != 0)) __nanosleep(200);
  }
  CLK_END
  __threadfence();
  __syncwarp();
}

__device__ __forceinline__ void gate_rows(const Maps& maps, uint32_t sbase, int w48, int w12, int lane) {
  const uint32_t buf = sbase + w12 * 16384, gb = sbase + BAR_OFF + 768 + w12 * 16;
  if (lane == 0) {
    mbar_init(gb, 1);
    mbar_init(gb + 8, 1);
    fence_barrier_init();
    for (int i = 0; i < 2; i++) {
      mbar_expect_tx(gb + 8 * i, 8192);
      bulk_load(buf + i * 8192, maps.x + (size_t)(w48 + 48 * i) * 4 * DM, 8192, gb + 8 * i);
    }
  }
  __syncwarp();
  uint4 wv[4];
#pragma unroll
  for (int i = 0; i < 4; i++) wv[i] = __ldg(reinterpret_cast<const uint4*>(maps.gate_w + (i * 32 + lane) * 8));
  int it = 0;
#pragma unroll 1
  for (int row = w48 * 4; row < S_LEN; row += 48 * 4, it++) {
    mbar_wait(gb + 8 * (it & 1), (it >> 1) & 1);
    uint4 xv[4][4];
#pragma unroll
    for (int r = 0; r < 4; r++)
#pragma unroll
      for (int i = 0; i < 4; i++) xv[r][i] = lds128(buf + (it & 1) * 8192 + r * 2048 + (i * 32 + lane) * 16);
    float d[2][4];
#pragma unroll
    for (int pr = 0; pr < 2; pr++) {
      d[pr][0] = d[pr][1] = d[pr][2] = d[pr][3] = 0.f;
      auto acc = [&](uint32_t a0, uint32_t a2, uint32_t b0, uint32_t b2, uint32_t w0, uint32_t w2) {
        asm volatile(
            "mma.sync.aligned.m16n8k16.row.col.f32.bf16.bf16.f32 {%0, %1, %2, %3}, {%4, %5, %6, %7}, {%8, %8}, "
            "{%0, %1, %2, %3};"
            : "+f"(d[pr][0]), "+f"(d[pr][1]), "+f"(d[pr][2]), "+f"(d[pr][3])
            : "r"(mul_bf2(a0, w0)), "r"(mul_bf2(b0, w0)), "r"(mul_bf2(a2, w2)), "r"(mul_bf2(b2, w2)), "r"(0x3f803f80u));
      };
#pragma unroll
      for (int i = 0; i < 4; i++) {
        acc(xv[2 * pr][i].x, xv[2 * pr][i].y, xv[2 * pr + 1][i].x, xv[2 * pr + 1][i].y, wv[i].x, wv[i].y);
        acc(xv[2 * pr][i].z, xv[2 * pr][i].w, xv[2 * pr + 1][i].z, xv[2 * pr + 1][i].w, wv[i].z, wv[i].w);
      }
    }
    float sum = (lane & 2) ? ((lane & 1) ? d[1][2] : d[1][0]) : ((lane & 1) ? d[0][2] : d[0][0]);
#pragma unroll
    for (int off = 16; off >= 4; off >>= 1) sum += __shfl_xor_sync(0xffffffffu, sum, off);
    if (lane < 4) g_gate[row + lane] = bf16_round(rcp(1.0f + __expf(-bf16_round(sum))));
    if (lane == 0 && row + 2 * 48 * 4 < S_LEN) {
      mbar_expect_tx(gb + 8 * (it & 1), 8192);
      bulk_load(buf + (it & 1) * 8192, maps.x + (size_t)(row + 2 * 48 * 4) * DM, 8192, gb + 8 * (it & 1));
    }
  }
}

constexpr float Q_SCALE = 0.08838834764831845f * 1.4426950408889634f;
__device__ __forceinline__ uint32_t qkv_consumer(const Maps& maps, uint32_t smem0, uint32_t sn, uint32_t (&p)[32]) {
  PHASE_PROLOGUE
  float acc[128];
#pragma unroll
  for (int i = 0; i < 128; i++) asm volatile("mov.b32 %0, 0;" : "=f"(acc[i]));
  uint32_t stage = 0, phase = 0, prev_stage = 0;
  const uint32_t stg = sbase + G_STG_OFF + wg * 18432;
  const int st_row = warp * 16 + (lane & 7) + ((lane >> 3) & 1) * 8;
  const int st_cb = lane >> 4;
  uint32_t pend[32];
  int m_tile, group;
  qkv_tile(maps, 0, m_tile, group);
  auto put_box = [&](uint32_t buf, const uint32_t* v) {
#pragma unroll
    for (int jp = 0; jp < 4; jp++) {
      const int chunk = jp * 2 + st_cb;
      const uint32_t addr = buf + st_row * 128 + ((chunk ^ (st_row & 7)) << 4);
      stmatrix_x4(addr, v[jp * 4], v[jp * 4 + 1], v[jp * 4 + 2], v[jp * 4 + 3]);
    }
  };
  GT(gti++)
#pragma unroll
  for (int i = 0; i < 32; i++) pend[i] = 0;
#pragma unroll 1
  for (int it = 0;; it++) {
    const int nk = it == 2 ? 16 : 8;
#pragma unroll 1
    for (int kt = 0; kt < nk; kt++) {
      mbar_wait((bar + B_GFULL) + 8 * stage, phase);
      GT(gti++)
      const uint64_t da0 = make_desc(sbase + stage * G_STAGE_BYTES + wg * 8192, 16, 1024, DESC_SW128);
      const uint64_t db0 = make_desc(sbase + stage * G_STAGE_BYTES + G_A_BYTES, 8192, 1024, DESC_SW128);
      asm volatile("{\n.reg .pred p;\nsetp.ne.u32 p, %0, 0;\n@p bar.sync 3, 256;\n}\n" ::"r"((uint32_t)(wg && kt == nk - 1))
                   : "memory");
      wgmma_fence();
#pragma unroll
      for (int kk = 0; kk < 4; kk++) {
        wgmma_m64n256_ss_tb(acc, desc_add(da0, kk * 2), desc_add(db0, kk * 128), (kt | kk) != 0);
      }
      wgmma_commit();
      asm volatile("{\n.reg .pred p;\nsetp.ne.u32 p, %0, 0;\n@p bar.arrive 3, 256;\n}\n" ::"r"((uint32_t)(!wg && kt == nk - 1))
                   : "memory");
      const uint32_t when = it == 0 ? 0 : wg ? 0xAA : 0x55;
      if ((when >> kt) & 1) {
        const int c = kt >> 1;
        st_wait(bar, wg, sn - (it + c == 1 ? 1 : 2));
        const uint32_t buf = stg + (c & 1) * 8192;
        switch (c) {
          case 0: put_box(buf, p); break;
          case 1: put_box(buf, p + 16); break;
          case 2: put_box(buf, pend); break;
          default: put_box(buf, pend + 16); break;
        }
        st_post(bar, wg, wtid, sn, it + c == 5 ? ST_BOX1P : ST_BOX1, it - 1, buf, group * 256 + c * 64,
                m_tile * 128 + wg * 64, c == 3 ? CNT_KV + (sn > 8) : -1);
        sn++;
      }
      wgmma_wait<1>();
      mbar_arrive_if((bar + B_GEMPTY) + 8 * prev_stage, wtid == 32 && kt > 0);
      prev_stage = stage;
      if (++stage == G_STAGES) { stage = 0; phase ^= 1; }
    }
    wgmma_wait<0>();
    fence_regs(acc);
    GT(gti++)
    mbar_arrive_if((bar + B_GEMPTY) + 8 * prev_stage, wtid == 32);
    if (it == G_NTILES - 1) break;
#pragma unroll
    for (int j = 0; j < 32; j++) {
      p[j] = pack_bf16(acc[2 * j], acc[2 * j + 1]);
      pend[j] = pack_bf16(acc[64 + 2 * j], acc[64 + 2 * j + 1]);
    }
  }
  ST(19)
  st_wait(bar, wg, sn - 1);
  mbar_wait(bar + B_GEMPTY, 1);
#pragma unroll
  for (int j = 0; j < 32; j++) pend[j] = pack_bf16(acc[2 * j] * Q_SCALE, acc[2 * j + 1] * Q_SCALE);
  put_box(sbase + wg * 8192, pend);
  put_box(sbase + 16384 + wg * 8192, pend + 16);
#pragma unroll
  for (int j = 0; j < 32; j++) p[j] = pack_bf16(acc[64 + 2 * j] * Q_SCALE, acc[65 + 2 * j] * Q_SCALE);
  put_box(stg, p);
  put_box(stg + 8192, p + 16);
  st_post(bar, wg, wtid, sn, ST_PEER, 0, stg, sn >> 4, 0, 0);
  sn++;
  GT(gti++)
  return sn;
}

constexpr int A_TILE = 128 * 128 * 2;
constexpr int A_Q_OFF = 0;
constexpr int A_K_OFF = 2 * A_TILE;
constexpr int A_V_OFF = 4 * A_TILE;
constexpr int A_O_OFF = 6 * A_TILE;

constexpr uint32_t A_STEPS = 17;
__device__ __forceinline__ int item_m(uint32_t it) { return it & 15; }
__device__ __forceinline__ int item_h(uint32_t it) { return it >> 4; }

constexpr int C_H0 = 16, C_U = C_H0 + 4096 + 112, C_SLOT = C_U + 4096;
constexpr int C_H1 = 2 * C_SLOT + 80;
constexpr int C_X_OFF = C_H1 + 4096 + 48;

__device__ __forceinline__ uint32_t item_of(const Maps& maps, uint32_t r) {
  const uint32_t b = maps.id[blockIdx.x & 127][1];
  return (b >> 4) * 64 + r * 16 + ((b ^ ((r & 1) * 15)) & 15);
}

constexpr uint32_t C_SIDE = 48;
__device__ __forceinline__ uint32_t conv_first(const Maps& maps) {
  const uint32_t b = maps.id[blockIdx.x & 127][1];
  return (b >> 4) * 128 + (b & 15);
}

__device__ __forceinline__ void conv_consumer(const Maps& maps, uint32_t smem0, uint32_t first, uint32_t step,
                                              uint32_t end) {
  PHASE_PROLOGUE
  const uint32_t full = bar + B_CFULL + wg * 16;
  const uint32_t ca = sbase + (wg ? A_V_OFF + A_TILE : A_Q_OFF);
  const int w4 = __shfl_sync(0xffffffffu, warp, 0);
  auto fetch = [&](uint32_t c, uint32_t slot) {
    if (w4 == 2 && c < end) {
      if (elect_one()) {
        const uint32_t sb = ca + slot * C_SLOT, fb = full + 8 * slot;
        const uint64_t pol = policy_evict_first();
        mbar_expect_tx(fb, 2 * 4096);
        bulk_load_hint(sb + C_H0, maps.ssm_k + (size_t)c * S_LEN, 4096, fb, pol);
        bulk_load_hint(sb + C_U, g_kvT + (size_t)c * S_LEN, 4096, fb, pol);
      }
    }
  };
  auto shift_h = [&](uint32_t so) {
    const uint32_t a = ca + so + C_H0 + wtid * 16;
#pragma unroll
    for (int i = 0; i < 2; i++) {
      uint32_t p;
      const uint4 v = lds128(a + i * 2048);
      asm volatile("ld.shared.u32 %0, [%1];" : "=r"(p) : "r"(a + i * 2048 - 4));
      sts128(ca + C_H1 + wtid * 16 + i * 2048, make_uint4(__byte_perm(p, v.x, 0x5432), __byte_perm(v.x, v.y, 0x5432),
                                                      __byte_perm(v.y, v.z, 0x5432), __byte_perm(v.z, v.w, 0x5432)));
    }
  };
  if (wtid == 96 && wg) { TD(15) }
  fetch(first, 0);
  if (wtid < 17)
    sts128(ca + (wtid >> 3) * C_SLOT + (wtid & 7 ? 4096 + (wtid & 7) * 16 : (wtid & 16) * 4), make_uint4(0, 0, 0, 0));
  fence_proxy_async();
  const uint32_t ha = ca + ((lane & 4) ? C_H1 : C_H0) + 4 * ((lane & 3) - (lane >> 3)) + w4 * 256;
  const uint32_t ua = ca + C_U + w4 * 256 + (lane >> 4) * 1024 + (lane & 15) * 16;
  const uint32_t xa = ca + C_X_OFF + lane * 8, xw = xa + w4 * 3072;
  uint32_t xg[3];
#pragma unroll
  for (int k = 0; k < 3; k++) {
    const int w = (w4 + k + 1) & 3;
    xg[k] = xa + (w * 12 + w4 - w - (w < w4 ? 1 : 0)) * 256;
  }
  const bool pp = step != 16;
  uint32_t h[2][16];
  const uint32_t hs = (lane & 4) ? 0 : C_SLOT;
  auto load_h = [&](uint32_t so, int a) {
#pragma unroll
    for (int i = 0; i < 16; i++)
      asm volatile("ld.shared.u32 %0, [%1];"
                   : "=r"(h[a & 1][i])
                   : "r"(ha + so + 1024 * a + 32 * (i >> 2) + (i & 1) * 128 + (~i & 2) * 8));
  };
  mbar_wait(full, 0);
  named_bar_sync(1 + wg, 128);
  shift_h(0);
  named_bar_sync(1 + wg, 128);
  fetch(first + step, 1);
  load_h(0, 0);
  load_h(0, 1);
  mbar_wait(bar + B_OFREE, 0);
  mbar_wait(bar + B_OFREE + 8, 0);
  uint32_t n = 0, ch = first;
  for (; ch < end; n++, ch += step) {
    CT(0)
    const uint32_t so = (n & 1) * C_SLOT, ho = (n & 1) * hs;
    uint32_t db = (uint32_t)make_desc(ca + so + C_U - 16, 16, 0, 0);
    asm volatile("" : "+r"(db));
    uint32_t dsk = __ldg(reinterpret_cast<const unsigned short*>(maps.ssm_D) + (ch | (lane & rt_zero)));
    float d[4][32], own[16];
    auto mma = [&](int a) {
      wgmma_fence();
#pragma unroll
      for (int c = a; c < 4; c++)
#pragma unroll
        for (int b = 0; b < 4; b++)
          wgmma_m64n64_rs(d[c], &h[a & 1][4 * b], (8ull << 32) | (db + 64 * (c - a) - 2 * b), (a | b) != 0);
      wgmma_commit();
    };
    auto put = [&](int c) {
      fence_regs(d[c]);
#pragma unroll
      for (int e = 0; e < 2; e++) {
        if (c == 0) asm volatile("mov.b32 %0, %1;" : "=f"(own[e]) : "f"(d[c][e]));
        else own[4 * c + e] += d[c][e];
        own[4 * c + 2 + e] = d[c][4 + e] + d[c][2 + e];
        if (c < 3) asm volatile("mov.b32 %0, %1;" : "=f"(own[4 * c + 4 + e]) : "f"(d[c][30 + e]));
      }
#pragma unroll
      for (int j = 1; j < 4; j++)
        asm volatile("{\n.reg .pred p;\nsetp.lt.s32 p, %3, 4;\n@p st.shared.v2.u32 [%0], {%1, %2};\n}\n" ::"r"(
                         xw + (3 * c + j - 1) * 256),
                     "r"(pack_bf16(d[c][8 * j] + d[c][8 * j - 2], d[c][8 * j + 1] + d[c][8 * j - 1])),
                     "r"(pack_bf16(d[c][8 * j + 4] + d[c][8 * j + 2], d[c][8 * j + 5] + d[c][8 * j + 3])),
                     "r"(c < 3 ? 0 : w4 + j)
                     : "memory");
    };
    named_bar_sync(pp ? 4 + wg : 1 + wg, pp ? 256 : 128);
    CT(1)
    mma(0);
    mma(1);
    wgmma_wait<1>();
    load_h(ho, 2);
    put(0);
    mma(2);
    CT(2)
    wgmma_wait<1>();
    load_h(ho, 3);
    put(1);
    mma(3);
    asm volatile("{\n.reg .pred p;\nsetp.ne.u32 p, %1, 0;\n@p bar.arrive %0, 256;\n}\n" ::"r"(5 - wg), "r"((uint32_t)pp) : "memory");
    CT(3)
    uint32_t sk[8];
    asm volatile("ldmatrix.sync.aligned.m8n8.x4.trans.shared.b16 {%0, %1, %2, %3}, [%4];"
                 : "=r"(sk[0]), "=r"(sk[1]), "=r"(sk[2]), "=r"(sk[3])
                 : "r"(ua + so));
    asm volatile("ldmatrix.sync.aligned.m8n8.x4.trans.shared.b16 {%0, %1, %2, %3}, [%4];"
                 : "=r"(sk[4]), "=r"(sk[5]), "=r"(sk[6]), "=r"(sk[7])
                 : "r"(ua + so + 2048));
    mbar_wait(full + 8 * (~n & 1), (((n + 1) >> 1) & 1) ^ (ch + step < end ? 0 : 1));
    named_bar_sync(1 + wg, 128);
    shift_h(C_SLOT - so);
    wgmma_wait<1>();
    put(2);
    uint32_t dep = 0;
#pragma unroll
    for (int i = 0; i < 8; i++) dep |= sk[i] = mul_bf2(sk[i], dsk | (dsk << 16));
    CT(4)
    wgmma_wait<0>();
    put(3);
    named_bar_sync((1 + wg) | (dep & rt_zero), 128);
    CT(5)
    fetch(ch + 2 * step, n & 1);
    if (wtid == 96 && n) note(bar, CNT_Y2 + (((ch - step) & 127) >= 112));
    uint2 q[12];
#pragma unroll
    for (int i = 0; i < 12; i++) {
      if (i >= 3) {
        asm volatile("ld.shared.v2.u32 {%0, %1}, [%2];" : "=r"(q[i].x), "=r"(q[i].y) : "r"(xg[i % 3] + (i / 3) * 768));
      } else {
        q[i] = make_uint2(0, 0);
        asm volatile("{\n.reg .pred p;\nsetp.gt.s32 p, %3, 2;\n@p ld.shared.v2.u32 {%0, %1}, [%2];\n}\n"
                     : "+r"(q[i].x), "+r"(q[i].y)
                     : "r"(xg[i]), "r"(w4 + i));
      }
    }
    load_h(hs - ho, 0);
    load_h(hs - ho, 1);
    CT(6)
    uint32_t* dst = reinterpret_cast<uint32_t*>(g_y2T + (size_t)ch * S_LEN) + 64 * w4 + (lane ^ 28);
#pragma unroll
    for (int f = 0; f < 4; f++) {
#pragma unroll
      for (int k = 0; k < 3; k++) {
        own[4 * f] += bf_lo(q[3 * f + k].x);
        own[4 * f + 1] += bf_hi(q[3 * f + k].x);
        own[4 * f + 2] += bf_lo(q[3 * f + k].y);
        own[4 * f + 3] += bf_hi(q[3 * f + k].y);
      }
#pragma unroll
      for (int i = 0; i < 2; i++) {
        dst[256 * f + 32 * i] = add_bf2(pack_bf16(own[4 * f + 2 * i], own[4 * f + 2 * i + 1]), sk[2 * f + i]);
      }
    }
    CT(7)
  }
  named_bar_sync(1 + wg, 128);
  if (wtid == 96 && wg) { TD(8) }
  if (wtid == 96) cnt_signal_release(CNT_Y2 + (((ch - step) & 127) >= 112), 1);
  if (wtid == 64) note(bar, CNT_DONE);
  if (wtid == 96 && wg) { TD(9) }
}

__device__ __forceinline__ void attn_producer(const Maps& maps, uint32_t sbase, int pass, bool dry) {
  const uint32_t bar = sbase + BAR_OFF;
  const uint32_t q_full = bar + B_QFULL, q_empty = bar + B_QEMPTY;
  const uint32_t k_full = bar + B_KFULL, k_empty = bar + B_KEMPTY, v_full = bar + B_VFULL, v_empty = bar + B_VEMPTY;
  int ndrained = 0;
  auto wait = [&](uint32_t b, uint32_t par) {
    if (!dry) mbar_wait_sleep(b, par);
  };
  auto drained = [&](int upto) {
#pragma unroll 1
    for (; ndrained <= upto; ndrained++) wait(bar + B_GEMPTY + 8 * ndrained, 1);
  };
  uint32_t st = 0, ph = 1, vs = 0, vp = 1;
  int pend_j = -1, pend_h = 0;
  PT_DECL
  cnt_wait(CNT_KV + pass, dry ? 0 : 512);
  drained(1);
  if (!dry) {
    mbar_arrive(q_full);
    mbar_expect_tx(q_full + 8, A_TILE);
  }
  mbar_arrive_cluster_if(bar + B_QPEER, ~blockIdx.x & 1, !dry);
#pragma unroll 1
  for (int round = dry; round < 3; round++) {
    const uint32_t item = item_of(maps, round);
    const int m = round == 2 ? -1 : dry ? 0 : item_m(item), h = (item >> 6) * 4 + round * 2;
    const int tpost = m >= 3 ? m - 1 : m;
#pragma unroll 1
    for (int t = m < 0 ? -1 : 0; t <= m; t++) {
      const int j = (t < m && round) ? m - 1 - t : t;
      if (t >= 0) {
        drained(1 + st);
        wait(k_empty + 8 * st, ph);
        if (!dry) {
          PT
          mbar_expect_tx(k_full + 8 * st, A_TILE);
          tma_load_3d(sbase + A_K_OFF + st * A_TILE, &maps.k, k_full + 8 * st, 0, j * 128, h);
        }
        if (++st == 2) { st = 0; ph ^= 1; }
      }
      if (pend_j >= 0) {
        drained(3);
        wait(v_empty + 8 * vs, vp);
        if (!dry) {
          mbar_expect_tx(v_full + 8 * vs, A_TILE);
          tma_load_3d(sbase + A_V_OFF + (vs ^ 1) * A_TILE, &maps.v, v_full + 8 * vs, 0, pend_j * 128, pend_h);
        }
        if (++vs == 2) { vs = 0; vp ^= 1; }
      }
      pend_j = j;
      pend_h = h;
      if (t == tpost && round == 1) {
        if (pass) {
          cnt_wait(CNT_PREP + 1, dry ? 0 : 516);
          cnt_wait(CNT_CTX, dry ? 0 : 2 * A_ITEMS);
          asm volatile("cp.async.bulk.prefetch.L2.global [%0], 4096;" ::"l"(maps.ssm_k + (size_t)conv_first(maps) * S_LEN));
          if (!dry)
            asm volatile("cp.async.bulk.prefetch.L2.global [%0], 4096;" ::"l"(g_kvT + (size_t)conv_first(maps) * S_LEN));
        }
        wait(q_empty, 0);
        if (!dry) mbar_arrive(q_full);
      }
    }
  }
}

__device__ __forceinline__ uint32_t attn_consumer(const Maps& maps, uint32_t smem0, uint32_t sn, uint32_t (&p)[32]) {
  PHASE_PROLOGUE
  float s[64], o[64], e[32];
  const uint32_t q_full = bar + B_QFULL, q_empty = bar + B_QEMPTY;
  const uint32_t k_full = bar + B_KFULL, k_empty = bar + B_KEMPTY, v_full = bar + B_VFULL;
  uint32_t dep = 0;
  constexpr int MIDJ = 5;
  float l0 = 0.f, l1 = 0.f, b0 = 0.f, b1 = 0.f;
  const int sched_own = 4 + wg, sched_other = 5 - wg;

  const uint32_t qd0 = (uint32_t)make_desc(sbase + A_Q_OFF + wg * 8192, 16, 0, 0);
  const uint32_t kd0 = (uint32_t)make_desc(sbase + A_K_OFF, 16, 0, 0);
  const uint32_t vd0 = (uint32_t)make_desc(sbase + A_V_OFF, 16384, 0, 0);
  constexpr uint64_t DHI = DESC_SW128 | ((uint64_t)(1024 >> 4) << 32);
  constexpr uint32_t DST = A_TILE >> 4;
  auto issue_qk = [&](uint32_t qd, uint32_t kd, uint32_t z = 0) {
#pragma unroll
    for (int kk = 0; kk < 8; kk++) {
      const uint32_t off = ((kk >> 2) * 16384 + (kk & 3) * 32) >> 4;
      wgmma_m64n128_ss(s, DHI | (qd + off), DHI | (kd + off), kk ? 1 : z);
    }
    wgmma_commit();
  };
  auto issue_pv = [&](uint32_t vd, bool accumulate, int nk) {
#pragma unroll
    for (int kk = 0; kk < 8; kk++) {
      if (kk < nk)
        wgmma_m64n128_rs_tb(o, p[4 * kk], p[4 * kk + 1], p[4 * kk + 2], p[4 * kk + 3], DHI | (vd + kk * 128),
                            accumulate || (kk != 0));
    }
    wgmma_commit();
  };
  auto exp_lo = [&](float& a0, float& a1) {
#pragma unroll
    for (int j = 0; j < 8; j++) {
      e[4 * j] = ex2(s[4 * j]);
      e[4 * j + 1] = ex2(s[4 * j + 1]);
      e[4 * j + 2] = ex2(s[4 * j + 2]);
      e[4 * j + 3] = ex2(s[4 * j + 3]);
      a0 += e[4 * j];
      a0 += e[4 * j + 1];
      a1 += e[4 * j + 2];
      a1 += e[4 * j + 3];
      if (j == MIDJ) dep = (__float_as_uint(a0) | __float_as_uint(a1)) & rt_zero;
    }
  };
  auto pack_lo = [&]() {
#pragma unroll
    for (int j = 0; j < 16; j++) p[j] = pack_bf16(e[2 * j], e[2 * j + 1]);
  };
  auto finish_p = [&](float& a0, float& a1) {
    pack_lo();
#pragma unroll
    for (int j = 8; j < 16; j++) {
      const float e0 = ex2(s[4 * j]), e1 = ex2(s[4 * j + 1]), e2 = ex2(s[4 * j + 2]), e3 = ex2(s[4 * j + 3]);
      a0 += e0;
      a0 += e1;
      a1 += e2;
      a1 += e3;
      p[2 * j] = pack_bf16(e0, e1);
      p[2 * j + 1] = pack_bf16(e2, e3);
      if (j == 8 + MIDJ) dep = __float_as_uint(a0) & rt_zero;
    }
  };
  auto quad_sum = [&](float t) {
    t += __shfl_xor_sync(0xffffffffu, t, 1);
    return t + __shfl_xor_sync(0xffffffffu, t, 2);
  };
  auto write_o = [&](const float (&o)[64], float i0, float i1) {
    st_wait(bar, wg, sn - 1);
    const int st_row = warp * 16 + (lane & 7) + ((lane >> 3) & 1) * 8;
    const uint32_t so = sbase + A_O_OFF + wg * 18432 + st_row * 128;
#pragma unroll
    for (int j = 0; j < 16; j += 2)
      stmatrix_x4(so + (j >> 3) * 8192 + ((((j & 7) + (lane >> 4)) ^ (lane & 7)) << 4),
                  pack_bf16(o[4 * j] * i0, o[4 * j + 1] * i0), pack_bf16(o[4 * j + 2] * i1, o[4 * j + 3] * i1),
                  pack_bf16(o[4 * j + 4] * i0, o[4 * j + 5] * i0), pack_bf16(o[4 * j + 6] * i1, o[4 * j + 7] * i1));
  };
  auto store_o = [&](uint32_t r, int kind) {
    const uint32_t pass = sn >> 4, it = item_of(maps, 2 * pass + r);
    st_post(bar, wg, wtid, sn, kind, 2, sbase + A_O_OFF + wg * 18432, item_h(it) * 128,
            item_m(it) * 128 + wg * 64, CNT_CTX + pass);
    sn++;
  };
  auto mask_half = [&](float* sh) {
    const int u = warp * 16 + (lane >> 2) - (lane & 3) * 2;
#pragma unroll
    for (int j = 0; j < 8; j++) {
      if (8 * j > u) sh[4 * j] = -INFINITY;
      if (8 * j + 1 > u) sh[4 * j + 1] = -INFINITY;
      if (8 * j - 8 > u) sh[4 * j + 2] = -INFINITY;
      if (8 * j - 7 > u) sh[4 * j + 3] = -INFINITY;
    }
  };
  ST(0)
  mbar_wait(k_full, 0);
  ST(20)
  named_bar_sync(sched_own, 256);
  ST(21)
#pragma unroll
  for (int i = 0; i < 64; i++) asm volatile("mov.b32 %0, 0;" : "=f"(s[i]));
  wgmma_fence();
  issue_qk(qd0, kd0, rt_zero);
  named_bar_arrive(sched_other, 256);
  ST(36) ST(37) ST(38)
  ST(22)
#pragma unroll
  for (int i = 0; i < 64; i++) asm volatile("mov.b32 %0, 0;" : "=f"(o[i]));
  wgmma_wait<0>();
  fence_regs(s);
  mbar_arrive_if(k_empty, wtid == 32);
  uint32_t g = 0;
  uint32_t rnd = 0;
  int rem = item_m(item_of(maps, 0));
  uint32_t first = 1;
  uint32_t fl = 0;
#define redo (fl & 1)
#define shifted (fl & 2)
  float d0 = 0.f, d1 = 0.f;
  float pi0 = 1.f, pi1 = 1.f;
  ST(1)
  for (;;) {
    if (shifted) {
#pragma unroll
      for (int j = 0; j < 16; j++) {
        s[4 * j] -= d0;
        s[4 * j + 1] -= d0;
        s[4 * j + 2] -= d1;
        s[4 * j + 3] -= d1;
      }
    }
    if (rem == 0 && !redo) {
      mbar_arrive_if(q_empty + 8 * (rnd & 1), wtid == 96);
      rnd++;
      if (wg == 0) mask_half(s);
      else mask_half(s + 32);
    }
    for (;;) {
      const bool kill = rem == 0 && wg == 0;
      const uint32_t kd = kd0 + ((g + 1) & 1) * DST, vd = vd0 + (~g & 1) * DST;
      float a0 = 0.f, a1 = 0.f;
      exp_lo(a0, a1);
      fence_regs(e);
      const uint32_t kb = k_full + 8 * ((g + 1) & 1);
      const uint32_t kpar = ((((g + 1) >> 1) & 1) ^ (g == A_STEPS - 1 ? 1u : 0u)) | dep;
      if (!mbar_try(kb, kpar)) mbar_wait(kb, kpar | ((__float_as_uint(a0) | __float_as_uint(a1)) & rt_zero));
      wgmma_wait<0>();
      fence_regs(o);
      ST(g < 4 ? 24 + 3 * g : 39)
      if (kill) {
        mbar_arrive_if(kb + (B_VEMPTY - B_KFULL), wtid == 64 && !redo && g > 0);
        fence_regs(e);
        pack_lo();
#pragma unroll
        for (int j = 16; j < 32; j++) asm volatile("mov.u32 %0, 0;" : "=r"(p[j]));
        goto check;
      }
#pragma unroll
      for (int i = 32; i < 64; i++) asm volatile("" : "+f"(s[i])::"memory");
      mbar_arrive_if(kb + (B_VEMPTY - B_KFULL), wtid == 64 && !redo && g > 0);
      finish_p(a0, a1);
      if (__any_sync(0xffffffffu, !(mbar_try(v_full + 8 * (g & 1), ((g >> 1) & 1) | dep) &
                                    mbar_try(q_full + 8 * (rnd & 1), ((rnd >> 1) & 1) | dep)) ||
                                      !(a0 + a1 < 1.0995116e12f) || !(fminf(a0, a1) > (first ? 9.094947e-13f : -1.f)))) {
      check:
        bool bad = !(a0 + a1 < 1.0995116e12f);
        if (first) bad |= !(fminf(quad_sum(a0), quad_sum(a1)) > 9.094947e-13f);
        if (!redo && __any_sync(0xffffffffu, bad)) {
          d0 = d1 = first ? -INFINITY : 0.f;
#pragma unroll
          for (int j = 0; j < 16; j++) {
            if (j < 8 || !kill) {
              d0 = fmaxf(d0, fmaxf(s[4 * j], s[4 * j + 1]));
              d1 = fmaxf(d1, fmaxf(s[4 * j + 2], s[4 * j + 3]));
            }
          }
#pragma unroll
          for (int x = 1; x <= 2; x++) {
            d0 = fmaxf(d0, __shfl_xor_sync(0xffffffffu, d0, x));
            d1 = fmaxf(d1, __shfl_xor_sync(0xffffffffu, d1, x));
          }
          b0 += d0;
          b1 += d1;
          if (!first) {
            const float al0 = ex2(-d0), al1 = ex2(-d1);
            l0 *= al0;
            l1 *= al1;
#pragma unroll
            for (int j = 0; j < 16; j++) {
              o[4 * j] *= al0;
              o[4 * j + 1] *= al0;
              o[4 * j + 2] *= al1;
              o[4 * j + 3] *= al1;
            }
          }
          fl = 3;
          break;
        }
        mbar_wait(v_full + 8 * (g & 1), (g >> 1) & 1);
        mbar_wait(q_full + 8 * (rnd & 1), (rnd >> 1) & 1);
      }
      ST(g < 4 ? 25 + 3 * g : 39)
      named_bar_sync(sched_own, 256);
      ST(g < 4 ? 26 + 3 * g : 39)
      if (g == A_STEPS - 1) {
        if (first) write_o(o, pi0, pi1);
        fence_regs(o);
        wgmma_fence();
        issue_pv(vd, !first, 8);
        named_bar_arrive(sched_other, 256);
        if (first) store_o(0, ST_BOX2);
        pi0 = rcp(quad_sum(l0 + a0));
        pi1 = rcp(quad_sum(l1 + a1));
        goto done;
      }
      wgmma_fence();
      issue_qk(qd0 + (rnd & 1) * DST, kd);
      if (first && g) write_o(o, pi0, pi1);
      fence_regs(o);
      if (kill) {
        wgmma_fence();
        issue_pv(vd, !first, 4);
      } else {
        wgmma_fence();
        issue_pv(vd, !first, 8);
      }
      named_bar_arrive(sched_other, 256);
      fl &= 2;
      l0 += a0;
      l1 += a1;
      if (rem == 0 || first) {
        if (first && g) store_o(0, ST_BOX2);
        first = rem == 0;
        if (first) {
          pi0 = rcp(quad_sum(l0));
          pi1 = rcp(quad_sum(l1));
          l0 = l1 = b0 = b1 = 0.f;
          fl = 0;
          rem = item_m(item_of(maps, 1)) + 1;
        }
      }
      rem--;
      g++;
      wgmma_wait<1>();
      fence_regs(s);
      mbar_arrive_if(kb + (B_KEMPTY - B_KFULL), wtid == 32);
      ST(g + 1)
      if (rem == 0 || shifted) {
        d0 = b0;
        d1 = b1;
        break;
      }
    }
  }
done:
#undef redo
#undef shifted
  wgmma_wait<0>();
  fence_regs(o);
  mbar_arrive_if(bar + B_VEMPTY, wtid == 64);
  write_o(o, pi0, pi1);
  store_o(1, ST_BOX2W + (sn >> 4));
  ST(18)
  return sn;
}

constexpr int O_STAGES = 5;
constexpr int O_STAGE_BYTES = 32768;
constexpr int O_Y_OFF = 5 * 32768;
constexpr int O_X_OFF = 6 * 32768 + 2048;
constexpr int O_NK = HDIM / 64;

__device__ __forceinline__ uint32_t out_stage(uint32_t st) { return ((0x41230u >> (4 * st)) & 7) * O_STAGE_BYTES; }

__device__ __forceinline__ void out_producer(const Maps& maps, uint32_t sbase, bool dry) {
  const uint32_t bar = sbase + BAR_OFF;
  const uint32_t rank = blockIdx.x & 1;
  const int m_tile = maps.id[blockIdx.x][2] & 15, n_tile = maps.id[blockIdx.x][2] >> 4;
  uint32_t stage = 0, phase = 0;
  const int kx = dry ? 0 : 17 + (blockIdx.x >> 1) % 12;
#pragma unroll 1
  for (int ki = 0; ki < (dry ? 1 : O_NK); ki++) {
    const int kt = (ki & 14) * 4 + (ki >> 4) * 2 + (ki & 1);
    const uint32_t fb = bar + B_OFULL + 8 * stage, eb = bar + B_OEMPTY + 8 * stage;
    const uint32_t sa = sbase + out_stage(stage);
    if (ki < O_STAGES) {
      constexpr uint32_t LASTB = (B_KEMPTY + 8) | (B_KEMPTY << 8) | ((B_QEMPTY + 8) << 16) | ((B_VEMPTY + 8) << 24);
      if (ki > 0 && !dry) mbar_wait_sleep(bar + ((LASTB >> (8 * ki - 8)) & 255), (0x12 >> ki) & 1);
      mbar_arrive_cluster_if(eb, 0, !dry);
      mbar_arrive_cluster_if(eb, 1, !dry);
    }
    if (ki == (dry ? 0 : 16)) cnt_wait(CNT_CTX + 1, dry ? 0 : 2 * A_ITEMS);
    if (ki == kx) {
      if (!dry) {
        mbar_wait_sleep(bar + B_OFREE, 0);
        mbar_wait_sleep(bar + B_OFREE + 8, 0);
        mbar_expect_tx(bar + B_OY, 32768);
        tma_load_4d(sbase + O_X_OFF, &maps.ox, bar + B_OY, n_tile * 128, m_tile);
        tma_load_4d(sbase + O_X_OFF + 16384, &maps.ox, bar + B_OY, n_tile * 128 + 64, m_tile);
      }
    }
    if (!dry) {
      mbar_wait_sleep(eb, phase);
      mbar_expect_tx(fb, O_STAGE_BYTES);
      tma_load_2d_mc(sa + 16384 + rank * 8192, &maps.ob, fb, n_tile * 128 + rank * 64, kt * 64, (uint16_t)3);
      tma_load_4d(sa, &maps.oa, fb, kt * 64, m_tile);
    }
    if (++stage == O_STAGES) { stage = 0; phase ^= 1; }
  }
  if (!dry) mbar_wait_sleep(bar + B_OY2, 0);
}

__device__ __forceinline__ void out_side(const Maps& maps, uint32_t smem0, const float (&gv)[4]) {
  PHASE_PROLOGUE
  const int m_tile = maps.id[blockIdx.x][2] & 15, n_tile = maps.id[blockIdx.x][2] >> 4;
  const int w4 = __shfl_sync(0xffffffffu, warp, 0);
  if (w4 == 0) {
    if (elect_one()) {
      mbar_expect_tx(bar + B_OY, 32768 - 4096);
      TD(10)
      GS(0)
      cnt_wait(CNT_Y2, DM - 128);
      GS(1)
      TD(7)
      for (const uint32_t t = clock(); (uint32_t)clock() - t < (blockIdx.x & 14) * 200;) __nanosleep(32);
      TD(11)
      GS(2)
      fence_proxy_async();
      tma_load_2d(sbase + O_Y_OFF, &maps.y, bar + B_OY, m_tile * 128, n_tile * 128);
      tma_load_2d(sbase + O_Y_OFF + 16384, &maps.y, bar + B_OY, m_tile * 128 + 64, n_tile * 128);
    }
  }
  mbar_wait_sleep(bar + B_OY, 0);
  const int st_row = warp * 16 + (lane & 7) + ((lane >> 3) & 1) * 8;
  const int mrow = (lane & 7) + ((lane >> 4) & 1) * 8;
  const int mchunk = warp * 2 + ((lane >> 3) & 1);
  const uint32_t xrow = sbase + O_X_OFF + st_row * 128;
  const uint32_t yrow = sbase + O_Y_OFF + mrow * 128 + ((mchunk ^ (lane & 7)) << 4);
  uint32_t y[7][4], x[7][4], om[4];
#pragma unroll
  for (int i = 0; i < 4; i++) om[i] = pack_bf16(1.0f - gv[i], 1.0f - gv[i]);
  auto xa = [&](int h, int i) { return xrow + h * 8192 + (i >> 2) * 16384 + ((((i & 3) * 2 + (lane >> 4)) ^ (lane & 7)) << 4); };
  auto load = [&](int r, int h, int i) {
    ldsm4t(y[r], yrow + h * 16384 + i * 2048);
    asm volatile("ldmatrix.sync.aligned.m8n8.x4.shared.b16 {%0, %1, %2, %3}, [%4];"
                 : "=r"(x[r][0]), "=r"(x[r][1]), "=r"(x[r][2]), "=r"(x[r][3])
                 : "r"(xa(h, i)));
  };
  auto store = [&](int r, int h, int i, uint32_t om0, uint32_t om1) {
    stmatrix_x4(xa(h, i), mul_bf2(om0, mul_bf2(x[r][0], y[r][0])), mul_bf2(om1, mul_bf2(x[r][1], y[r][1])),
                mul_bf2(om0, mul_bf2(x[r][2], y[r][2])), mul_bf2(om1, mul_bf2(x[r][3], y[r][3])));
  };
  if (wtid == 0) { TD(12) GS(3) }
#pragma unroll 1
  for (int h = 0; h < 2; h++) {
#pragma unroll
    for (int i = 0; i < 7; i++) load(i, h, i);
#pragma unroll
    for (int i = 0; i < 7; i++) store(i, h, i, h ? om[2] : om[0], h ? om[3] : om[1]);
  }
  if (wtid == 0) { TD(4) GS(4) }
  if (w4 == 0) {
    if (elect_one()) {
      mbar_expect_tx(bar + B_OY2, 4096);
      cnt_wait(CNT_Y2 + 1, 128);
      GS(5)
      for (int i = 0; i < 2; i++)
        tma_load_2d(sbase + O_Y_OFF + i * 16384 + 112 * 128, &maps.y2, bar + B_OY2, m_tile * 128 + i * 64,
                    n_tile * 128 + 112);
    }
  }
  mbar_wait_sleep(bar + B_OY2, 0);
#pragma unroll
  for (int h = 0; h < 2; h++) load(h, h, 7);
#pragma unroll
  for (int h = 0; h < 2; h++) store(h, h, 7, om[2 * h], om[2 * h + 1]);
  __syncwarp();
  mbar_arrive_if(bar + B_OY + 8, lane == 0);
  if (wtid == 0) { TD(13) GS(6) }
#pragma unroll
  for (int i = 0; i < 4; i++) {
    const int h = i >> 1, c = i & 1;
    named_bar_sync(6 + i, 256);
    if (elect_one()) {
      fence_proxy_async();
      tma_store_4d(&maps.oc, sbase + O_X_OFF + c * 16384 + h * 8192 + w4 * 2048, n_tile * 128 + c * 64, 2 * w4,
                   2 * m_tile + h);
      tma_store_commit();
    }
  }
}

__device__ __forceinline__ void out_gemm(const Maps& maps, uint32_t smem0) {
  PHASE_PROLOGUE
  const int m_tile = maps.id[blockIdx.x][2] & 15;
  float acc[2][64];
  undef_regs(acc[0]);
  undef_regs(acc[1]);
  uint32_t stage = 0, phase = 0, prev_stage = 0;
  GT(gti++)
  const float* gp = g_gate + m_tile * 128 + warp * 2 + (lane >> 2) * 8;
  const float gv[4] = {__ldcg(gp), __ldcg(gp + 1), __ldcg(gp + 64), __ldcg(gp + 65)};
  if (wg == 1) {
    out_side(maps, smem0, gv);
    return;
  }
  constexpr uint64_t DHI = DESC_SW128 | ((uint64_t)(1024 >> 4) << 32);
#pragma unroll 1
  for (int kt = 0; kt < O_NK - 1; kt++) {
    uint32_t da = (uint32_t)make_desc(sbase + out_stage(stage), 16, 0, 0);
    uint32_t db = (uint32_t)make_desc(sbase + out_stage(stage) + 16384, 8192, 0, 0);
    asm volatile("" : "+r"(da), "+r"(db));
    mbar_wait(bar + B_OFULL + 8 * stage, phase);
    GT(gti++)
    constexpr int OWAIT = 2;
#pragma unroll
    for (int kk = 0; kk < 4; kk++) {
      wgmma_wait<OWAIT>();
      if (kk == OWAIT)
        mbar_arrive_cluster_if(bar + B_OEMPTY + 8 * prev_stage, wtid >> 6,
                               (wtid & 63) == 32 && kt > 0 && kt - 1 + O_STAGES < O_NK);
      wgmma_fence();
      wgmma_m64n128_ss_tb(acc[0], DHI | (da + kk * 2), DHI | (db + kk * 128), (kt | kk) != 0);
      wgmma_m64n128_ss_tb(acc[1], DHI | (da + 512 + kk * 2), DHI | (db + kk * 128), (kt | kk) != 0);
      wgmma_commit();
    }
    prev_stage = stage;
    if (++stage == O_STAGES) { stage = 0; phase ^= 1; }
  }
  {
    const uint32_t da = (uint32_t)make_desc(sbase + out_stage((O_NK - 1) % O_STAGES), 16, 0, 0);
    const uint32_t db = (uint32_t)make_desc(sbase + out_stage((O_NK - 1) % O_STAGES) + 16384, 8192, 0, 0);
    mbar_wait(bar + B_OFULL + 8 * ((O_NK - 1) % O_STAGES), ((O_NK - 1) / O_STAGES) & 1);
    GT(gti++)
#pragma unroll
    for (int h = 0; h < 2; h++) {
      wgmma_fence();
#pragma unroll
      for (int kk = 0; kk < 4; kk++)
        wgmma_m64n128_ss_tb(acc[h], DHI | (da + h * 512 + kk * 2), DHI | (db + kk * 128), 1);
      wgmma_commit();
    }
  }
  if (tid == 0) { TD(14) }
  const int st_row = warp * 16 + (lane & 7) + ((lane >> 3) & 1) * 8;
  const uint32_t rowa = sbase + O_X_OFF + st_row * 128;
  auto oa = [&](int i) { return rowa + (i >> 3) * 8192 + (i & 4) * 4096 + ((((i & 3) * 2 + (lane >> 4)) ^ (st_row & 7)) << 4); };
  uint32_t b[16][4];
  mbar_wait(bar + B_OY + 8, 0);
#pragma unroll
  for (int i = 0; i < 16; i++)
    asm volatile("ldmatrix.sync.aligned.m8n8.x4.shared.b16 {%0, %1, %2, %3}, [%4];"
                 : "=r"(b[i][0]), "=r"(b[i][1]), "=r"(b[i][2]), "=r"(b[i][3])
                 : "r"(oa(i)));
  uint32_t gg[4];
#pragma unroll
  for (int i = 0; i < 4; i++) gg[i] = pack_bf16(gv[i], gv[i]);
#pragma unroll
  for (int i = 0; i < 16; i++) {
    const int h = i >> 3;
    if (i == 0) wgmma_wait<1>();
    if (i == 8) wgmma_wait<0>();
    if (i % 8 == 0) fence_regs(acc[h]);
    const float* a = acc[h] + 8 * (i & 7);
    const uint32_t gg0 = gg[2 * h], gg1 = gg[2 * h + 1];
    stmatrix_x4(oa(i), fma_bf2(gg0, pack_bf16(a[0], a[1]), b[i][0]), fma_bf2(gg1, pack_bf16(a[2], a[3]), b[i][1]),
                fma_bf2(gg0, pack_bf16(a[4], a[5]), b[i][2]), fma_bf2(gg1, pack_bf16(a[6], a[7]), b[i][3]));
    if (i % 4 == 3) named_bar_arrive(6 + i / 4, 256);
  }
  GT(gti++)
}

__device__ __noinline__ void leave_kernel() {
  if (atomicAdd(g_cnt + CNT_DONE * 32, 1u) == 2 * gridDim.x - 1) {
    for (int i = 0; i < CNT_N; i++) g_cnt[i * 32] = 0;
  }
}

__device__ __noinline__ void side_jobs(const Maps& maps, uint32_t sbase) {
  const int w12 = __shfl_sync(0xffffffffu, threadIdx.x >> 5, 0);
  gate_rows(maps, sbase, (blockIdx.x - 128) * 12 + w12, w12, threadIdx.x & 31);
  fence_proxy_async();
  __syncthreads();
  if (threadIdx.x == 320) cnt_signal_release(CNT_PREP + 1, 1);
}

__global__ void __launch_bounds__(384, 1) fused_kernel(const __grid_constant__ Maps maps) {
  extern __shared__ __align__(1024) uint8_t smem_raw[];
  {
    const uint32_t sbase = __shfl_sync(0xffffffffu, smem_u32(smem_raw), 0);
    const uint32_t bar = sbase + BAR_OFF;
    const int tid = threadIdx.x;
    TL(0, 0) LT(0, 0)
    if (__shfl_sync(0xffffffffu, tid >> 5, 0) == 1 && blockIdx.x < 128) {
      if (elect_one()) {
        for (int i = 0; i < G_STAGES; i++) mbar_init(bar + B_GFULL + 8 * i, 1);
        fence_barrier_init();
        qkv_producer(maps, sbase, 0, true);
      }
    }
    if (tid == 0) {
      for (int i = 0; i < G_STAGES; i++) {
        mbar_init(bar + B_GEMPTY + 8 * i, 2);
        mbar_init(bar + B_SFULL + 8 * i, 4);
        mbar_init(bar + B_SFREE + 8 * i, 1);
      }
      for (int i = 0; i < 2; i++) {
        mbar_init(bar + B_OFREE + 8 * i, 1);
        mbar_init(bar + B_QFULL + 8 * i, 1);
        mbar_init(bar + B_QEMPTY + 8 * i, 2);
        mbar_init(bar + B_KFULL + 8 * i, 1);
        mbar_init(bar + B_KEMPTY + 8 * i, 2);
        mbar_init(bar + B_VFULL + 8 * i, 1);
        mbar_init(bar + B_VEMPTY + 8 * i, 2);
      }
      for (int i = 0; i < O_STAGES; i++) {
        mbar_init(bar + B_OFULL + 8 * i, 1);
        mbar_init(bar + B_OEMPTY + 8 * i, 2);
      }
      mbar_init(bar + B_OY, 2);
      mbar_init(bar + B_OY2, 1);
      mbar_init(bar + B_OY + 8, 4);
      mbar_init(bar + B_QPEER, 1);
      for (int i = 0; i < 8; i++) mbar_init(bar + B_CFULL + 8 * i, 1);
      for (int i = 0; i < CNT_N; i++) asm volatile("st.shared.u32 [%0], 0;" ::"r"(bar + B_PEND + 4 * i) : "memory");
      fence_barrier_init();
    }
    __syncthreads();
    asm volatile("barrier.cluster.arrive.relaxed.aligned;" ::: "memory");
    if (blockIdx.x >= 128) side_jobs(maps, sbase);
  }
  uint32_t smem0 = smem_u32(smem_raw);
  PHASE_PROLOGUE
  const bool mainc = blockIdx.x < 128;
  TL(0, 1)

  if (wg != 2) {
    reg_alloc<232>();
    if (wg == 1) named_bar_arrive(4, 256);
    mbar_wait(bar + B_OFREE + 8, mainc);
    if (mainc) {
      uint32_t sn = 0, p[32];
#pragma unroll
      for (int i = 0; i < 32; i++) asm volatile("" : "=r"(p[i]));
#pragma unroll 1
      do {
        sn = qkv_consumer(maps, smem_u32(smem_raw), sn, p);
        LT(1 + 2 * (sn >> 4), 0)
        sn = attn_consumer(maps, smem_u32(smem_raw), sn, p);
        LT(2 + 2 * (sn >> 4), 0)
      } while (sn < 16);
    }
    asm volatile("barrier.cluster.wait.acquire.aligned;" ::: "memory");
    if (mainc && __shfl_sync(0xffffffffu, threadIdx.x, 0) < 128) {
      named_bar_arrive(3, 256);
    } else {
      named_bar_sync(3, 256);
      const uint32_t b2 = blockIdx.x * 2 + (threadIdx.x >> 7);
      const uint32_t first = __shfl_sync(0xffffffffu, mainc ? conv_first(maps) : (b2 - 255) * 128 - C_SIDE, 0);
      conv_consumer(maps, smem_u32(smem_raw), first, mainc ? 16 : 1, (first | 127) + 1 - (mainc ? C_SIDE : 0));
    }
    if (mainc) out_gemm(maps, smem_u32(smem_raw));
    tma_store_wait_read<0>();
    TL2(3, 2) LT(5, 128)
  } else {
    reg_dealloc<40>();
    asm volatile("barrier.cluster.wait.acquire.aligned;" ::: "memory");
    const int w = __shfl_sync(0xffffffffu, tid >> 5, 0) - 8;
    if (w < 2) {
      if (mainc) agent_warp(maps, smem_u32(smem_raw));
    } else {
      if (mainc && elect_one()) {
        const bool dry = w == 2;
#pragma unroll 1
        for (int pass = dry; pass < 2; pass++) {
          if (!dry) qkv_producer(maps, sbase, pass, false);
          attn_producer(maps, sbase, pass, dry);
        }
        out_producer(maps, sbase, dry);
      }
      if (!mainc && tid == 352) {
        cnt_wait(CNT_PREP, 256);
        mbar_arrive(bar + B_OFREE);
        mbar_arrive(bar + B_OFREE + 8);
      }
      __syncwarp();
      if (w == 2) publisher(bar, tid & 31, mainc ? 3 : 2);
      if ((tid & 31) == 0) leave_kernel();
    }
  }
}

__device__ __forceinline__ float ldf(const bf16* p) { return __bfloat162float(*p); }
__global__ void __launch_bounds__(256) plain_gemm(const bf16* A, const bf16* B, bf16* C, int k, int ldb, int n) {
  __shared__ float sa[16][65], sb[16][64];
  const int tx = threadIdx.x & 15, ty = threadIdx.x >> 4, m0 = blockIdx.y * 64, n0 = blockIdx.x * 64;
  float acc[4][4] = {};
  for (int k0 = 0; k0 < k; k0 += 16) {
    for (int i = threadIdx.x; i < 1024; i += 256) {
      sa[i & 15][i >> 4] = ldf(A + (size_t)(m0 + (i >> 4)) * k + k0 + (i & 15));
      sb[i >> 6][i & 63] = ldf(B + (size_t)(k0 + (i >> 6)) * ldb + n0 + (i & 63));
    }
    __syncthreads();
    for (int kk = 0; kk < 16; kk++)
      for (int i = 0; i < 4; i++)
        for (int j = 0; j < 4; j++) acc[i][j] += sa[kk][ty * 4 + i] * sb[kk][tx + 16 * j];
    __syncthreads();
  }
  for (int i = 0; i < 4; i++)
    for (int j = 0; j < 4; j++) C[(size_t)(m0 + ty * 4 + i) * n + n0 + tx + 16 * j] = __float2bfloat16_rn(acc[i][j]);
}
__global__ void __launch_bounds__(256) plain_attn(int half) {
  const int lane = threadIdx.x & 31, t = blockIdx.x * 8 + (threadIdx.x >> 5), c = blockIdx.y * HD + lane * 4;
  bf16* io = g_ctx + (size_t)t * HDIM + half * (HDIM / 2) + c;
  float q[4], o[4] = {}, m = -INFINITY, l = 0.f;
  for (int i = 0; i < 4; i++) q[i] = ldf(io + i) * 0.08838834764831845f;
  for (int j = 0; j <= t; j++) {
    float s = 0.f;
    for (int i = 0; i < 4; i++) s += q[i] * ldf(g_k + (size_t)j * (HDIM / 2) + c + i);
    for (int x = 16; x; x >>= 1) s += __shfl_xor_sync(0xffffffffu, s, x);
    const float mn = fmaxf(m, s), al = __expf(m - mn), p = __expf(s - mn);
    for (int i = 0; i < 4; i++) o[i] = o[i] * al + p * ldf(g_v + (size_t)j * (HDIM / 2) + c + i);
    l = l * al + p;
    m = mn;
  }
  for (int i = 0; i < 4; i++) io[i] = __float2bfloat16_rn(o[i] / l);
}
__global__ void __launch_bounds__(256) plain_gate(const bf16* x, const bf16* w) {
  const int lane = threadIdx.x & 31, t = blockIdx.x * 8 + (threadIdx.x >> 5);
  float s = 0.f;
  for (int i = lane; i < DM; i += 32) s += bf16_round(ldf(x + (size_t)t * DM + i) * ldf(w + i));
  for (int o = 16; o; o >>= 1) s += __shfl_xor_sync(0xffffffffu, s, o);
  if (lane == 0) g_gate[t] = bf16_round(1.0f / (1.0f + __expf(-bf16_round(s))));
}
__global__ void __launch_bounds__(256) plain_conv(const bf16* x, const bf16* k, const bf16* v, const bf16* shift_k,
                                                  const bf16* ssm_k, const bf16* ssm_D, bf16* out) {
  __shared__ float u[S_LEN], h[S_LEN];
  const int c = blockIdx.x;
  for (int t = threadIdx.x; t < S_LEN; t += 256) {
    float s = 0.f;
    for (int i = 3; i >= 0; i--)
      if (t >= i) s = bf16_round(s + bf16_round(ldf(k + (size_t)(t - i) * DM + c) * ldf(shift_k + c * 4 + i)));
    u[t] = bf16_round(s * ldf(v + (size_t)t * DM + c));
    h[t] = ldf(ssm_k + (size_t)c * S_LEN + t);
  }
  __syncthreads();
  for (int t = threadIdx.x; t < S_LEN; t += 256) {
    float y = 0.f;
    for (int i = 0; i <= t; i++) y += h[i] * u[t - i];
    y = bf16_round(bf16_round(y) + bf16_round(u[t] * ldf(ssm_D + c)));
    const float g = g_gate[t], b = bf16_round(ldf(x + (size_t)t * DM + c) * y);
    bf16* o = out + (size_t)t * DM + c;
    *o = __float2bfloat16_rn(bf16_round(g * ldf(o)) + bf16_round(bf16_round(1.0f - g) * b));
  }
}

typedef CUresult (*PFN_tmapEncode)(CUtensorMap*, CUtensorMapDataType, cuuint32_t, void*, const cuuint64_t*,
                                   const cuuint64_t*, const cuuint32_t*, const cuuint32_t*, CUtensorMapInterleave,
                                   CUtensorMapSwizzle, CUtensorMapL2promotion, CUtensorMapFloatOOBfill);
static PFN_tmapEncode s_encode = nullptr;

static void make_map_2d(CUtensorMap* m, const void* ptr, int rows, int cols, int box_rows,
                        CUtensorMapL2promotion prom = CU_TENSOR_MAP_L2_PROMOTION_L2_256B) {
  cuuint64_t dims[2] = {(cuuint64_t)cols, (cuuint64_t)rows};
  cuuint64_t strides[1] = {(cuuint64_t)cols * 2};
  cuuint32_t box[2] = {64, (cuuint32_t)box_rows};
  cuuint32_t es[2] = {1, 1};
  s_encode(m, CU_TENSOR_MAP_DATA_TYPE_BFLOAT16, 2, const_cast<void*>(ptr), dims, strides, box, es,
           CU_TENSOR_MAP_INTERLEAVE_NONE, CU_TENSOR_MAP_SWIZZLE_128B, prom,
           CU_TENSOR_MAP_FLOAT_OOB_FILL_NONE);
}
static void make_map_3d(CUtensorMap* m, const void* ptr, int rows, int cols, int box_rows, int box_chunks) {
  cuuint64_t dims[3] = {64, (cuuint64_t)rows, (cuuint64_t)(cols / 64)};
  cuuint64_t strides[2] = {(cuuint64_t)cols * 2, 128};
  cuuint32_t box[3] = {64, (cuuint32_t)box_rows, (cuuint32_t)box_chunks};
  cuuint32_t es[3] = {1, 1, 1};
  s_encode(m, CU_TENSOR_MAP_DATA_TYPE_BFLOAT16, 3, const_cast<void*>(ptr), dims, strides, box, es,
           CU_TENSOR_MAP_INTERLEAVE_NONE, CU_TENSOR_MAP_SWIZZLE_128B, CU_TENSOR_MAP_L2_PROMOTION_L2_256B,
           CU_TENSOR_MAP_FLOAT_OOB_FILL_NONE);
}

static void make_map_4d(CUtensorMap* m, const void* ptr, int rows, int cols, int b2, int groups) {
  cuuint64_t dims[4] = {(cuuint64_t)cols, 8, 8, (cuuint64_t)(rows / 64)};
  cuuint64_t strides[3] = {(cuuint64_t)cols * 16, (cuuint64_t)cols * 2, (cuuint64_t)cols * 128};
  cuuint32_t box[4] = {64, 8, (cuuint32_t)b2, (cuuint32_t)groups};
  cuuint32_t es[4] = {1, 1, 1, 1};
  s_encode(m, CU_TENSOR_MAP_DATA_TYPE_BFLOAT16, 4, const_cast<void*>(ptr), dims, strides, box, es,
           CU_TENSOR_MAP_INTERLEAVE_NONE, CU_TENSOR_MAP_SWIZZLE_128B, CU_TENSOR_MAP_L2_PROMOTION_L2_256B,
           CU_TENSOR_MAP_FLOAT_OOB_FILL_NONE);
}

static cudaLaunchConfig_t fused_cfg(cudaLaunchAttribute* at) {
  cudaLaunchConfig_t cfg = {};
  cfg.gridDim = dim3(132);
  cfg.blockDim = dim3(384);
  cfg.dynamicSmemBytes = SMEM_BYTES;
  cfg.stream = cudaStreamPerThread;
  at[0].id = cudaLaunchAttributeClusterDimension;
  at[0].val.clusterDim.x = 2;
  at[0].val.clusterDim.y = 1;
  at[0].val.clusterDim.z = 1;
  cfg.attrs = at;
  cfg.numAttrs = 1;
  return cfg;
}

extern "C" void kernel_launch(void* const* d_in, const int* in_sizes, int n_in, void* d_out, int out_size) {
  const bf16* x = (const bf16*)d_in[0];
  const bf16* ckv = (const bf16*)d_in[1];
  const bf16* wq = (const bf16*)d_in[2];
  const bf16* wuk = (const bf16*)d_in[3];
  const bf16* wuv = (const bf16*)d_in[4];
  const bf16* wo = (const bf16*)d_in[5];
  const bf16* bk = (const bf16*)d_in[7];
  const bf16* bv = (const bf16*)d_in[8];
  const bf16* shift_k = (const bf16*)d_in[9];
  const bf16* ssm_k = (const bf16*)d_in[10];
  const bf16* ssm_D = (const bf16*)d_in[11];
  const bf16* gate_w = (const bf16*)d_in[12];
  bf16* out = (bf16*)d_out;

  static void *pk = nullptr, *pv = nullptr, *pctx = nullptr, *pb = nullptr;
  static int max_clusters = 0;
  if (!s_encode) {
    void* fn = nullptr;
    cudaDriverEntryPointQueryResult qres;
    cudaGetDriverEntryPoint("cuTensorMapEncodeTiled", &fn, cudaEnableDefault, &qres);
    s_encode = (PFN_tmapEncode)fn;
    cudaGetSymbolAddress(&pk, g_k);
    cudaGetSymbolAddress(&pv, g_v);
    cudaGetSymbolAddress(&pctx, g_ctx);
    cudaGetSymbolAddress(&pb, g_y2T);
    cudaFuncSetAttribute(fused_kernel, cudaFuncAttributeMaxDynamicSharedMemorySize, SMEM_BYTES);
    cudaLaunchAttribute at[1];
    cudaLaunchConfig_t cfg = fused_cfg(at);
    if (cudaOccupancyMaxActiveClusters(&max_clusters, fused_kernel, &cfg) != cudaSuccess) max_clusters = 0;
  }

  Maps all = {};
  make_map_2d(&all.a[0], ckv, S_LEN, DC, 128);
  make_map_2d(&all.a[1], x, S_LEN, DM, 128);
  make_map_3d(&all.b[0], wuk, DC, HDIM, 64, 4);
  make_map_3d(&all.b[1], wuv, DC, HDIM, 64, 4);
  make_map_3d(&all.b[2], wq, DM, HDIM, 64, 4);
  make_map_2d(&all.c[0], pk, S_LEN, HDIM / 2, 64);
  make_map_2d(&all.c[1], pv, S_LEN, HDIM / 2, 64);
  make_map_3d(&all.k, pk, S_LEN, HDIM / 2, 128, 2);
  make_map_3d(&all.v, pv, S_LEN, HDIM / 2, 128, 2);
  make_map_2d(&all.c[2], pctx, S_LEN, HDIM, 64);
  all.ssm_k = ssm_k;
  all.ssm_D = ssm_D;
  make_map_4d(&all.oa, pctx, S_LEN, HDIM, 8, 2);
  make_map_4d(&all.ox, x, S_LEN, DM, 8, 2);
  make_map_2d(&all.ob, wo, HDIM, DM, 64);
  make_map_4d(&all.oc, out, S_LEN, DM, 2, 1);
  make_map_2d(&all.y, pb, DM, S_LEN, 112);
  make_map_2d(&all.y2, pb, DM, S_LEN, 16);

  make_map_2d(&all.bk, bk, S_LEN, DM, 35, CU_TENSOR_MAP_L2_PROMOTION_L2_128B);
  make_map_2d(&all.bv, bv, S_LEN, DM, 32, CU_TENSOR_MAP_L2_PROMOTION_L2_128B);
  for (int b = 0; b < 128; b++) {
    const int c = b >> 1, r = b & 1;
    const int G = c < 4 ? 0 : c < 36 ? (c - 4) % 8 : 1 + (c - 36) % 7;
    const int i = c < 4 ? 4 + c : c < 36 ? (c - 4) / 8 : 4 + (c - 36) / 7;
    all.id[b][0] = r + 2 * (i & 1) + 4 * (G & 3) + 16 * (i >> 1) + 64 * (G >> 2);
    all.id[b][1] = (r ? 15 - i : i) + 16 * G;
    all.id[b][2] = r + 2 * G + 16 * i;
  }
  all.shift_k = shift_k;
  all.x = x;
  all.gate_w = gate_w;
  cudaLaunchAttribute at[1];
  cudaLaunchConfig_t cfg = fused_cfg(at);
  if (max_clusters >= 66) {
    cudaLaunchKernelEx(&cfg, fused_kernel, all);
  } else {
    const cudaStream_t st = cudaStreamPerThread;
    plain_gemm<<<dim3(HDIM / 64, S_LEN / 64), 256, 0, st>>>(x, wq, (bf16*)pctx, DM, HDIM, HDIM);
    for (int half = 0; half < 2; half++) {
      plain_gemm<<<dim3(HDIM / 128, S_LEN / 64), 256, 0, st>>>(ckv, wuk + half * (HDIM / 2), (bf16*)pk, DC, HDIM, HDIM / 2);
      plain_gemm<<<dim3(HDIM / 128, S_LEN / 64), 256, 0, st>>>(ckv, wuv + half * (HDIM / 2), (bf16*)pv, DC, HDIM, HDIM / 2);
      plain_attn<<<dim3(S_LEN / 8, NH / 2), 256, 0, st>>>(half);
    }
    plain_gemm<<<dim3(DM / 64, S_LEN / 64), 256, 0, st>>>((const bf16*)pctx, wo, out, HDIM, DM, DM);
    plain_gate<<<S_LEN / 8, 256, 0, st>>>(x, gate_w);
    plain_conv<<<DM, 256, 0, st>>>(x, bk, bv, shift_k, ssm_k, ssm_D, out);
  }
}
```

```cpp
#include <cuda_runtime.h>
#include <cuda_bf16.h>
#include <cuda.h>
#include <stdint.h>

typedef __nv_bfloat16 bf16;
#define INPLACE 3

constexpr int S_LEN = 2048;
constexpr int DM = 1024;
constexpr int NH = 32;
constexpr int HD = 128;
constexpr int DC = 512;
constexpr int HDIM = NH * HD;

__device__ __align__(1024) bf16 g_k[S_LEN * HDIM / 2];
__device__ __align__(1024) bf16 g_v[S_LEN * HDIM / 2];
__device__ __align__(1024) bf16 g_ctx[S_LEN * HDIM];
__device__ __align__(1024) bf16 g_kvT[DM * S_LEN];
#define g_y2T g_kvT
__device__ __align__(1024) float g_gate[S_LEN];
enum { CNT_KV = 0, CNT_PREP = 2, CNT_CTX = 4, CNT_Y2 = 6, CNT_DONE = 8, CNT_N };
__device__ unsigned int g_cnt[CNT_N * 32];

#define TL(k, i)
#define TL2(k, i)
#define TD(i)
#define LT(i, thr)
#define PT_DECL
#define PT
#define CLK_DECL
#define CLK_SAMPLE
#define CLK_END
#define CT(i)
#define GT(i)
#define GS(i)
#define GA(i)
#define ST(i)

__device__ __forceinline__ uint32_t smem_u32(const void* p) { return (uint32_t)__cvta_generic_to_shared(p); }

__device__ __forceinline__ void mbar_init(uint32_t bar, uint32_t count) {
  asm volatile("mbarrier.init.shared::cta.b64 [%0], %1;" ::"r"(bar), "r"(count));
}
__device__ __forceinline__ void mbar_expect_tx(uint32_t bar, uint32_t bytes) {
  asm volatile("mbarrier.arrive.expect_tx.shared::cta.b64 _, [%0], %1;" ::"r"(bar), "r"(bytes) : "memory");
}
__device__ __forceinline__ void mbar_arrive(uint32_t bar) {
  asm volatile("mbarrier.arrive.shared::cta.b64 _, [%0];" ::"r"(bar) : "memory");
}
__device__ __forceinline__ void mbar_wait(uint32_t bar, uint32_t parity) {
  uint32_t done;
  uint32_t spins = 0;
  do {
    asm volatile(
        "{\n.reg .pred p;\n"
        "mbarrier.try_wait.parity.shared::cta.b64 p, [%1], %2;\n"
        "selp.u32 %0, 1, 0, p;\n}\n"
        : "=r"(done)
        : "r"(bar), "r"(parity)
        : "memory");
    if (++spins > (1u << 22)) break;
  } while (!done);
}
__device__ __forceinline__ bool mbar_try(uint32_t bar, uint32_t parity) {
  uint32_t done;
  asm volatile(
      "{\n.reg .pred p;\n"
      "mbarrier.try_wait.parity.shared::cta.b64 p, [%1], %2;\n"
      "selp.u32 %0, 1, 0, p;\n}\n"
      : "=r"(done)
      : "r"(bar), "r"(parity)
      : "memory");
  return done != 0;
}
__device__ __forceinline__ bool elect_one() {
  uint32_t pred;
  asm volatile("{\n.reg .pred p;\nelect.sync _|p, 0xffffffff;\nselp.u32 %0, 1, 0, p;\n}\n" : "=r"(pred));
  return pred != 0;
}
__device__ __forceinline__ void mbar_arrive_if(uint32_t bar, bool pred) {
  asm volatile(
      "{\n.reg .pred p;\nsetp.ne.b32 p, %1, 0;\n"
      "@p mbarrier.arrive.shared::cta.b64 _, [%0];\n}\n" ::"r"(bar),
      "r"((uint32_t)pred)
      : "memory");
}
__device__ __forceinline__ void mbar_wait_sleep(uint32_t bar, uint32_t parity) {
  uint32_t done;
  uint32_t spins = 0;
  do {
    asm volatile(
        "{\n.reg .pred p;\n"
        "mbarrier.try_wait.parity.shared::cta.b64 p, [%1], %2, %3;\n"
        "selp.u32 %0, 1, 0, p;\n}\n"
        : "=r"(done)
        : "r"(bar), "r"(parity), "r"(20000u)
        : "memory");
    if (++spins > (1u << 16)) break;
  } while (!done);
}
__device__ __forceinline__ void fence_barrier_init() {
  asm volatile("fence.mbarrier_init.release.cluster;" ::: "memory");
}
__device__ __forceinline__ void fence_proxy_async() {
  asm volatile("fence.proxy.async.shared::cta;" ::: "memory");
}
__device__ __forceinline__ void named_bar_sync(int id, int nthreads) {
  asm volatile("bar.sync %0, %1;" ::"r"(id), "r"(nthreads) : "memory");
}
__device__ __forceinline__ void named_bar_arrive(int id, int nthreads) {
  asm volatile("bar.arrive %0, %1;" ::"r"(id), "r"(nthreads) : "memory");
}
__device__ __forceinline__ void tma_load_2d(uint32_t dst, const CUtensorMap* m, uint32_t bar, int c0, int c1) {
  asm volatile(
      "cp.async.bulk.tensor.2d.shared::cluster.global.mbarrier::complete_tx::bytes [%0], [%1, {%3, %4}], [%2];" ::"r"(dst),
      "l"(reinterpret_cast<uint64_t>(m)), "r"(bar), "r"(c0), "r"(c1)
      : "memory");
}
__device__ __forceinline__ void tma_load_3d(uint32_t dst, const CUtensorMap* m, uint32_t bar, int c0, int c1, int c2) {
  asm volatile(
      "cp.async.bulk.tensor.3d.shared::cluster.global.mbarrier::complete_tx::bytes [%0], [%1, {%3, %4, %5}], [%2];" ::"r"(dst),
      "l"(reinterpret_cast<uint64_t>(m)), "r"(bar), "r"(c0), "r"(c1), "r"(c2)
      : "memory");
}
__device__ __forceinline__ void tma_store_2d(const CUtensorMap* m, uint32_t src, int c0, int c1) {
  asm volatile("cp.async.bulk.tensor.2d.global.shared::cta.bulk_group [%0, {%2, %3}], [%1];" ::"l"(
                   reinterpret_cast<uint64_t>(m)),
               "r"(src), "r"(c0), "r"(c1)
               : "memory");
}
__device__ __forceinline__ void tma_load_4d(uint32_t dst, const CUtensorMap* m, uint32_t bar, int c0, int tile) {
  asm volatile(
      "cp.async.bulk.tensor.4d.shared::cluster.global.mbarrier::complete_tx::bytes [%0], [%1, {%3, %4, %4, %5}], [%2];" ::"r"(dst),
      "l"(reinterpret_cast<uint64_t>(m)), "r"(bar), "r"(c0), "r"(0), "r"(2 * tile)
      : "memory");
}
__device__ __forceinline__ void tma_store_4d(const CUtensorMap* m, uint32_t src, int c0, int c2, int group) {
  asm volatile("cp.async.bulk.tensor.4d.global.shared::cta.bulk_group [%0, {%2, %3, %4, %5}], [%1];" ::"l"(
                   reinterpret_cast<uint64_t>(m)),
               "r"(src), "r"(c0), "r"(0), "r"(c2), "r"(group)
               : "memory");
}
__device__ __forceinline__ void bulk_load(uint32_t dst, const void* src, uint32_t bytes, uint32_t bar) {
  asm volatile("cp.async.bulk.shared::cluster.global.mbarrier::complete_tx::bytes [%0], [%1], %2, [%3];" ::"r"(dst),
               "l"(src), "r"(bytes), "r"(bar)
               : "memory");
}
__device__ __forceinline__ void tma_load_2d_mc(uint32_t dst, const CUtensorMap* m, uint32_t bar, int c0, int c1,
                                               uint16_t mask) {
  asm volatile(
      "cp.async.bulk.tensor.2d.shared::cluster.global.mbarrier::complete_tx::bytes.multicast::cluster [%0], [%1, {%3, "
      "%4}], [%2], %5;" ::"r"(dst),
      "l"(reinterpret_cast<uint64_t>(m)), "r"(bar), "r"(c0), "r"(c1), "h"(mask)
      : "memory");
}
__device__ __forceinline__ void mbar_arrive_cluster_if(uint32_t bar, uint32_t cta, bool pred) {
  asm volatile(
      "{\n.reg .b32 ra;\n.reg .pred p;\nsetp.ne.b32 p, %2, 0;\n"
      "mapa.shared::cluster.u32 ra, %0, %1;\n"
      "@p mbarrier.arrive.shared::cluster.b64 _, [ra];\n}\n" ::"r"(bar),
      "r"(cta), "r"((uint32_t)pred)
      : "memory");
}
__device__ __forceinline__ uint64_t policy_evict_first() {
  uint64_t pol;
  asm volatile("createpolicy.fractional.L2::evict_first.b64 %0, 1.0;" : "=l"(pol));
  return pol;
}
__device__ __forceinline__ void tma_load_2d_hint(uint32_t dst, const CUtensorMap* m, uint32_t bar, int c0, int c1,
                                                 uint64_t pol) {
  asm volatile(
      "cp.async.bulk.tensor.2d.shared::cluster.global.mbarrier::complete_tx::bytes.L2::cache_hint [%0], [%1, {%3, %4}], "
      "[%2], %5;" ::"r"(dst),
      "l"(reinterpret_cast<uint64_t>(m)), "r"(bar), "r"(c0), "r"(c1), "l"(pol)
      : "memory");
}
__device__ __forceinline__ void tma_load_3d_hint(uint32_t dst, const CUtensorMap* m, uint32_t bar, int c0, int c1,
                                                 int c2, uint64_t pol) {
  asm volatile(
      "cp.async.bulk.tensor.3d.shared::cluster.global.mbarrier::complete_tx::bytes.L2::cache_hint [%0], [%1, {%3, %4, "
      "%5}], [%2], %6;" ::"r"(dst),
      "l"(reinterpret_cast<uint64_t>(m)), "r"(bar), "r"(c0), "r"(c1), "r"(c2), "l"(pol)
      : "memory");
}
__device__ __forceinline__ void bulk_load_hint(uint32_t dst, const void* src, uint32_t bytes, uint32_t bar, uint64_t pol) {
  asm volatile(
      "cp.async.bulk.shared::cluster.global.mbarrier::complete_tx::bytes.L2::cache_hint [%0], [%1], %2, [%3], %4;" ::"r"(dst),
      "l"(src), "r"(bytes), "r"(bar), "l"(pol)
      : "memory");
}
__device__ __forceinline__ void cnt_signal_release(int which, uint32_t n) {
  asm volatile("red.release.gpu.global.add.u32 [%0], %1;" ::"l"(g_cnt + which * 32), "r"(n) : "memory");
}
__device__ __forceinline__ void cnt_wait(int which, uint32_t target) {
  uint32_t v, spins = 0;
  while (true) {
    asm volatile("ld.acquire.gpu.global.u32 %0, [%1];" : "=r"(v) : "l"(g_cnt + which * 32) : "memory");
    if (v >= target || ++spins > (1u << 18)) break;
    __nanosleep(64);
  }
  asm volatile("fence.proxy.async.global;" ::: "memory");
}
__device__ __forceinline__ void tma_store_commit() { asm volatile("cp.async.bulk.commit_group;" ::: "memory"); }
template <int N>
__device__ __forceinline__ void tma_store_wait_read() {
  asm volatile("cp.async.bulk.wait_group.read %0;" ::"n"(N) : "memory");
}
template <int N>
__device__ __forceinline__ void tma_store_wait() {
  asm volatile("cp.async.bulk.wait_group %0;" ::"n"(N) : "memory");
}
__device__ __forceinline__ void wgmma_fence() { asm volatile("wgmma.fence.sync.aligned;" ::: "memory"); }
__device__ __forceinline__ void wgmma_commit() { asm volatile("wgmma.commit_group.sync.aligned;" ::: "memory"); }
template <int N>
__device__ __forceinline__ void wgmma_wait() {
  asm volatile("wgmma.wait_group.sync.aligned %0;" ::"n"(N) : "memory");
}
template <int R>
__device__ __forceinline__ void reg_alloc() { asm volatile("setmaxnreg.inc.sync.aligned.u32 %0;" ::"n"(R)); }
template <int R>
__device__ __forceinline__ void reg_dealloc() { asm volatile("setmaxnreg.dec.sync.aligned.u32 %0;" ::"n"(R)); }

__device__ __forceinline__ void stmatrix_x4(uint32_t addr, uint32_t r0, uint32_t r1, uint32_t r2, uint32_t r3) {
  asm volatile("stmatrix.sync.aligned.m8n8.x4.shared.b16 [%0], {%1, %2, %3, %4};" ::"r"(addr), "r"(r0), "r"(r1),
               "r"(r2), "r"(r3)
               : "memory");
}
__device__ __forceinline__ uint32_t pack_bf16(float lo, float hi) {
  uint32_t r;
  asm("cvt.rn.bf16x2.f32 %0, %1, %2;" : "=r"(r) : "f"(hi), "f"(lo));
  return r;
}
__device__ __forceinline__ float bf16_round(float x) { return __bfloat162float(__float2bfloat16_rn(x)); }
__device__ __forceinline__ float bf_lo(uint32_t v) { return __uint_as_float(v << 16); }
__device__ __forceinline__ float bf_hi(uint32_t v) { return __uint_as_float(v & 0xffff0000u); }
__device__ __forceinline__ uint4 lds128(uint32_t a) {
  uint4 v;
  asm volatile("ld.shared.v4.u32 {%0, %1, %2, %3}, [%4];" : "=r"(v.x), "=r"(v.y), "=r"(v.z), "=r"(v.w) : "r"(a));
  return v;
}
__device__ __forceinline__ void sts128(uint32_t a, uint4 v) {
  asm volatile("st.shared.v4.u32 [%0], {%1, %2, %3, %4};" ::"r"(a), "r"(v.x), "r"(v.y), "r"(v.z), "r"(v.w) : "memory");
}
__device__ __forceinline__ uint32_t mul_bf2(uint32_t a, uint32_t b) {
  uint32_t r;
  asm("mul.rn.bf16x2 %0, %1, %2;" : "=r"(r) : "r"(a), "r"(b));
  return r;
}
__device__ __forceinline__ uint32_t add_bf2(uint32_t a, uint32_t b) {
  uint32_t r;
  asm("add.rn.bf16x2 %0, %1, %2;" : "=r"(r) : "r"(a), "r"(b));
  return r;
}
__device__ __forceinline__ float ex2(float x) {
  float y;
  asm("ex2.approx.ftz.f32 %0, %1;" : "=f"(y) : "f"(x));
  return y;
}
__device__ __forceinline__ float rcp(float x) {
  float y;
  asm("rcp.approx.ftz.f32 %0, %1;" : "=f"(y) : "f"(x));
  return y;
}
template <int N>
__device__ __forceinline__ void fence_regs(float (&r)[N]) {
#pragma unroll
  for (int i = 0; i < N; i++) asm volatile("" : "+f"(r[i])::"memory");
}

template <int N>
__device__ __forceinline__ void undef_regs(float (&r)[N]) {
#pragma unroll
  for (int i = 0; i < N; i++) asm volatile("" : "=f"(r[i]));
}
template <int N>
__device__ __forceinline__ void fence_regs_u(uint32_t (&r)[N]) {
#pragma unroll
  for (int i = 0; i < N; i++) asm volatile("" : "+r"(r[i])::"memory");
}

constexpr uint64_t DESC_SW128 = 1ull << 62;
__device__ __forceinline__ uint64_t make_desc(uint32_t addr, uint32_t lbo_bytes, uint32_t sbo_bytes, uint64_t swz) {
  return (uint64_t)((addr & 0x3FFFF) >> 4) | ((uint64_t)((lbo_bytes & 0x3FFFF) >> 4) << 16) |
         ((uint64_t)((sbo_bytes & 0x3FFFF) >> 4) << 32) | swz;
}

__device__ __forceinline__ uint64_t desc_add(uint64_t d, uint32_t off16) {
  return (d & 0xFFFFFFFF00000000ull) | (uint64_t)((uint32_t)d + off16);
}

__device__ __forceinline__ void wgmma_m64n256_ss_tb(float (&d)[128], uint64_t da, uint64_t db, int sd) {
  asm volatile(
    "{\n.reg .pred p;\nsetp.ne.b32 p, %130, 0;\n"
    "wgmma.mma_async.sync.aligned.m64n256k16.f32.bf16.bf16 "
    "{%0, %1, %2, %3, %4, %5, %6, %7, %8, %9, %10, %11, %12, %13, %14, %15, %16, %17, %18, %19, %20, %21, %22, %23, %24, %25, %26, %27, %28, %29, %30, %31, %32, %33, %34, %35, %36, %37, %38, %39, %40, %41, %42, %43, %44, %45, %46, %47, %48, %49, %50, %51, %52, %53, %54, %55, %56, %57, %58, %59, %60, %61, %62, %63, %64, %65, %66, %67, %68, %69, %70, %71, %72, %73, %74, %75, %76, %77, %78, %79, %80, %81, %82, %83, %84, %85, %86, %87, %88, %89, %90, %91, %92, %93, %94, %95, %96, %97, %98, %99, %100, %101, %102, %103, %104, %105, %106, %107, %108, %109, %110, %111, %112, %113, %114, %115, %116, %117, %118, %119, %120, %121, %122, %123, %124, %125, %126, %127}, %128, %129, p, 1, 1, 0, 1;\n}\n"
    : "+f"(d[0]), "+f"(d[1]), "+f"(d[2]), "+f"(d[3]), "+f"(d[4]), "+f"(d[5]), "+f"(d[6]), "+f"(d[7]), "+f"(d[8]), "+f"(d[9]), "+f"(d[10]), "+f"(d[11]), "+f"(d[12]), "+f"(d[13]), "+f"(d[14]), "+f"(d[15]), "+f"(d[16]), "+f"(d[17]), "+f"(d[18]), "+f"(d[19]), "+f"(d[20]), "+f"(d[21]), "+f"(d[22]), "+f"(d[23]), "+f"(d[24]), "+f"(d[25]), "+f"(d[26]), "+f"(d[27]), "+f"(d[28]), "+f"(d[29]), "+f"(d[30]), "+f"(d[31]), "+f"(d[32]), "+f"(d[33]), "+f"(d[34]), "+f"(d[35]), "+f"(d[36]), "+f"(d[37]), "+f"(d[38]), "+f"(d[39]), "+f"(d[40]), "+f"(d[41]), "+f"(d[42]), "+f"(d[43]), "+f"(d[44]), "+f"(d[45]), "+f"(d[46]), "+f"(d[47]), "+f"(d[48]), "+f"(d[49]), "+f"(d[50]), "+f"(d[51]), "+f"(d[52]), "+f"(d[53]), "+f"(d[54]), "+f"(d[55]), "+f"(d[56]), "+f"(d[57]), "+f"(d[58]), "+f"(d[59]), "+f"(d[60]), "+f"(d[61]), "+f"(d[62]), "+f"(d[63]), "+f"(d[64]), "+f"(d[65]), "+f"(d[66]), "+f"(d[67]), "+f"(d[68]), "+f"(d[69]), "+f"(d[70]), "+f"(d[71]), "+f"(d[72]), "+f"(d[73]), "+f"(d[74]), "+f"(d[75]), "+f"(d[76]), "+f"(d[77]), "+f"(d[78]), "+f"(d[79]), "+f"(d[80]), "+f"(d[81]), "+f"(d[82]), "+f"(d[83]), "+f"(d[84]), "+f"(d[85]), "+f"(d[86]), "+f"(d[87]), "+f"(d[88]), "+f"(d[89]), "+f"(d[90]), "+f"(d[91]), "+f"(d[92]), "+f"(d[93]), "+f"(d[94]), "+f"(d[95]), "+f"(d[96]), "+f"(d[97]), "+f"(d[98]), "+f"(d[99]), "+f"(d[100]), "+f"(d[101]), "+f"(d[102]), "+f"(d[103]), "+f"(d[104]), "+f"(d[105]), "+f"(d[106]), "+f"(d[107]), "+f"(d[108]), "+f"(d[109]), "+f"(d[110]), "+f"(d[111]), "+f"(d[112]), "+f"(d[113]), "+f"(d[114]), "+f"(d[115]), "+f"(d[116]), "+f"(d[117]), "+f"(d[118]), "+f"(d[119]), "+f"(d[120]), "+f"(d[121]), "+f"(d[122]), "+f"(d[123]), "+f"(d[124]), "+f"(d[125]), "+f"(d[126]), "+f"(d[127])
    : "l"(da), "l"(db), "r"(sd));
}

__device__ __forceinline__ void wgmma_m64n128_ss(float (&d)[64], uint64_t da, uint64_t db, int sd) {
  asm volatile(
    "{\n.reg .pred p;\nsetp.ne.b32 p, %66, 0;\n"
    "wgmma.mma_async.sync.aligned.m64n128k16.f32.bf16.bf16 "
    "{%0, %1, %2, %3, %4, %5, %6, %7, %8, %9, %10, %11, %12, %13, %14, %15, %16, %17, %18, %19, %20, %21, %22, %23, %24, %25, %26, %27, %28, %29, %30, %31, %32, %33, %34, %35, %36, %37, %38, %39, %40, %41, %42, %43, %44, %45, %46, %47, %48, %49, %50, %51, %52, %53, %54, %55, %56, %57, %58, %59, %60, %61, %62, %63}, %64, %65, p, 1, 1, 0, 0;\n}\n"
    : "+f"(d[0]), "+f"(d[1]), "+f"(d[2]), "+f"(d[3]), "+f"(d[4]), "+f"(d[5]), "+f"(d[6]), "+f"(d[7]), "+f"(d[8]), "+f"(d[9]), "+f"(d[10]), "+f"(d[11]), "+f"(d[12]), "+f"(d[13]), "+f"(d[14]), "+f"(d[15]), "+f"(d[16]), "+f"(d[17]), "+f"(d[18]), "+f"(d[19]), "+f"(d[20]), "+f"(d[21]), "+f"(d[22]), "+f"(d[23]), "+f"(d[24]), "+f"(d[25]), "+f"(d[26]), "+f"(d[27]), "+f"(d[28]), "+f"(d[29]), "+f"(d[30]), "+f"(d[31]), "+f"(d[32]), "+f"(d[33]), "+f"(d[34]), "+f"(d[35]), "+f"(d[36]), "+f"(d[37]), "+f"(d[38]), "+f"(d[39]), "+f"(d[40]), "+f"(d[41]), "+f"(d[42]), "+f"(d[43]), "+f"(d[44]), "+f"(d[45]), "+f"(d[46]), "+f"(d[47]), "+f"(d[48]), "+f"(d[49]), "+f"(d[50]), "+f"(d[51]), "+f"(d[52]), "+f"(d[53]), "+f"(d[54]), "+f"(d[55]), "+f"(d[56]), "+f"(d[57]), "+f"(d[58]), "+f"(d[59]), "+f"(d[60]), "+f"(d[61]), "+f"(d[62]), "+f"(d[63])
    : "l"(da), "l"(db), "r"(sd));
}

__device__ __forceinline__ void wgmma_m64n128_ss_tb(float (&d)[64], uint64_t da, uint64_t db, int sd) {
  asm volatile(
    "{\n.reg .pred p;\nsetp.ne.b32 p, %66, 0;\n"
    "wgmma.mma_async.sync.aligned.m64n128k16.f32.bf16.bf16 "
    "{%0, %1, %2, %3, %4, %5, %6, %7, %8, %9, %10, %11, %12, %13, %14, %15, %16, %17, %18, %19, %20, %21, %22, %23, %24, %25, %26, %27, %28, %29, %30, %31, %32, %33, %34, %35, %36, %37, %38, %39, %40, %41, %42, %43, %44, %45, %46, %47, %48, %49, %50, %51, %52, %53, %54, %55, %56, %57, %58, %59, %60, %61, %62, %63}, %64, %65, p, 1, 1, 0, 1;\n}\n"
    : "+f"(d[0]), "+f"(d[1]), "+f"(d[2]), "+f"(d[3]), "+f"(d[4]), "+f"(d[5]), "+f"(d[6]), "+f"(d[7]), "+f"(d[8]), "+f"(d[9]), "+f"(d[10]), "+f"(d[11]), "+f"(d[12]), "+f"(d[13]), "+f"(d[14]), "+f"(d[15]), "+f"(d[16]), "+f"(d[17]), "+f"(d[18]), "+f"(d[19]), "+f"(d[20]), "+f"(d[21]), "+f"(d[22]), "+f"(d[23]), "+f"(d[24]), "+f"(d[25]), "+f"(d[26]), "+f"(d[27]), "+f"(d[28]), "+f"(d[29]), "+f"(d[30]), "+f"(d[31]), "+f"(d[32]), "+f"(d[33]), "+f"(d[34]), "+f"(d[35]), "+f"(d[36]), "+f"(d[37]), "+f"(d[38]), "+f"(d[39]), "+f"(d[40]), "+f"(d[41]), "+f"(d[42]), "+f"(d[43]), "+f"(d[44]), "+f"(d[45]), "+f"(d[46]), "+f"(d[47]), "+f"(d[48]), "+f"(d[49]), "+f"(d[50]), "+f"(d[51]), "+f"(d[52]), "+f"(d[53]), "+f"(d[54]), "+f"(d[55]), "+f"(d[56]), "+f"(d[57]), "+f"(d[58]), "+f"(d[59]), "+f"(d[60]), "+f"(d[61]), "+f"(d[62]), "+f"(d[63])
    : "l"(da), "l"(db), "r"(sd));
}

__device__ __forceinline__ void wgmma_m64n128_rs_tb(float* d, uint32_t a0, uint32_t a1, uint32_t a2, uint32_t a3, uint64_t db, int sd) {
  asm volatile(
    "{\n.reg .pred p;\nsetp.ne.b32 p, %69, 0;\n"
    "wgmma.mma_async.sync.aligned.m64n128k16.f32.bf16.bf16 "
    "{%0, %1, %2, %3, %4, %5, %6, %7, %8, %9, %10, %11, %12, %13, %14, %15, %16, %17, %18, %19, %20, %21, %22, %23, %24, %25, %26, %27, %28, %29, %30, %31, %32, %33, %34, %35, %36, %37, %38, %39, %40, %41, %42, %43, %44, %45, %46, %47, %48, %49, %50, %51, %52, %53, %54, %55, %56, %57, %58, %59, %60, %61, %62, %63}, {%64, %65, %66, %67}, %68, p, 1, 1, 1;\n}\n"
    : "+f"(d[0]), "+f"(d[1]), "+f"(d[2]), "+f"(d[3]), "+f"(d[4]), "+f"(d[5]), "+f"(d[6]), "+f"(d[7]), "+f"(d[8]), "+f"(d[9]), "+f"(d[10]), "+f"(d[11]), "+f"(d[12]), "+f"(d[13]), "+f"(d[14]), "+f"(d[15]), "+f"(d[16]), "+f"(d[17]), "+f"(d[18]), "+f"(d[19]), "+f"(d[20]), "+f"(d[21]), "+f"(d[22]), "+f"(d[23]), "+f"(d[24]), "+f"(d[25]), "+f"(d[26]), "+f"(d[27]), "+f"(d[28]), "+f"(d[29]), "+f"(d[30]), "+f"(d[31]), "+f"(d[32]), "+f"(d[33]), "+f"(d[34]), "+f"(d[35]), "+f"(d[36]), "+f"(d[37]), "+f"(d[38]), "+f"(d[39]), "+f"(d[40]), "+f"(d[41]), "+f"(d[42]), "+f"(d[43]), "+f"(d[44]), "+f"(d[45]), "+f"(d[46]), "+f"(d[47]), "+f"(d[48]), "+f"(d[49]), "+f"(d[50]), "+f"(d[51]), "+f"(d[52]), "+f"(d[53]), "+f"(d[54]), "+f"(d[55]), "+f"(d[56]), "+f"(d[57]), "+f"(d[58]), "+f"(d[59]), "+f"(d[60]), "+f"(d[61]), "+f"(d[62]), "+f"(d[63])
    : "r"(a0), "r"(a1), "r"(a2), "r"(a3), "l"(db), "r"(sd));
}

__device__ __forceinline__ void wgmma_m64n64_rs(float (&d)[32], const uint32_t* a, uint64_t db, int sd) {
  asm volatile(
    "{\n.reg .pred p;\nsetp.ne.b32 p, %37, 0;\n"
    "wgmma.mma_async.sync.aligned.m64n64k16.f32.bf16.bf16 "
    "{%0, %1, %2, %3, %4, %5, %6, %7, %8, %9, %10, %11, %12, %13, %14, %15, %16, %17, %18, %19, %20, %21, %22, %23, %24, %25, %26, %27, %28, %29, %30, %31}, {%32, %33, %34, %35}, %36, p, 1, 1, 0;\n}\n"
    : "+f"(d[0]), "+f"(d[1]), "+f"(d[2]), "+f"(d[3]), "+f"(d[4]), "+f"(d[5]), "+f"(d[6]), "+f"(d[7]), "+f"(d[8]), "+f"(d[9]), "+f"(d[10]), "+f"(d[11]), "+f"(d[12]), "+f"(d[13]), "+f"(d[14]), "+f"(d[15]), "+f"(d[16]), "+f"(d[17]), "+f"(d[18]), "+f"(d[19]), "+f"(d[20]), "+f"(d[21]), "+f"(d[22]), "+f"(d[23]), "+f"(d[24]), "+f"(d[25]), "+f"(d[26]), "+f"(d[27]), "+f"(d[28]), "+f"(d[29]), "+f"(d[30]), "+f"(d[31])
    : "r"(a[0]), "r"(a[1]), "r"(a[2]), "r"(a[3]), "l"(db), "r"(sd));
}

constexpr int G_STAGES = 4;
constexpr int G_A_BYTES = 128 * 64 * 2;
constexpr int G_B_BYTES = 256 * 64 * 2;
constexpr int G_STAGE_BYTES = G_A_BYTES + G_B_BYTES;
constexpr int G_STG_OFF = G_STAGES * G_STAGE_BYTES;
constexpr int BAR_OFF = G_STG_OFF + 32768 + 2048;
constexpr int SMEM_BYTES = BAR_OFF + 1024;
constexpr int B_GFULL = 0, B_GEMPTY = 32, B_OY2 = 64, B_PFULL = 224;
constexpr int B_KFULL = 80, B_KEMPTY = 96, B_VFULL = 112, B_VEMPTY = 128, B_QFULL = 144, B_QEMPTY = 160,
              B_QPEER = 184;
constexpr int B_CFULL = 192;
constexpr int B_OFREE = 256, B_OFULL = 272, B_OEMPTY = 320, B_OY = 368;
constexpr int B_SFULL = 392, B_SFREE = 424, B_PEND = 456, B_SCMD = 512;

#define PHASE_PROLOGUE                                                                \
  uint32_t tid, rt_zero;                                                              \
  asm volatile("mov.u32 %0, %%tid.x;" : "=r"(tid));                                   \
  asm volatile("mov.u32 %0, %%nctaid.y;" : "=r"(rt_zero));                            \
  asm volatile("" : "+r"(smem0));                                                     \
  rt_zero = __shfl_sync(0xffffffffu, rt_zero >> 8, 0);   \
  const uint32_t sbase = __shfl_sync(0xffffffffu, smem0, 0);                          \
  const uint32_t bar = sbase + BAR_OFF;                                               \
  const int wg = __shfl_sync(0xffffffffu, tid >> 7, 0);                               \
  const int warp = (tid >> 5) & 3, lane = tid & 31, wtid = tid & 127;                 \
  (void)rt_zero; (void)bar; (void)warp; (void)lane; (void)wtid;

constexpr int A_ITEMS = 256;
enum { ST_BOX1, ST_BOX1P, ST_BOX2, ST_BOX2W, ST_BOX2L, ST_PEER };
__device__ __forceinline__ void st_post(uint32_t bar, int wg, int wtid, uint32_t n, int kind, int dst, uint32_t src,
                                        int c0, int c1, int sig) {
  if (wtid == 0) sts128(bar + B_SCMD + wg * 32 + (n & 1) * 16, make_uint4(kind + dst * 8 + sig * 32, src, c0, c1));
  fence_proxy_async();
  __syncwarp();
  mbar_arrive_if(bar + B_SFULL + wg * 16 + (n & 1) * 8, (wtid & 31) == 0);
}
__device__ __forceinline__ void st_wait(uint32_t bar, int wg, uint32_t n) {
  const uint32_t b = bar + B_SFREE + wg * 16 + (n & 1) * 8;
  if (!mbar_try(b, ~(n >> 1) & 1)) mbar_wait(b, ~(n >> 1) & 1);
}
__device__ __forceinline__ void note(uint32_t bar, uint32_t cnt) {
  asm volatile("red.release.cta.shared.add.u32 [%0], 1;" ::"r"(bar + B_PEND + 4 * cnt) : "memory");
}
__device__ __forceinline__ void store_agent(const CUtensorMap* maps, uint32_t bar, int wg, uint32_t n) {
  const uint32_t fr = bar + B_SFREE + wg * 16;
  mbar_arrive(fr + (~n & 1) * 8);
  if (n == 0) mbar_arrive(fr);
  for (;; n++) {
    mbar_wait_sleep(bar + B_SFULL + wg * 16 + (n & 1) * 8, (n >> 1) & 1);
    uint4 c = lds128(bar + B_SCMD + wg * 32 + (n & 1) * 16);
    const CUtensorMap* dst = maps + ((c.x >> 3) & 3);
    const int sig = (int)c.x >> 5;
    c.x &= 7;
    if (c.x == ST_PEER) {
      mbar_wait_sleep(bar + B_QPEER, c.z);
      asm volatile(
          "{\n.reg .b32 d, b;\nmapa.shared::cluster.u32 d, %0, %2;\nmapa.shared::cluster.u32 b, %1, %2;\n"
          "cp.async.bulk.shared::cluster.shared::cta.mbarrier::complete_tx::bytes [d], [%3], 8192, [b];\n"
          "cp.async.bulk.shared::cluster.shared::cta.mbarrier::complete_tx::bytes [d + 16384], [%3 + 8192], 8192, [b];\n}\n" ::"r"(
              bar - BAR_OFF + 32768 + wg * 8192),
          "r"(bar + B_QFULL + 8), "r"(~blockIdx.x & 1), "r"(c.y)
          : "memory");
      mbar_wait_sleep(bar + B_QFULL + 8, 0);
      mbar_arrive_cluster_if(fr + (n & 1) * 8, ~blockIdx.x & 1, true);
      continue;
    }
    tma_store_2d(dst, c.y, c.z, c.w);
    if (c.x >= ST_BOX2) tma_store_2d(dst, c.y + 8192, c.z + 64, c.w);
    tma_store_commit();
    tma_store_wait_read<0>();
    if (c.x != ST_BOX1P) mbar_arrive(fr + (n & 1) * 8);
    if (c.x == ST_BOX2L) mbar_arrive(bar + B_OFREE + 8 * wg);
    if (sig >= 0) {
      tma_store_wait<0>();
      asm volatile("fence.proxy.async.global;" ::: "memory");
      note(bar, sig);
      if (c.x == ST_BOX2W) cnt_wait(CNT_CTX, 2 * A_ITEMS);
      if (c.x == ST_BOX2L) note(bar, CNT_DONE);
      if (c.x == ST_BOX2L || c.x == ST_BOX1P) break;
    }
  }
}

struct Maps {
  const bf16 *shift_k, *x, *gate_w, *ssm_k, *ssm_D;
  uint8_t id[128][4];
  CUtensorMap a[2];
  CUtensorMap b[3];
  CUtensorMap c[3];
  CUtensorMap bk, bv;
  CUtensorMap k, v;
  CUtensorMap oa, ob, oc, ox;
  CUtensorMap y, y2;
};

constexpr int P_SLOT = 67 * 128, P_V = 35 * 128, P_TAPS = 2 * P_SLOT;
__device__ __forceinline__ void ldsm4t(uint32_t (&r)[4], uint32_t a) {
  asm volatile("ldmatrix.sync.aligned.m8n8.x4.trans.shared.b16 {%0, %1, %2, %3}, [%4];"
               : "=r"(r[0]), "=r"(r[1]), "=r"(r[2]), "=r"(r[3])
               : "r"(a));
}
__device__ __forceinline__ uint32_t fma_bf2(uint32_t a, uint32_t b, uint32_t c) {
  uint32_t r;
  asm("fma.rn.bf16x2 %0, %1, %2, %3;" : "=r"(r) : "r"(a), "r"(b), "r"(c));
  return r;
}
__device__ __forceinline__ void agent_warp(const Maps& maps, uint32_t smem0) {
  mbar_wait_sleep(smem0 + BAR_OFF + B_GFULL + 8 * (G_STAGES - 1), 0);
#pragma unroll 1
  for (int j = 0; j < 7; j++) {
    PHASE_PROLOGUE
    const int w = __shfl_sync(0xffffffffu, warp, 0), i = j >> 1;
    const uint32_t pb = bar + B_PFULL + w * 16, sw = sbase + G_STG_OFF + w * (P_TAPS + 512);
    const int d0 = (blockIdx.x >> 4) * 128 + (j < 3 ? 64 : 0), t0 = (blockIdx.x & 15) * 128 + w * 64;
    const bool work = (0x56 >> j) & 1;
    GA(80 + 2 * j)
    if (work) mbar_wait_sleep(pb + (i & 1) * 8, i >> 1);
    GA(81 + 2 * j)
    if (((0x2b >> j) & 1) && elect_one()) {
      const uint32_t l = ((j + 1) >> 1) & 1, b = pb + l * 8, dst = sw + l * P_SLOT;
      mbar_expect_tx(b, work ? P_SLOT : P_SLOT + 512);
      const uint64_t pol = policy_evict_first();
      tma_load_2d_hint(dst, &maps.bk, b, d0, t0 + 32 * l - 3, pol);
      tma_load_2d_hint(dst + P_V, &maps.bv, b, d0, t0 + 32 * l, pol);
      if (!work) bulk_load(sbase + G_STG_OFF + P_TAPS, maps.shift_k + d0 * 4, 512, b);
    }
    if (!work) continue;
    const uint32_t so = sw + (i & 1) * P_SLOT;
    uint32_t ak[4];
#pragma unroll
    for (int r = 0; r < 4; r++) {
      const uint32_t a = so / 128 + r + 4 * (lane & 6) + (((((lane >> 2) ^ lane) & 6) + (lane & 1)) ^ 7);
      ak[r] = a * 128 + (a & 7) * 16;
    }
    bf16* dst = g_kvT + (size_t)(d0 + (lane >> 2)) * S_LEN + t0 + ((lane & 3) + 4 * (i & 1)) * 8;
#pragma unroll 1
    for (int cg = 0; cg < 128; cg += 16) {
      uint32_t t01, t23, k[4][4], v[4];
      asm volatile("ld.shared.v2.u32 {%0, %1}, [%2];"
                   : "=r"(t01), "=r"(t23)
                   : "r"(sbase + G_STG_OFF + P_TAPS + cg * 4 + (lane >> 2) * 8));
#pragma unroll
      for (int r = 0; r < 4; r++) ldsm4t(k[r], ak[r] ^ cg);
      ldsm4t(v, (ak[3] ^ cg) + 4096);
      const uint32_t w0 = __byte_perm(t01, 0, 0x1010), w1 = __byte_perm(t01, 0, 0x3232);
      const uint32_t w2 = __byte_perm(t23, 0, 0x1010), w3 = __byte_perm(t23, 0, 0x3232);
#pragma unroll
      for (int j = 0; j < 4; j++)
        v[j] = mul_bf2(fma_bf2(k[3][j], w0, fma_bf2(k[2][j], w1, fma_bf2(k[1][j], w2, mul_bf2(k[0][j], w3)))), v[j]);
      const bool s1 = lane & 1, s2 = lane & 2;
      const uint32_t a0 = s1 ? v[1] : v[0], a1 = s1 ? v[0] : v[1], a2 = s1 ? v[3] : v[2], a3 = s1 ? v[2] : v[3];
      *reinterpret_cast<uint4*>(dst) = make_uint4(s2 ? a2 : a0, s2 ? a3 : a1, s2 ? a0 : a2, s2 ? a1 : a3);
      dst += 8 * S_LEN;
    }
    fence_proxy_async();
    __syncwarp();
    if (j == 1) continue;
    GA(94)
    if (elect_one()) {
      note(bar, CNT_PREP + (j > 2));
      store_agent(maps.c, bar, w, (0x130800 >> (4 * j - 8)) & 255);
    }
    __syncwarp();
  }
}

__device__ __forceinline__ void qkv_tile(const Maps& maps, int it, int& m_tile, int& group) {
  const int b = maps.id[blockIdx.x][it >> 1];
  m_tile = b & 15;
  group = b >> 4;
}

constexpr int G_NTILES = 3;
__device__ __forceinline__ void qkv_producer(const Maps& maps, uint32_t sbase, int pass, bool first) {
  const uint32_t bar = sbase + BAR_OFF;
  uint32_t stage = 0, phase = pass;
#pragma unroll 1
  for (int it = 0; it < (first ? 1 : G_NTILES); it++) {
    int m_tile, group;
    qkv_tile(maps, it, m_tile, group);
    const CUtensorMap* ma = &maps.a[it >> 1];
    const CUtensorMap* mb = &maps.b[it];
    const int nk = first ? G_STAGES : it == 2 ? 16 : 8;
#pragma unroll 1
    for (int kt = (it == 0 && !first && !pass) ? G_STAGES : 0; kt < nk; kt++) {
      if (pass && it == 0 && kt < G_STAGES) {
        constexpr uint32_t LASTB = (B_QEMPTY + 8) | (B_KEMPTY << 8) | ((B_VEMPTY + 8) << 16) | (B_VEMPTY << 24);
        mbar_wait_sleep(bar + ((LASTB >> (8 * kt)) & 255), kt == 2);
      }
      if (!first) mbar_wait_sleep(bar + B_GEMPTY + 8 * stage, phase);
      const uint32_t fb = bar + B_GFULL + 8 * stage;
      const uint32_t sa = sbase + stage * G_STAGE_BYTES;
      mbar_expect_tx(fb, G_STAGE_BYTES);
      tma_load_2d(sa, ma, fb, kt * 64, m_tile * 128);
      tma_load_3d(sa + G_A_BYTES, mb, fb, 0, kt * 64, group * 8 + pass * 4);
      if (++stage == G_STAGES) { stage = 0; phase ^= 1; }
      {
        const int b = maps.id[blockIdx.x][1];
        if (it == 1 && kt == (b & 7))
          asm volatile("cp.async.bulk.prefetch.tensor.3d.L2.global.tile [%0, {%1, %2, %3}];" ::"l"(&maps.b[2]), "r"(0),
                       "r"((b & 15) * 64), "r"((b >> 4) * 8 + pass * 4)
                       : "memory");
      }
      if (pass && it == 0 && kt == G_STAGES - 1) {
#pragma unroll 1
        for (int i = 0; i < 12; i++) {
          asm volatile("mbarrier.inval.shared::cta.b64 [%0];" ::"r"(bar + B_KFULL + 8 * i) : "memory");
          mbar_init(bar + B_KFULL + 8 * i, 1 + ((i >> 1) & 1));
        }
        fence_proxy_async();
      }
    }
  }
}

__device__ __noinline__ void publisher(uint32_t bar, int lane, uint32_t nsrc) {
  uint32_t done = 0;
  CLK_DECL
#pragma unroll 1
  for (uint32_t spins = 0; done < nsrc && spins < (1u << 20); spins++) {
    CLK_SAMPLE
    uint32_t v = 0;
    if (lane < CNT_N)
      asm volatile("atom.acquire.cta.shared.exch.b32 %0, [%1], 0;" : "=r"(v) : "r"(bar + B_PEND + 4 * lane) : "memory");
    done += __shfl_sync(0xffffffffu, v, CNT_DONE);
    if (lane == CNT_DONE) v = 0;
    if (done == nsrc && lane < CNT_DONE) {
      uint32_t w;
      asm volatile("atom.acquire.cta.shared.exch.b32 %0, [%1], 0;" : "=r"(w) : "r"(bar + B_PEND + 4 * lane) : "memory");
      v += w;
    }
    if (v && lane == 0) { TD(0) }
    if (v) cnt_signal_release(lane, v);
    if (v && lane == 0) { TD(1) }
    if (!__any_sync(0xffffffffu, v != 0)) __nanosleep(200);
  }
  CLK_END
  __threadfence();
  __syncwarp();
}

__device__ __forceinline__ void gate_rows(const Maps& maps, uint32_t sbase, int w48, int w12, int lane) {
  const uint32_t buf = sbase + w12 * 16384, gb = sbase + BAR_OFF + 768 + w12 * 16;
  if (lane == 0) {
    mbar_init(gb, 1);
    mbar_init(gb + 8, 1);
    fence_barrier_init();
    for (int i = 0; i < 2; i++) {
      mbar_expect_tx(gb + 8 * i, 8192);
      bulk_load(buf + i * 8192, maps.x + (size_t)(w48 + 48 * i) * 4 * DM, 8192, gb + 8 * i);
    }
  }
  __syncwarp();
  uint4 wv[4];
#pragma unroll
  for (int i = 0; i < 4; i++) wv[i] = __ldg(reinterpret_cast<const uint4*>(maps.gate_w + (i * 32 + lane) * 8));
  int it = 0;
#pragma unroll 1
  for (int row = w48 * 4; row < S_LEN; row += 48 * 4, it++) {
    mbar_wait(gb + 8 * (it & 1), (it >> 1) & 1);
    uint4 xv[4][4];
#pragma unroll
    for (int r = 0; r < 4; r++)
#pragma unroll
      for (int i = 0; i < 4; i++) xv[r][i] = lds128(buf + (it & 1) * 8192 + r * 2048 + (i * 32 + lane) * 16);
    float d[2][4];
#pragma unroll
    for (int pr = 0; pr < 2; pr++) {
      d[pr][0] = d[pr][1] = d[pr][2] = d[pr][3] = 0.f;
      auto acc = [&](uint32_t a0, uint32_t a2, uint32_t b0, uint32_t b2, uint32_t w0, uint32_t w2) {
        asm volatile(
            "mma.sync.aligned.m16n8k16.row.col.f32.bf16.bf16.f32 {%0, %1, %2, %3}, {%4, %5, %6, %7}, {%8, %8}, "
            "{%0, %1, %2, %3};"
            : "+f"(d[pr][0]), "+f"(d[pr][1]), "+f"(d[pr][2]), "+f"(d[pr][3])
            : "r"(mul_bf2(a0, w0)), "r"(mul_bf2(b0, w0)), "r"(mul_bf2(a2, w2)), "r"(mul_bf2(b2, w2)), "r"(0x3f803f80u));
      };
#pragma unroll
      for (int i = 0; i < 4; i++) {
        acc(xv[2 * pr][i].x, xv[2 * pr][i].y, xv[2 * pr + 1][i].x, xv[2 * pr + 1][i].y, wv[i].x, wv[i].y);
        acc(xv[2 * pr][i].z, xv[2 * pr][i].w, xv[2 * pr + 1][i].z, xv[2 * pr + 1][i].w, wv[i].z, wv[i].w);
      }
    }
    float sum = (lane & 2) ? ((lane & 1) ? d[1][2] : d[1][0]) : ((lane & 1) ? d[0][2] : d[0][0]);
#pragma unroll
    for (int off = 16; off >= 4; off >>= 1) sum += __shfl_xor_sync(0xffffffffu, sum, off);
    if (lane < 4) g_gate[row + lane] = bf16_round(rcp(1.0f + __expf(-bf16_round(sum))));
    if (lane == 0 && row + 2 * 48 * 4 < S_LEN) {
      mbar_expect_tx(gb + 8 * (it & 1), 8192);
      bulk_load(buf + (it & 1) * 8192, maps.x + (size_t)(row + 2 * 48 * 4) * DM, 8192, gb + 8 * (it & 1));
    }
  }
}

constexpr float Q_SCALE = 0.08838834764831845f * 1.4426950408889634f;
__device__ __forceinline__ uint32_t qkv_consumer(const Maps& maps, uint32_t smem0, uint32_t sn, uint32_t (&p)[32]) {
  PHASE_PROLOGUE
  float acc[128];
#pragma unroll
  for (int i = 0; i < 128; i++) asm volatile("mov.b32 %0, 0;" : "=f"(acc[i]));
  uint32_t stage = 0, phase = 0, prev_stage = 0;
  const uint32_t stg = sbase + G_STG_OFF + wg * 18432;
  const int st_row = warp * 16 + (lane & 7) + ((lane >> 3) & 1) * 8;
  const int st_cb = lane >> 4;
  uint32_t pend[32];
  int m_tile, group;
  qkv_tile(maps, 0, m_tile, group);
  auto put_box = [&](uint32_t buf, const uint32_t* v) {
#pragma unroll
    for (int jp = 0; jp < 4; jp++) {
      const int chunk = jp * 2 + st_cb;
      const uint32_t addr = buf + st_row * 128 + ((chunk ^ (st_row & 7)) << 4);
      stmatrix_x4(addr, v[jp * 4], v[jp * 4 + 1], v[jp * 4 + 2], v[jp * 4 + 3]);
    }
  };
  GT(gti++)
#pragma unroll
  for (int i = 0; i < 32; i++) pend[i] = 0;
#pragma unroll 1
  for (int it = 0;; it++) {
    const int nk = it == 2 ? 16 : 8;
#pragma unroll 1
    for (int kt = 0; kt < nk; kt++) {
      mbar_wait((bar + B_GFULL) + 8 * stage, phase);
      GT(gti++)
      const uint64_t da0 = make_desc(sbase + stage * G_STAGE_BYTES + wg * 8192, 16, 1024, DESC_SW128);
      const uint64_t db0 = make_desc(sbase + stage * G_STAGE_BYTES + G_A_BYTES, 8192, 1024, DESC_SW128);
      asm volatile("{\n.reg .pred p;\nsetp.ne.u32 p, %0, 0;\n@p bar.sync 3, 256;\n}\n" ::"r"((uint32_t)(wg && kt == nk - 1))
                   : "memory");
      wgmma_fence();
#pragma unroll
      for (int kk = 0; kk < 4; kk++) {
        wgmma_m64n256_ss_tb(acc, desc_add(da0, kk * 2), desc_add(db0, kk * 128), (kt | kk) != 0);
      }
      wgmma_commit();
      asm volatile("{\n.reg .pred p;\nsetp.ne.u32 p, %0, 0;\n@p bar.arrive 3, 256;\n}\n" ::"r"((uint32_t)(!wg && kt == nk - 1))
                   : "memory");
      const uint32_t when = it == 0 ? 0 : wg ? 0xAA : 0x55;
      if ((when >> kt) & 1) {
        const int c = kt >> 1;
        st_wait(bar, wg, sn - (it + c == 1 ? 1 : 2));
        const uint32_t buf = stg + (c & 1) * 8192;
        switch (c) {
          case 0: put_box(buf, p); break;
          case 1: put_box(buf, p + 16); break;
          case 2: put_box(buf, pend); break;
          default: put_box(buf, pend + 16); break;
        }
        st_post(bar, wg, wtid, sn, it + c == 5 ? ST_BOX1P : ST_BOX1, it - 1, buf, group * 256 + c * 64,
                m_tile * 128 + wg * 64, c == 3 ? CNT_KV + (sn > 8) : -1);
        sn++;
      }
      wgmma_wait<1>();
      mbar_arrive_if((bar + B_GEMPTY) + 8 * prev_stage, wtid == 32 && kt > 0);
      prev_stage = stage;
      if (++stage == G_STAGES) { stage = 0; phase ^= 1; }
    }
    wgmma_wait<0>();
    fence_regs(acc);
    GT(gti++)
    mbar_arrive_if((bar + B_GEMPTY) + 8 * prev_stage, wtid == 32);
    if (it == G_NTILES - 1) break;
#pragma unroll
    for (int j = 0; j < 32; j++) {
      p[j] = pack_bf16(acc[2 * j], acc[2 * j + 1]);
      pend[j] = pack_bf16(acc[64 + 2 * j], acc[64 + 2 * j + 1]);
    }
  }
  ST(19)
  st_wait(bar, wg, sn - 1);
  mbar_wait(bar + B_GEMPTY, 1);
#pragma unroll
  for (int j = 0; j < 32; j++) pend[j] = pack_bf16(acc[2 * j] * Q_SCALE, acc[2 * j + 1] * Q_SCALE);
  put_box(sbase + wg * 8192, pend);
  put_box(sbase + 16384 + wg * 8192, pend + 16);
#pragma unroll
  for (int j = 0; j < 32; j++) p[j] = pack_bf16(acc[64 + 2 * j] * Q_SCALE, acc[65 + 2 * j] * Q_SCALE);
  put_box(stg, p);
  put_box(stg + 8192, p + 16);
  st_post(bar, wg, wtid, sn, ST_PEER, 0, stg, sn >> 4, 0, 0);
  sn++;
  GT(gti++)
  return sn;
}

constexpr int A_TILE = 128 * 128 * 2;
constexpr int A_Q_OFF = 0;
constexpr int A_K_OFF = 2 * A_TILE;
constexpr int A_V_OFF = 4 * A_TILE;
constexpr int A_O_OFF = 6 * A_TILE;

constexpr uint32_t A_STEPS = 17;
__device__ __forceinline__ int item_m(uint32_t it) { return it & 15; }
__device__ __forceinline__ int item_h(uint32_t it) { return it >> 4; }

constexpr int C_H0 = 16, C_U = C_H0 + 4096 + 112, C_SLOT = C_U + 4096;
constexpr int C_H1 = 2 * C_SLOT + 80;
constexpr int C_X_OFF = C_H1 + 4096 + 48;

__device__ __forceinline__ uint32_t item_of(const Maps& maps, uint32_t r) {
  const uint32_t b = maps.id[blockIdx.x & 127][1];
  return (b >> 4) * 64 + r * 16 + ((b ^ ((r & 1) * 15)) & 15);
}

constexpr uint32_t C_SIDE = 48;
__device__ __forceinline__ uint32_t conv_first(const Maps& maps) {
  const uint32_t b = maps.id[blockIdx.x & 127][1];
  return (b >> 4) * 128 + (b & 15);
}

__device__ __forceinline__ void conv_consumer(const Maps& maps, uint32_t smem0, uint32_t first, uint32_t step,
                                              uint32_t end) {
  PHASE_PROLOGUE
  const uint32_t full = bar + B_CFULL + wg * 16;
  const uint32_t ca = sbase + (wg ? A_V_OFF + A_TILE : A_Q_OFF);
  const int w4 = __shfl_sync(0xffffffffu, warp, 0);
  auto fetch = [&](uint32_t c, uint32_t slot) {
    if (w4 == 2 && c < end) {
      if (elect_one()) {
        const uint32_t sb = ca + slot * C_SLOT, fb = full + 8 * slot;
        const uint64_t pol = policy_evict_first();
        mbar_expect_tx(fb, 2 * 4096);
        bulk_load_hint(sb + C_H0, maps.ssm_k + (size_t)c * S_LEN, 4096, fb, pol);
        bulk_load_hint(sb + C_U, g_kvT + (size_t)c * S_LEN, 4096, fb, pol);
      }
    }
  };
  auto shift_h = [&](uint32_t so) {
    const uint32_t a = ca + so + C_H0 + wtid * 16;
#pragma unroll
    for (int i = 0; i < 2; i++) {
      uint32_t p;
      const uint4 v = lds128(a + i * 2048);
      asm volatile("ld.shared.u32 %0, [%1];" : "=r"(p) : "r"(a + i * 2048 - 4));
      sts128(ca + C_H1 + wtid * 16 + i * 2048, make_uint4(__byte_perm(p, v.x, 0x5432), __byte_perm(v.x, v.y, 0x5432),
                                                      __byte_perm(v.y, v.z, 0x5432), __byte_perm(v.z, v.w, 0x5432)));
    }
  };
  if (wtid == 96 && wg) { TD(15) }
  fetch(first, 0);
  if (wtid < 17)
    sts128(ca + (wtid >> 3) * C_SLOT + (wtid & 7 ? 4096 + (wtid & 7) * 16 : (wtid & 16) * 4), make_uint4(0, 0, 0, 0));
  fence_proxy_async();
  const uint32_t ha = ca + ((lane & 4) ? C_H1 : C_H0) + 4 * ((lane & 3) - (lane >> 3)) + w4 * 256;
  const uint32_t ua = ca + C_U + w4 * 256 + (lane >> 4) * 1024 + (lane & 15) * 16;
  const uint32_t xa = ca + C_X_OFF + lane * 8, xw = xa + w4 * 3072;
  uint32_t xg[3];
#pragma unroll
  for (int k = 0; k < 3; k++) {
    const int w = (w4 + k + 1) & 3;
    xg[k] = xa + (w * 12 + w4 - w - (w < w4 ? 1 : 0)) * 256;
  }
  const bool pp = step != 16;
  uint32_t h[2][16];
  const uint32_t hs = (lane & 4) ? 0 : C_SLOT;
  auto load_h = [&](uint32_t so, int a) {
#pragma unroll
    for (int i = 0; i < 16; i++)
      asm volatile("ld.shared.u32 %0, [%1];"
                   : "=r"(h[a & 1][i])
                   : "r"(ha + so + 1024 * a + 32 * (i >> 2) + (i & 1) * 128 + (~i & 2) * 8));
  };
  mbar_wait(full, 0);
  named_bar_sync(1 + wg, 128);
  shift_h(0);
  named_bar_sync(1 + wg, 128);
  fetch(first + step, 1);
  load_h(0, 0);
  load_h(0, 1);
  mbar_wait(bar + B_OFREE, 0);
  mbar_wait(bar + B_OFREE + 8, 0);
  uint32_t n = 0, ch = first;
  for (; ch < end; n++, ch += step) {
    CT(0)
    const uint32_t so = (n & 1) * C_SLOT, ho = (n & 1) * hs;
    uint32_t db = (uint32_t)make_desc(ca + so + C_U - 16, 16, 0, 0);
    asm volatile("" : "+r"(db));
    uint32_t dsk = __ldg(reinterpret_cast<const unsigned short*>(maps.ssm_D) + (ch | (lane & rt_zero)));
    float d[4][32], own[16];
    auto mma = [&](int a) {
      wgmma_fence();
#pragma unroll
      for (int c = a; c < 4; c++)
#pragma unroll
        for (int b = 0; b < 4; b++)
          wgmma_m64n64_rs(d[c], &h[a & 1][4 * b], (8ull << 32) | (db + 64 * (c - a) - 2 * b), (a | b) != 0);
      wgmma_commit();
    };
    auto put = [&](int c) {
      fence_regs(d[c]);
#pragma unroll
      for (int e = 0; e < 2; e++) {
        if (c == 0) asm volatile("mov.b32 %0, %1;" : "=f"(own[e]) : "f"(d[c][e]));
        else own[4 * c + e] += d[c][e];
        own[4 * c + 2 + e] = d[c][4 + e] + d[c][2 + e];
        if (c < 3) asm volatile("mov.b32 %0, %1;" : "=f"(own[4 * c + 4 + e]) : "f"(d[c][30 + e]));
      }
#pragma unroll
      for (int j = 1; j < 4; j++)
        asm volatile("{\n.reg .pred p;\nsetp.lt.s32 p, %3, 4;\n@p st.shared.v2.u32 [%0], {%1, %2};\n}\n" ::"r"(
                         xw + (3 * c + j - 1) * 256),
                     "r"(pack_bf16(d[c][8 * j] + d[c][8 * j - 2], d[c][8 * j + 1] + d[c][8 * j - 1])),
                     "r"(pack_bf16(d[c][8 * j + 4] + d[c][8 * j + 2], d[c][8 * j + 5] + d[c][8 * j + 3])),
                     "r"(c < 3 ? 0 : w4 + j)
                     : "memory");
    };
    named_bar_sync(pp ? 4 + wg : 1 + wg, pp ? 256 : 128);
    CT(1)
    mma(0);
    mma(1);
    wgmma_wait<1>();
    load_h(ho, 2);
    put(0);
    mma(2);
    CT(2)
    wgmma_wait<1>();
    load_h(ho, 3);
    put(1);
    mma(3);
    asm volatile("{\n.reg .pred p;\nsetp.ne.u32 p, %1, 0;\n@p bar.arrive %0, 256;\n}\n" ::"r"(5 - wg), "r"((uint32_t)pp) : "memory");
    CT(3)
    uint32_t sk[8];
    asm volatile("ldmatrix.sync.aligned.m8n8.x4.trans.shared.b16 {%0, %1, %2, %3}, [%4];"
                 : "=r"(sk[0]), "=r"(sk[1]), "=r"(sk[2]), "=r"(sk[3])
                 : "r"(ua + so));
    asm volatile("ldmatrix.sync.aligned.m8n8.x4.trans.shared.b16 {%0, %1, %2, %3}, [%4];"
                 : "=r"(sk[4]), "=r"(sk[5]), "=r"(sk[6]), "=r"(sk[7])
                 : "r"(ua + so + 2048));
    mbar_wait(full + 8 * (~n & 1), (((n + 1) >> 1) & 1) ^ (ch + step < end ? 0 : 1));
    named_bar_sync(1 + wg, 128);
    shift_h(C_SLOT - so);
    wgmma_wait<1>();
    put(2);
    uint32_t dep = 0;
#pragma unroll
    for (int i = 0; i < 8; i++) dep |= sk[i] = mul_bf2(sk[i], dsk | (dsk << 16));
    CT(4)
    wgmma_wait<0>();
    put(3);
    named_bar_sync((1 + wg) | (dep & rt_zero), 128);
    CT(5)
    fetch(ch + 2 * step, n & 1);
    if (wtid == 96 && n) note(bar, CNT_Y2 + (((ch - step) & 127) >= 112));
    uint2 q[12];
#pragma unroll
    for (int i = 0; i < 12; i++) {
      if (i >= 3) {
        asm volatile("ld.shared.v2.u32 {%0, %1}, [%2];" : "=r"(q[i].x), "=r"(q[i].y) : "r"(xg[i % 3] + (i / 3) * 768));
      } else {
        q[i] = make_uint2(0, 0);
        asm volatile("{\n.reg .pred p;\nsetp.gt.s32 p, %3, 2;\n@p ld.shared.v2.u32 {%0, %1}, [%2];\n}\n"
                     : "+r"(q[i].x), "+r"(q[i].y)
                     : "r"(xg[i]), "r"(w4 + i));
      }
    }
    load_h(hs - ho, 0);
    load_h(hs - ho, 1);
    CT(6)
    uint32_t* dst = reinterpret_cast<uint32_t*>(g_y2T + (size_t)ch * S_LEN) + 64 * w4 + (lane ^ 28);
#pragma unroll
    for (int f = 0; f < 4; f++) {
#pragma unroll
      for (int k = 0; k < 3; k++) {
        own[4 * f] += bf_lo(q[3 * f + k].x);
        own[4 * f + 1] += bf_hi(q[3 * f + k].x);
        own[4 * f + 2] += bf_lo(q[3 * f + k].y);
        own[4 * f + 3] += bf_hi(q[3 * f + k].y);
      }
#pragma unroll
      for (int i = 0; i < 2; i++) {
        dst[256 * f + 32 * i] = add_bf2(pack_bf16(own[4 * f + 2 * i], own[4 * f + 2 * i + 1]), sk[2 * f + i]);
      }
    }
    CT(7)
  }
  named_bar_sync(1 + wg, 128);
  if (wtid == 96 && wg) { TD(8) }
  if (wtid == 96) cnt_signal_release(CNT_Y2 + (((ch - step) & 127) >= 112), 1);
  if (wtid == 64) note(bar, CNT_DONE);
  if (wtid == 96 && wg) { TD(9) }
}

__device__ __forceinline__ void attn_producer(const Maps& maps, uint32_t sbase, int pass, bool dry) {
  const uint32_t bar = sbase + BAR_OFF;
  const uint32_t q_full = bar + B_QFULL, q_empty = bar + B_QEMPTY;
  const uint32_t k_full = bar + B_KFULL, k_empty = bar + B_KEMPTY, v_full = bar + B_VFULL, v_empty = bar + B_VEMPTY;
  int ndrained = 0;
  auto wait = [&](uint32_t b, uint32_t par) {
    if (!dry) mbar_wait_sleep(b, par);
  };
  auto drained = [&](int upto) {
#pragma unroll 1
    for (; ndrained <= upto; ndrained++) wait(bar + B_GEMPTY + 8 * ndrained, 1);
  };
  uint32_t st = 0, ph = 1, vs = 0, vp = 1;
  int pend_j = -1, pend_h = 0;
  PT_DECL
  cnt_wait(CNT_KV + pass, dry ? 0 : 512);
  drained(1);
  if (!dry) {
    mbar_arrive(q_full);
    mbar_expect_tx(q_full + 8, A_TILE);
  }
  mbar_arrive_cluster_if(bar + B_QPEER, ~blockIdx.x & 1, !dry);
#pragma unroll 1
  for (int round = dry; round < 3; round++) {
    const uint32_t item = item_of(maps, round);
    const int m = round == 2 ? -1 : dry ? 0 : item_m(item), h = (item >> 6) * 4 + round * 2;
    const int tpost = m >= 3 ? m - 1 : m;
#pragma unroll 1
    for (int t = m < 0 ? -1 : 0; t <= m; t++) {
      const int j = (t < m && round) ? m - 1 - t : t;
      if (t >= 0) {
        drained(1 + st);
        wait(k_empty + 8 * st, ph);
        if (!dry) {
          PT
          mbar_expect_tx(k_full + 8 * st, A_TILE);
          tma_load_3d(sbase + A_K_OFF + st * A_TILE, &maps.k, k_full + 8 * st, 0, j * 128, h);
        }
        if (++st == 2) { st = 0; ph ^= 1; }
      }
      if (pend_j >= 0) {
        drained(3);
        wait(v_empty + 8 * vs, vp);
        if (!dry) {
          mbar_expect_tx(v_full + 8 * vs, A_TILE);
          tma_load_3d(sbase + A_V_OFF + (vs ^ 1) * A_TILE, &maps.v, v_full + 8 * vs, 0, pend_j * 128, pend_h);
        }
        if (++vs == 2) { vs = 0; vp ^= 1; }
      }
      pend_j = j;
      pend_h = h;
      if (t == tpost && round == 1) {
        if (pass) {
          cnt_wait(CNT_PREP + 1, dry ? 0 : 516);
          cnt_wait(CNT_CTX, dry ? 0 : 2 * A_ITEMS);
          asm volatile("cp.async.bulk.prefetch.L2.global [%0], 4096;" ::"l"(maps.ssm_k + (size_t)conv_first(maps) * S_LEN));
          if (!dry)
            asm volatile("cp.async.bulk.prefetch.L2.global [%0], 4096;" ::"l"(g_kvT + (size_t)conv_first(maps) * S_LEN));
        }
        wait(q_empty, 0);
        if (!dry) mbar_arrive(q_full);
      }
    }
  }
}

__device__ __forceinline__ uint32_t attn_consumer(const Maps& maps, uint32_t smem0, uint32_t sn, uint32_t (&p)[32]) {
  PHASE_PROLOGUE
  float s[64], o[64], e[32];
  const uint32_t q_full = bar + B_QFULL, q_empty = bar + B_QEMPTY;
  const uint32_t k_full = bar + B_KFULL, k_empty = bar + B_KEMPTY, v_full = bar + B_VFULL;
  uint32_t dep = 0;
  constexpr int MIDJ = 5;
  float l0 = 0.f, l1 = 0.f, b0 = 0.f, b1 = 0.f;
  const int sched_own = 4 + wg, sched_other = 5 - wg;

  const uint32_t qd0 = (uint32_t)make_desc(sbase + A_Q_OFF + wg * 8192, 16, 0, 0);
  const uint32_t kd0 = (uint32_t)make_desc(sbase + A_K_OFF, 16, 0, 0);
  const uint32_t vd0 = (uint32_t)make_desc(sbase + A_V_OFF, 16384, 0, 0);
  constexpr uint64_t DHI = DESC_SW128 | ((uint64_t)(1024 >> 4) << 32);
  constexpr uint32_t DST = A_TILE >> 4;
  auto issue_qk = [&](uint32_t qd, uint32_t kd, uint32_t z = 0) {
#pragma unroll
    for (int kk = 0; kk < 8; kk++) {
      const uint32_t off = ((kk >> 2) * 16384 + (kk & 3) * 32) >> 4;
      wgmma_m64n128_ss(s, DHI | (qd + off), DHI | (kd + off), kk ? 1 : z);
    }
    wgmma_commit();
  };
  auto issue_pv = [&](uint32_t vd, bool accumulate, int nk) {
#pragma unroll
    for (int kk = 0; kk < 8; kk++) {
      if (kk < nk)
        wgmma_m64n128_rs_tb(o, p[4 * kk], p[4 * kk + 1], p[4 * kk + 2], p[4 * kk + 3], DHI | (vd + kk * 128),
                            accumulate || (kk != 0));
    }
    wgmma_commit();
  };
  auto exp_lo = [&](float& a0, float& a1) {
#pragma unroll
    for (int j = 0; j < 8; j++) {
      e[4 * j] = ex2(s[4 * j]);
      e[4 * j + 1] = ex2(s[4 * j + 1]);
      e[4 * j + 2] = ex2(s[4 * j + 2]);
      e[4 * j + 3] = ex2(s[4 * j + 3]);
      a0 += e[4 * j];
      a0 += e[4 * j + 1];
      a1 += e[4 * j + 2];
      a1 += e[4 * j + 3];
      if (j == MIDJ) dep = (__float_as_uint(a0) | __float_as_uint(a1)) & rt_zero;
    }
  };
  auto pack_lo = [&]() {
#pragma unroll
    for (int j = 0; j < 16; j++) p[j] = pack_bf16(e[2 * j], e[2 * j + 1]);
  };
  auto finish_p = [&](float& a0, float& a1) {
    pack_lo();
#pragma unroll
    for (int j = 8; j < 16; j++) {
      const float e0 = ex2(s[4 * j]), e1 = ex2(s[4 * j + 1]), e2 = ex2(s[4 * j + 2]), e3 = ex2(s[4 * j + 3]);
      a0 += e0;
      a0 += e1;
      a1 += e2;
      a1 += e3;
      p[2 * j] = pack_bf16(e0, e1);
      p[2 * j + 1] = pack_bf16(e2, e3);
      if (j == 8 + MIDJ) dep = __float_as_uint(a0) & rt_zero;
    }
  };
  auto quad_sum = [&](float t) {
    t += __shfl_xor_sync(0xffffffffu, t, 1);
    return t + __shfl_xor_sync(0xffffffffu, t, 2);
  };
  auto write_o = [&](const float (&o)[64], float i0, float i1) {
    st_wait(bar, wg, sn - 1);
    const int st_row = warp * 16 + (lane & 7) + ((lane >> 3) & 1) * 8;
    const uint32_t so = sbase + A_O_OFF + wg * 18432 + st_row * 128;
#pragma unroll
    for (int j = 0; j < 16; j += 2)
      stmatrix_x4(so + (j >> 3) * 8192 + ((((j & 7) + (lane >> 4)) ^ (lane & 7)) << 4),
                  pack_bf16(o[4 * j] * i0, o[4 * j + 1] * i0), pack_bf16(o[4 * j + 2] * i1, o[4 * j + 3] * i1),
                  pack_bf16(o[4 * j + 4] * i0, o[4 * j + 5] * i0), pack_bf16(o[4 * j + 6] * i1, o[4 * j + 7] * i1));
  };
  auto store_o = [&](uint32_t r, int kind) {
    const uint32_t pass = sn >> 4, it = item_of(maps, 2 * pass + r);
    st_post(bar, wg, wtid, sn, kind, 2, sbase + A_O_OFF + wg * 18432, item_h(it) * 128,
            item_m(it) * 128 + wg * 64, CNT_CTX + pass);
    sn++;
  };
  auto mask_half = [&](float* sh) {
    const int u = warp * 16 + (lane >> 2) - (lane & 3) * 2;
#pragma unroll
    for (int j = 0; j < 8; j++) {
      if (8 * j > u) sh[4 * j] = -INFINITY;
      if (8 * j + 1 > u) sh[4 * j + 1] = -INFINITY;
      if (8 * j - 8 > u) sh[4 * j + 2] = -INFINITY;
      if (8 * j - 7 > u) sh[4 * j + 3] = -INFINITY;
    }
  };
  ST(0)
  mbar_wait(k_full, 0);
  ST(20)
  named_bar_sync(sched_own, 256);
  ST(21)
#pragma unroll
  for (int i = 0; i < 64; i++) asm volatile("mov.b32 %0, 0;" : "=f"(s[i]));
  wgmma_fence();
  issue_qk(qd0, kd0, rt_zero);
  named_bar_arrive(sched_other, 256);
  ST(36) ST(37) ST(38)
  ST(22)
#pragma unroll
  for (int i = 0; i < 64; i++) asm volatile("mov.b32 %0, 0;" : "=f"(o[i]));
  wgmma_wait<0>();
  fence_regs(s);
  mbar_arrive_if(k_empty, wtid == 32);
  uint32_t g = 0;
  uint32_t rnd = 0;
  int rem = item_m(item_of(maps, 0));
  uint32_t first = 1;
  uint32_t fl = 0;
#define redo (fl & 1)
#define shifted (fl & 2)
  float d0 = 0.f, d1 = 0.f;
  float pi0 = 1.f, pi1 = 1.f;
  ST(1)
  for (;;) {
    if (shifted) {
#pragma unroll
      for (int j = 0; j < 16; j++) {
        s[4 * j] -= d0;
        s[4 * j + 1] -= d0;
        s[4 * j + 2] -= d1;
        s[4 * j + 3] -= d1;
      }
    }
    if (rem == 0 && !redo) {
      mbar_arrive_if(q_empty + 8 * (rnd & 1), wtid == 96);
      rnd++;
      if (wg == 0) mask_half(s);
      else mask_half(s + 32);
    }
    for (;;) {
      const bool kill = rem == 0 && wg == 0;
      const uint32_t kd = kd0 + ((g + 1) & 1) * DST, vd = vd0 + (~g & 1) * DST;
      float a0 = 0.f, a1 = 0.f;
      exp_lo(a0, a1);
      fence_regs(e);
      const uint32_t kb = k_full + 8 * ((g + 1) & 1);
      const uint32_t kpar = ((((g + 1) >> 1) & 1) ^ (g == A_STEPS - 1 ? 1u : 0u)) | dep;
      if (!mbar_try(kb, kpar)) mbar_wait(kb, kpar | ((__float_as_uint(a0) | __float_as_uint(a1)) & rt_zero));
      wgmma_wait<0>();
      fence_regs(o);
      ST(g < 4 ? 24 + 3 * g : 39)
      if (kill) {
        mbar_arrive_if(kb + (B_VEMPTY - B_KFULL), wtid == 64 && !redo && g > 0);
        fence_regs(e);
        pack_lo();
#pragma unroll
        for (int j = 16; j < 32; j++) asm volatile("mov.u32 %0, 0;" : "=r"(p[j]));
        goto check;
      }
#pragma unroll
      for (int i = 32; i < 64; i++) asm volatile("" : "+f"(s[i])::"memory");
      mbar_arrive_if(kb + (B_VEMPTY - B_KFULL), wtid == 64 && !redo && g > 0);
      finish_p(a0, a1);
      if (__any_sync(0xffffffffu, !(mbar_try(v_full + 8 * (g & 1), ((g >> 1) & 1) | dep) &
                                    mbar_try(q_full + 8 * (rnd & 1), ((rnd >> 1) & 1) | dep)) ||
                                      !(a0 + a1 < 1.0995116e12f) || !(fminf(a0, a1) > (first ? 9.094947e-13f : -1.f)))) {
      check:
        bool bad = !(a0 + a1 < 1.0995116e12f);
        if (first) bad |= !(fminf(quad_sum(a0), quad_sum(a1)) > 9.094947e-13f);
        if (!redo && __any_sync(0xffffffffu, bad)) {
          d0 = d1 = first ? -INFINITY : 0.f;
#pragma unroll
          for (int j = 0; j < 16; j++) {
            if (j < 8 || !kill) {
              d0 = fmaxf(d0, fmaxf(s[4 * j], s[4 * j + 1]));
              d1 = fmaxf(d1, fmaxf(s[4 * j + 2], s[4 * j + 3]));
            }
          }
#pragma unroll
          for (int x = 1; x <= 2; x++) {
            d0 = fmaxf(d0, __shfl_xor_sync(0xffffffffu, d0, x));
            d1 = fmaxf(d1, __shfl_xor_sync(0xffffffffu, d1, x));
          }
          b0 += d0;
          b1 += d1;
          if (!first) {
            const float al0 = ex2(-d0), al1 = ex2(-d1);
            l0 *= al0;
            l1 *= al1;
#pragma unroll
            for (int j = 0; j < 16; j++) {
              o[4 * j] *= al0;
              o[4 * j + 1] *= al0;
              o[4 * j + 2] *= al1;
              o[4 * j + 3] *= al1;
            }
          }
          fl = 3;
          break;
        }
        mbar_wait(v_full + 8 * (g & 1), (g >> 1) & 1);
        mbar_wait(q_full + 8 * (rnd & 1), (rnd >> 1) & 1);
      }
      ST(g < 4 ? 25 + 3 * g : 39)
      named_bar_sync(sched_own, 256);
      ST(g < 4 ? 26 + 3 * g : 39)
      if (g == A_STEPS - 1) {
        if (first) write_o(o, pi0, pi1);
        fence_regs(o);
        wgmma_fence();
        issue_pv(vd, !first, 8);
        named_bar_arrive(sched_other, 256);
        if (first) store_o(0, ST_BOX2);
        pi0 = rcp(quad_sum(l0 + a0));
        pi1 = rcp(quad_sum(l1 + a1));
        goto done;
      }
      wgmma_fence();
      issue_qk(qd0 + (rnd & 1) * DST, kd);
      if (first && g) write_o(o, pi0, pi1);
      fence_regs(o);
      if (kill) {
        wgmma_fence();
        issue_pv(vd, !first, 4);
      } else {
        wgmma_fence();
        issue_pv(vd, !first, 8);
      }
      named_bar_arrive(sched_other, 256);
      fl &= 2;
      l0 += a0;
      l1 += a1;
      if (rem == 0 || first) {
        if (first && g) store_o(0, ST_BOX2);
        first = rem == 0;
        if (first) {
          pi0 = rcp(quad_sum(l0));
          pi1 = rcp(quad_sum(l1));
          l0 = l1 = b0 = b1 = 0.f;
          fl = 0;
          rem = item_m(item_of(maps, 1)) + 1;
        }
      }
      rem--;
      g++;
      wgmma_wait<1>();
      fence_regs(s);
      mbar_arrive_if(kb + (B_KEMPTY - B_KFULL), wtid == 32);
      ST(g + 1)
      if (rem == 0 || shifted) {
        d0 = b0;
        d1 = b1;
        break;
      }
    }
  }
done:
#undef redo
#undef shifted
  wgmma_wait<0>();
  fence_regs(o);
  mbar_arrive_if(bar + B_VEMPTY, wtid == 64);
  write_o(o, pi0, pi1);
  store_o(1, ST_BOX2W + (sn >> 4));
  ST(18)
  return sn;
}

constexpr int O_STAGES = 5;
constexpr int O_STAGE_BYTES = 32768;
constexpr int O_Y_OFF = 5 * 32768;
constexpr int O_X_OFF = 6 * 32768 + 2048;
constexpr int O_NK = HDIM / 64;

__device__ __forceinline__ uint32_t out_stage(uint32_t st) { return ((0x41230u >> (4 * st)) & 7) * O_STAGE_BYTES; }

__device__ __forceinline__ void out_producer(const Maps& maps, uint32_t sbase, bool dry) {
  const uint32_t bar = sbase + BAR_OFF;
  const uint32_t rank = blockIdx.x & 1;
  const int m_tile = maps.id[blockIdx.x][2] & 15, n_tile = maps.id[blockIdx.x][2] >> 4;
  uint32_t stage = 0, phase = 0;
  const int kx = dry ? O_STAGES : 17 + (blockIdx.x >> 1) % 12;
#pragma unroll 1
  for (int ki = 0; ki <= O_STAGES; ki++) {
    if (ki < O_STAGES) {
      constexpr uint32_t LASTB = (B_KEMPTY + 8) | (B_KEMPTY << 8) | ((B_QEMPTY + 8) << 16) | ((B_VEMPTY + 8) << 24);
      if (ki > 0 && !dry) mbar_wait_sleep(bar + ((LASTB >> (8 * ki - 8)) & 255), (0x12 >> ki) & 1);
      mbar_arrive_cluster_if(bar + B_OEMPTY + 8 * ki, 0, !dry);
      mbar_arrive_cluster_if(bar + B_OEMPTY + 8 * ki, 1, !dry);
      if (!dry) {
        mbar_expect_tx(bar + B_OFULL + 8 * ki, O_STAGE_BYTES);
        tma_load_4d(sbase + out_stage(ki), &maps.oa, bar + B_OFULL + 8 * ki, ((ki & 14) * 4 + (ki & 1)) * 64, m_tile);
      }
    }
    if (ki > 0 && !dry) {
      const int k = ki - 1;
      mbar_wait_sleep(bar + B_OEMPTY + 8 * k, 0);
      tma_load_2d_mc(sbase + out_stage(k) + 16384 + rank * 8192, &maps.ob, bar + B_OFULL + 8 * k, n_tile * 128 + rank * 64,
                     ((k & 14) * 4 + (k & 1)) * 64, (uint16_t)3);
    }
    if (dry) ki += O_STAGES - 1;
  }
  phase = 1;
#pragma unroll 1
  for (int ki = O_STAGES; ki < (dry ? O_STAGES + 1 : O_NK); ki++) {
    const int kt = (ki & 14) * 4 + (ki >> 4) * 2 + (ki & 1);
    const uint32_t fb = bar + B_OFULL + 8 * stage, eb = bar + B_OEMPTY + 8 * stage;
    const uint32_t sa = sbase + out_stage(stage);
    if (ki == (dry ? O_STAGES : 16)) cnt_wait(CNT_CTX + 1, dry ? 0 : 2 * A_ITEMS);
    if (ki == kx) {
      if (!dry) {
        mbar_wait_sleep(bar + B_OFREE, 0);
        mbar_wait_sleep(bar + B_OFREE + 8, 0);
        mbar_expect_tx(bar + B_OY, 32768);
        tma_load_4d(sbase + O_X_OFF, &maps.ox, bar + B_OY, n_tile * 128, m_tile);
        tma_load_4d(sbase + O_X_OFF + 16384, &maps.ox, bar + B_OY, n_tile * 128 + 64, m_tile);
      }
    }
    if (!dry) {
      mbar_wait_sleep(eb, phase);
      mbar_expect_tx(fb, O_STAGE_BYTES);
      tma_load_4d(sa, &maps.oa, fb, kt * 64, m_tile);
      tma_load_2d_mc(sa + 16384 + rank * 8192, &maps.ob, fb, n_tile * 128 + rank * 64, kt * 64, (uint16_t)3);
    }
    if (++stage == O_STAGES) { stage = 0; phase ^= 1; }
  }
  if (!dry) mbar_wait_sleep(bar + B_OY2, 0);
}

__device__ __forceinline__ void out_side(const Maps& maps, uint32_t smem0, const float (&gv)[4]) {
  PHASE_PROLOGUE
  const int m_tile = maps.id[blockIdx.x][2] & 15, n_tile = maps.id[blockIdx.x][2] >> 4;
  const int w4 = __shfl_sync(0xffffffffu, warp, 0);
  if (w4 == 0) {
    if (elect_one()) {
      mbar_expect_tx(bar + B_OY, 32768 - 4096);
      TD(10)
      GS(0)
      cnt_wait(CNT_Y2, DM - 128);
      GS(1)
      TD(7)
      for (const uint32_t t = clock(); (uint32_t)clock() - t < (blockIdx.x & 14) * 200;) __nanosleep(32);
      TD(11)
      GS(2)
      fence_proxy_async();
      tma_load_2d(sbase + O_Y_OFF, &maps.y, bar + B_OY, m_tile * 128, n_tile * 128);
      tma_load_2d(sbase + O_Y_OFF + 16384, &maps.y, bar + B_OY, m_tile * 128 + 64, n_tile * 128);
    }
  }
  mbar_wait_sleep(bar + B_OY, 0);
  const int st_row = warp * 16 + (lane & 7) + ((lane >> 3) & 1) * 8;
  const int mrow = (lane & 7) + ((lane >> 4) & 1) * 8;
  const int mchunk = warp * 2 + ((lane >> 3) & 1);
  const uint32_t xrow = sbase + O_X_OFF + st_row * 128;
  const uint32_t yrow = sbase + O_Y_OFF + mrow * 128 + ((mchunk ^ (lane & 7)) << 4);
  uint32_t y[7][4], x[7][4], om[4];
#pragma unroll
  for (int i = 0; i < 4; i++) om[i] = pack_bf16(1.0f - gv[i], 1.0f - gv[i]);
  auto xa = [&](int h, int i) { return xrow + h * 8192 + (i >> 2) * 16384 + ((((i & 3) * 2 + (lane >> 4)) ^ (lane & 7)) << 4); };
  auto load = [&](int r, int h, int i) {
    ldsm4t(y[r], yrow + h * 16384 + i * 2048);
    asm volatile("ldmatrix.sync.aligned.m8n8.x4.shared.b16 {%0, %1, %2, %3}, [%4];"
                 : "=r"(x[r][0]), "=r"(x[r][1]), "=r"(x[r][2]), "=r"(x[r][3])
                 : "r"(xa(h, i)));
  };
  auto store = [&](int r, int h, int i, uint32_t om0, uint32_t om1) {
    stmatrix_x4(xa(h, i), mul_bf2(om0, mul_bf2(x[r][0], y[r][0])), mul_bf2(om1, mul_bf2(x[r][1], y[r][1])),
                mul_bf2(om0, mul_bf2(x[r][2], y[r][2])), mul_bf2(om1, mul_bf2(x[r][3], y[r][3])));
  };
  if (wtid == 0) { TD(12) GS(3) }
#pragma unroll 1
  for (int h = 0; h < 2; h++) {
#pragma unroll
    for (int i = 0; i < 7; i++) load(i, h, i);
#pragma unroll
    for (int i = 0; i < 7; i++) store(i, h, i, h ? om[2] : om[0], h ? om[3] : om[1]);
  }
  if (wtid == 0) { TD(4) GS(4) }
  mbar_wait_sleep(bar + B_OY2, 0);
#pragma unroll
  for (int h = 0; h < 2; h++) load(h, h, 7);
#pragma unroll
  for (int h = 0; h < 2; h++) store(h, h, 7, om[2 * h], om[2 * h + 1]);
  __syncwarp();
  mbar_arrive_if(bar + B_OY + 8, lane == 0);
  if (wtid == 0) { TD(13) GS(6) }
#pragma unroll
  for (int i = 0; i < 4; i++) {
    const int h = i >> 1, c = i & 1;
    named_bar_sync(6 + i, 256);
    if (elect_one()) {
      fence_proxy_async();
      tma_store_4d(&maps.oc, sbase + O_X_OFF + c * 16384 + h * 8192 + w4 * 2048, n_tile * 128 + c * 64, 2 * w4,
                   2 * m_tile + h);
      tma_store_commit();
    }
  }
}

__device__ __forceinline__ void out_gemm(const Maps& maps, uint32_t smem0) {
  PHASE_PROLOGUE
  const int m_tile = maps.id[blockIdx.x][2] & 15;
  float acc[2][64];
  undef_regs(acc[0]);
  undef_regs(acc[1]);
  uint32_t stage = 0, phase = 0, prev_stage = 0;
  GT(gti++)
  const float* gp = g_gate + m_tile * 128 + warp * 2 + (lane >> 2) * 8;
  const float gv[4] = {__ldcg(gp), __ldcg(gp + 1), __ldcg(gp + 64), __ldcg(gp + 65)};
  if (wg == 1) {
    out_side(maps, smem0, gv);
    return;
  }
  constexpr uint64_t DHI = DESC_SW128 | ((uint64_t)(1024 >> 4) << 32);
#pragma unroll 1
  for (int kt = 0; kt < O_NK - 1; kt++) {
    uint32_t da = (uint32_t)make_desc(sbase + out_stage(stage), 16, 0, 0);
    uint32_t db = (uint32_t)make_desc(sbase + out_stage(stage) + 16384, 8192, 0, 0);
    asm volatile("" : "+r"(da), "+r"(db));
    mbar_wait(bar + B_OFULL + 8 * stage, phase);
    GT(gti++)
    constexpr int OWAIT = 2;
#pragma unroll
    for (int kk = 0; kk < 4; kk++) {
      wgmma_wait<OWAIT>();
      if (kk == OWAIT)
        mbar_arrive_cluster_if(bar + B_OEMPTY + 8 * prev_stage, wtid >> 6,
                               (wtid & 63) == 32 && kt > 0 && kt - 1 + O_STAGES < O_NK);
      wgmma_fence();
      wgmma_m64n128_ss_tb(acc[0], DHI | (da + kk * 2), DHI | (db + kk * 128), (kt | kk) != 0);
      wgmma_m64n128_ss_tb(acc[1], DHI | (da + 512 + kk * 2), DHI | (db + kk * 128), (kt | kk) != 0);
      wgmma_commit();
    }
    prev_stage = stage;
    if (++stage == O_STAGES) { stage = 0; phase ^= 1; }
  }
  {
    const uint32_t da = (uint32_t)make_desc(sbase + out_stage((O_NK - 1) % O_STAGES), 16, 0, 0);
    const uint32_t db = (uint32_t)make_desc(sbase + out_stage((O_NK - 1) % O_STAGES) + 16384, 8192, 0, 0);
    mbar_wait(bar + B_OFULL + 8 * ((O_NK - 1) % O_STAGES), ((O_NK - 1) / O_STAGES) & 1);
    GT(gti++)
#pragma unroll
    for (int h = 0; h < 2; h++) {
      wgmma_fence();
#pragma unroll
      for (int kk = 0; kk < 4; kk++)
        wgmma_m64n128_ss_tb(acc[h], DHI | (da + h * 512 + kk * 2), DHI | (db + kk * 128), 1);
      wgmma_commit();
    }
  }
  if (tid == 0) { TD(14) }
  const int st_row = warp * 16 + (lane & 7) + ((lane >> 3) & 1) * 8;
  const uint32_t rowa = sbase + O_X_OFF + st_row * 128;
  auto oa = [&](int i) { return rowa + (i >> 3) * 8192 + (i & 4) * 4096 + ((((i & 3) * 2 + (lane >> 4)) ^ (st_row & 7)) << 4); };
  uint32_t b[16][4];
  LT(6, 0)
  mbar_wait(bar + B_OY + 8, 0);
  LT(7, 0)
#pragma unroll
  for (int i = 0; i < 16; i++)
    asm volatile("ldmatrix.sync.aligned.m8n8.x4.shared.b16 {%0, %1, %2, %3}, [%4];"
                 : "=r"(b[i][0]), "=r"(b[i][1]), "=r"(b[i][2]), "=r"(b[i][3])
                 : "r"(oa(i)));
  uint32_t gg[4];
#pragma unroll
  for (int i = 0; i < 4; i++) gg[i] = pack_bf16(gv[i], gv[i]);
#pragma unroll
  for (int i = 0; i < 16; i++) {
    const int h = i >> 3;
    if (i == 0) wgmma_wait<1>();
    if (i == 8) wgmma_wait<0>();
    if (i % 8 == 0) fence_regs(acc[h]);
    const float* a = acc[h] + 8 * (i & 7);
    const uint32_t gg0 = gg[2 * h], gg1 = gg[2 * h + 1];
    stmatrix_x4(oa(i), fma_bf2(gg0, pack_bf16(a[0], a[1]), b[i][0]), fma_bf2(gg1, pack_bf16(a[2], a[3]), b[i][1]),
                fma_bf2(gg0, pack_bf16(a[4], a[5]), b[i][2]), fma_bf2(gg1, pack_bf16(a[6], a[7]), b[i][3]));
    if (i % 4 == 3) named_bar_arrive(6 + i / 4, 256);
  }
  GT(gti++)
}

__device__ __noinline__ void leave_kernel() {
  if (atomicAdd(g_cnt + CNT_DONE * 32, 1u) == 2 * gridDim.x - 1) {
    for (int i = 0; i < CNT_N; i++) g_cnt[i * 32] = 0;
  }
}

__device__ __noinline__ void side_jobs(const Maps& maps, uint32_t sbase) {
  const int w12 = __shfl_sync(0xffffffffu, threadIdx.x >> 5, 0);
  gate_rows(maps, sbase, (blockIdx.x - 128) * 12 + w12, w12, threadIdx.x & 31);
  fence_proxy_async();
  __syncthreads();
  if (threadIdx.x == 320) cnt_signal_release(CNT_PREP + 1, 1);
}

__global__ void __launch_bounds__(384, 1) fused_kernel(const __grid_constant__ Maps maps) {
  extern __shared__ __align__(1024) uint8_t smem_raw[];
  {
    const uint32_t sbase = __shfl_sync(0xffffffffu, smem_u32(smem_raw), 0);
    const uint32_t bar = sbase + BAR_OFF;
    const int tid = threadIdx.x;
    TL(0, 0) LT(0, 0)
    if (__shfl_sync(0xffffffffu, tid >> 5, 0) == 1 && blockIdx.x < 128) {
      if (elect_one()) {
        for (int i = 0; i < G_STAGES; i++) mbar_init(bar + B_GFULL + 8 * i, 1);
        fence_barrier_init();
        qkv_producer(maps, sbase, 0, true);
      }
    }
    if (tid == 0) {
      for (int i = 0; i < G_STAGES; i++) {
        mbar_init(bar + B_GEMPTY + 8 * i, 2);
        mbar_init(bar + B_SFULL + 8 * i, 4);
        mbar_init(bar + B_SFREE + 8 * i, 1);
      }
      for (int i = 0; i < 2; i++) {
        mbar_init(bar + B_OFREE + 8 * i, 1);
        mbar_init(bar + B_QFULL + 8 * i, 1);
        mbar_init(bar + B_QEMPTY + 8 * i, 2);
        mbar_init(bar + B_KFULL + 8 * i, 1);
        mbar_init(bar + B_KEMPTY + 8 * i, 2);
        mbar_init(bar + B_VFULL + 8 * i, 1);
        mbar_init(bar + B_VEMPTY + 8 * i, 2);
      }
      for (int i = 0; i < O_STAGES; i++) {
        mbar_init(bar + B_OFULL + 8 * i, 1);
        mbar_init(bar + B_OEMPTY + 8 * i, 2);
      }
      mbar_init(bar + B_OY, 2);
      mbar_init(bar + B_OY2, 1);
      mbar_init(bar + B_OY + 8, 4);
      mbar_init(bar + B_QPEER, 1);
      for (int i = 0; i < 8; i++) mbar_init(bar + B_CFULL + 8 * i, 1);
      for (int i = 0; i < CNT_N; i++) asm volatile("st.shared.u32 [%0], 0;" ::"r"(bar + B_PEND + 4 * i) : "memory");
      fence_barrier_init();
    }
    __syncthreads();
    asm volatile("barrier.cluster.arrive.relaxed.aligned;" ::: "memory");
    if (blockIdx.x >= 128) side_jobs(maps, sbase);
  }
  uint32_t smem0 = smem_u32(smem_raw);
  PHASE_PROLOGUE
  const bool mainc = blockIdx.x < 128;
  TL(0, 1)

  if (wg != 2) {
    reg_alloc<232>();
    if (wg == 1) named_bar_arrive(4, 256);
    mbar_wait(bar + B_OFREE + 8, mainc);
    if (mainc) {
      uint32_t sn = 0, p[32];
#pragma unroll
      for (int i = 0; i < 32; i++) asm volatile("" : "=r"(p[i]));
#pragma unroll 1
      do {
        sn = qkv_consumer(maps, smem_u32(smem_raw), sn, p);
        LT(1 + 2 * (sn >> 4), 0)
        sn = attn_consumer(maps, smem_u32(smem_raw), sn, p);
        LT(2 + 2 * (sn >> 4), 0)
      } while (sn < 16);
    }
    asm volatile("barrier.cluster.wait.acquire.aligned;" ::: "memory");
    if (mainc && __shfl_sync(0xffffffffu, threadIdx.x, 0) < 128) {
      named_bar_arrive(3, 256);
    } else {
      named_bar_sync(3, 256);
      const uint32_t b2 = blockIdx.x * 2 + (threadIdx.x >> 7);
      const uint32_t first = __shfl_sync(0xffffffffu, mainc ? conv_first(maps) : (b2 - 255) * 128 - C_SIDE, 0);
      conv_consumer(maps, smem_u32(smem_raw), first, mainc ? 16 : 1, (first | 127) + 1 - (mainc ? C_SIDE : 0));
    }
    if (mainc) out_gemm(maps, smem_u32(smem_raw));
    tma_store_wait_read<0>();
    TL2(3, 2) LT(5, 128)
  } else {
    reg_dealloc<40>();
    asm volatile("barrier.cluster.wait.acquire.aligned;" ::: "memory");
    const int w = __shfl_sync(0xffffffffu, tid >> 5, 0) - 8;
    if (w < 2) {
      if (mainc) agent_warp(maps, smem_u32(smem_raw));
      if (mainc && w == 0 && elect_one()) {
        mbar_wait_sleep(bar + B_OY, 0);
        mbar_expect_tx(bar + B_OY2, 4096);
        cnt_wait(CNT_Y2 + 1, 128);
        GS(5)
        const int id = maps.id[blockIdx.x][2];
        for (int i = 0; i < 2; i++)
          tma_load_2d(sbase + O_Y_OFF + i * 16384 + 112 * 128, &maps.y2, bar + B_OY2, (id & 15) * 128 + i * 64,
                      (id >> 4) * 128 + 112);
      }
    } else {
      if (mainc && elect_one()) {
        const bool dry = w == 2;
#pragma unroll 1
        for (int pass = dry; pass < 2; pass++) {
          if (!dry) qkv_producer(maps, sbase, pass, false);
          attn_producer(maps, sbase, pass, dry);
        }
        out_producer(maps, sbase, dry);
      }
      if (!mainc && tid == 352) {
        cnt_wait(CNT_PREP, 256);
        mbar_arrive(bar + B_OFREE);
        mbar_arrive(bar + B_OFREE + 8);
      }
      __syncwarp();
      if (w == 2) publisher(bar, tid & 31, mainc ? 3 : 2);
      if ((tid & 31) == 0) leave_kernel();
    }
  }
}

__device__ __forceinline__ float ldf(const bf16* p) { return __bfloat162float(*p); }
__global__ void __launch_bounds__(256) plain_gemm(const bf16* A, const bf16* B, bf16* C, int k, int ldb, int n) {
  __shared__ float sa[16][65], sb[16][64];
  const int tx = threadIdx.x & 15, ty = threadIdx.x >> 4, m0 = blockIdx.y * 64, n0 = blockIdx.x * 64;
  float acc[4][4] = {};
  for (int k0 = 0; k0 < k; k0 += 16) {
    for (int i = threadIdx.x; i < 1024; i += 256) {
      sa[i & 15][i >> 4] = ldf(A + (size_t)(m0 + (i >> 4)) * k + k0 + (i & 15));
      sb[i >> 6][i & 63] = ldf(B + (size_t)(k0 + (i >> 6)) * ldb + n0 + (i & 63));
    }
    __syncthreads();
    for (int kk = 0; kk < 16; kk++)
      for (int i = 0; i < 4; i++)
        for (int j = 0; j < 4; j++) acc[i][j] += sa[kk][ty * 4 + i] * sb[kk][tx + 16 * j];
    __syncthreads();
  }
  for (int i = 0; i < 4; i++)
    for (int j = 0; j < 4; j++) C[(size_t)(m0 + ty * 4 + i) * n + n0 + tx + 16 * j] = __float2bfloat16_rn(acc[i][j]);
}
__global__ void __launch_bounds__(256) plain_attn(int half) {
  const int lane = threadIdx.x & 31, t = blockIdx.x * 8 + (threadIdx.x >> 5), c = blockIdx.y * HD + lane * 4;
  bf16* io = g_ctx + (size_t)t * HDIM + half * (HDIM / 2) + c;
  float q[4], o[4] = {}, m = -INFINITY, l = 0.f;
  for (int i = 0; i < 4; i++) q[i] = ldf(io + i) * 0.08838834764831845f;
  for (int j = 0; j <= t; j++) {
    float s = 0.f;
    for (int i = 0; i < 4; i++) s += q[i] * ldf(g_k + (size_t)j * (HDIM / 2) + c + i);
    for (int x = 16; x; x >>= 1) s += __shfl_xor_sync(0xffffffffu, s, x);
    const float mn = fmaxf(m, s), al = __expf(m - mn), p = __expf(s - mn);
    for (int i = 0; i < 4; i++) o[i] = o[i] * al + p * ldf(g_v + (size_t)j * (HDIM / 2) + c + i);
    l = l * al + p;
    m = mn;
  }
  for (int i = 0; i < 4; i++) io[i] = __float2bfloat16_rn(o[i] / l);
}
__global__ void __launch_bounds__(256) plain_gate(const bf16* x, const bf16* w) {
  const int lane = threadIdx.x & 31, t = blockIdx.x * 8 + (threadIdx.x >> 5);
  float s = 0.f;
  for (int i = lane; i < DM; i += 32) s += bf16_round(ldf(x + (size_t)t * DM + i) * ldf(w + i));
  for (int o = 16; o; o >>= 1) s += __shfl_xor_sync(0xffffffffu, s, o);
  if (lane == 0) g_gate[t] = bf16_round(1.0f / (1.0f + __expf(-bf16_round(s))));
}
__global__ void __launch_bounds__(256) plain_conv(const bf16* x, const bf16* k, const bf16* v, const bf16* shift_k,
                                                  const bf16* ssm_k, const bf16* ssm_D, bf16* out) {
  __shared__ float u[S_LEN], h[S_LEN];
  const int c = blockIdx.x;
  for (int t = threadIdx.x; t < S_LEN; t += 256) {
    float s = 0.f;
    for (int i = 3; i >= 0; i--)
      if (t >= i) s = bf16_round(s + bf16_round(ldf(k + (size_t)(t - i) * DM + c) * ldf(shift_k + c * 4 + i)));
    u[t] = bf16_round(s * ldf(v + (size_t)t * DM + c));
    h[t] = ldf(ssm_k + (size_t)c * S_LEN + t);
  }
  __syncthreads();
  for (int t = threadIdx.x; t < S_LEN; t += 256) {
    float y = 0.f;
    for (int i = 0; i <= t; i++) y += h[i] * u[t - i];
    y = bf16_round(bf16_round(y) + bf16_round(u[t] * ldf(ssm_D + c)));
    const float g = g_gate[t], b = bf16_round(ldf(x + (size_t)t * DM + c) * y);
    bf16* o = out + (size_t)t * DM + c;
    *o = __float2bfloat16_rn(bf16_round(g * ldf(o)) + bf16_round(bf16_round(1.0f - g) * b));
  }
}

typedef CUresult (*PFN_tmapEncode)(CUtensorMap*, CUtensorMapDataType, cuuint32_t, void*, const cuuint64_t*,
                                   const cuuint64_t*, const cuuint32_t*, const cuuint32_t*, CUtensorMapInterleave,
                                   CUtensorMapSwizzle, CUtensorMapL2promotion, CUtensorMapFloatOOBfill);
static PFN_tmapEncode s_encode = nullptr;

static void make_map_2d(CUtensorMap* m, const void* ptr, int rows, int cols, int box_rows,
                        CUtensorMapL2promotion prom = CU_TENSOR_MAP_L2_PROMOTION_L2_256B) {
  cuuint64_t dims[2] = {(cuuint64_t)cols, (cuuint64_t)rows};
  cuuint64_t strides[1] = {(cuuint64_t)cols * 2};
  cuuint32_t box[2] = {64, (cuuint32_t)box_rows};
  cuuint32_t es[2] = {1, 1};
  s_encode(m, CU_TENSOR_MAP_DATA_TYPE_BFLOAT16, 2, const_cast<void*>(ptr), dims, strides, box, es,
           CU_TENSOR_MAP_INTERLEAVE_NONE, CU_TENSOR_MAP_SWIZZLE_128B, prom,
           CU_TENSOR_MAP_FLOAT_OOB_FILL_NONE);
}
static void make_map_3d(CUtensorMap* m, const void* ptr, int rows, int cols, int box_rows, int box_chunks) {
  cuuint64_t dims[3] = {64, (cuuint64_t)rows, (cuuint64_t)(cols / 64)};
  cuuint64_t strides[2] = {(cuuint64_t)cols * 2, 128};
  cuuint32_t box[3] = {64, (cuuint32_t)box_rows, (cuuint32_t)box_chunks};
  cuuint32_t es[3] = {1, 1, 1};
  s_encode(m, CU_TENSOR_MAP_DATA_TYPE_BFLOAT16, 3, const_cast<void*>(ptr), dims, strides, box, es,
           CU_TENSOR_MAP_INTERLEAVE_NONE, CU_TENSOR_MAP_SWIZZLE_128B, CU_TENSOR_MAP_L2_PROMOTION_L2_256B,
           CU_TENSOR_MAP_FLOAT_OOB_FILL_NONE);
}

static void make_map_4d(CUtensorMap* m, const void* ptr, int rows, int cols, int b2, int groups) {
  cuuint64_t dims[4] = {(cuuint64_t)cols, 8, 8, (cuuint64_t)(rows / 64)};
  cuuint64_t strides[3] = {(cuuint64_t)cols * 16, (cuuint64_t)cols * 2, (cuuint64_t)cols * 128};
  cuuint32_t box[4] = {64, 8, (cuuint32_t)b2, (cuuint32_t)groups};
  cuuint32_t es[4] = {1, 1, 1, 1};
  s_encode(m, CU_TENSOR_MAP_DATA_TYPE_BFLOAT16, 4, const_cast<void*>(ptr), dims, strides, box, es,
           CU_TENSOR_MAP_INTERLEAVE_NONE, CU_TENSOR_MAP_SWIZZLE_128B, CU_TENSOR_MAP_L2_PROMOTION_L2_256B,
           CU_TENSOR_MAP_FLOAT_OOB_FILL_NONE);
}

static cudaLaunchConfig_t fused_cfg(cudaLaunchAttribute* at) {
  cudaLaunchConfig_t cfg = {};
  cfg.gridDim = dim3(132);
  cfg.blockDim = dim3(384);
  cfg.dynamicSmemBytes = SMEM_BYTES;
  cfg.stream = cudaStreamPerThread;
  at[0].id = cudaLaunchAttributeClusterDimension;
  at[0].val.clusterDim.x = 2;
  at[0].val.clusterDim.y = 1;
  at[0].val.clusterDim.z = 1;
  cfg.attrs = at;
  cfg.numAttrs = 1;
  return cfg;
}

extern "C" void kernel_launch(void* const* d_in, const int* in_sizes, int n_in, void* d_out, int out_size) {
  const bf16* x = (const bf16*)d_in[0];
  const bf16* ckv = (const bf16*)d_in[1];
  const bf16* wq = (const bf16*)d_in[2];
  const bf16* wuk = (const bf16*)d_in[3];
  const bf16* wuv = (const bf16*)d_in[4];
  const bf16* wo = (const bf16*)d_in[5];
  const bf16* bk = (const bf16*)d_in[7];
  const bf16* bv = (const bf16*)d_in[8];
  const bf16* shift_k = (const bf16*)d_in[9];
  const bf16* ssm_k = (const bf16*)d_in[10];
  const bf16* ssm_D = (const bf16*)d_in[11];
  const bf16* gate_w = (const bf16*)d_in[12];
  bf16* out = (bf16*)d_out;

  static void *pk = nullptr, *pv = nullptr, *pctx = nullptr, *pb = nullptr;
  static int max_clusters = 0;
  if (!s_encode) {
    void* fn = nullptr;
    cudaDriverEntryPointQueryResult qres;
    cudaGetDriverEntryPoint("cuTensorMapEncodeTiled", &fn, cudaEnableDefault, &qres);
    s_encode = (PFN_tmapEncode)fn;
    cudaGetSymbolAddress(&pk, g_k);
    cudaGetSymbolAddress(&pv, g_v);
    cudaGetSymbolAddress(&pctx, g_ctx);
    cudaGetSymbolAddress(&pb, g_y2T);
    cudaFuncSetAttribute(fused_kernel, cudaFuncAttributeMaxDynamicSharedMemorySize, SMEM_BYTES);
    cudaLaunchAttribute at[1];
    cudaLaunchConfig_t cfg = fused_cfg(at);
    if (cudaOccupancyMaxActiveClusters(&max_clusters, fused_kernel, &cfg) != cudaSuccess) max_clusters = 0;
  }

  Maps all = {};
  make_map_2d(&all.a[0], ckv, S_LEN, DC, 128);
  make_map_2d(&all.a[1], x, S_LEN, DM, 128);
  make_map_3d(&all.b[0], wuk, DC, HDIM, 64, 4);
  make_map_3d(&all.b[1], wuv, DC, HDIM, 64, 4);
  make_map_3d(&all.b[2], wq, DM, HDIM, 64, 4);
  make_map_2d(&all.c[0], pk, S_LEN, HDIM / 2, 64);
  make_map_2d(&all.c[1], pv, S_LEN, HDIM / 2, 64);
  make_map_3d(&all.k, pk, S_LEN, HDIM / 2, 128, 2);
  make_map_3d(&all.v, pv, S_LEN, HDIM / 2, 128, 2);
  make_map_2d(&all.c[2], pctx, S_LEN, HDIM, 64);
  all.ssm_k = ssm_k;
  all.ssm_D = ssm_D;
  make_map_4d(&all.oa, pctx, S_LEN, HDIM, 8, 2);
  make_map_4d(&all.ox, x, S_LEN, DM, 8, 2);
  make_map_2d(&all.ob, wo, HDIM, DM, 64);
  make_map_4d(&all.oc, out, S_LEN, DM, 2, 1);
  make_map_2d(&all.y, pb, DM, S_LEN, 112);
  make_map_2d(&all.y2, pb, DM, S_LEN, 16);

  make_map_2d(&all.bk, bk, S_LEN, DM, 35, CU_TENSOR_MAP_L2_PROMOTION_L2_128B);
  make_map_2d(&all.bv, bv, S_LEN, DM, 32, CU_TENSOR_MAP_L2_PROMOTION_L2_128B);
  for (int b = 0; b < 128; b++) {
    const int c = b >> 1, r = b & 1;
    const int G = c < 4 ? 0 : c < 36 ? (c - 4) % 8 : 1 + (c - 36) % 7;
    const int i = c < 4 ? 4 + c : c < 36 ? (c - 4) / 8 : 4 + (c - 36) / 7;
    all.id[b][0] = r + 2 * (i & 1) + 4 * (G & 3) + 16 * (i >> 1) + 64 * (G >> 2);
    all.id[b][1] = (r ? 15 - i : i) + 16 * G;
    all.id[b][2] = r + 2 * G + 16 * i;
  }
  all.shift_k = shift_k;
  all.x = x;
  all.gate_w = gate_w;
  cudaLaunchAttribute at[1];
  cudaLaunchConfig_t cfg = fused_cfg(at);
  if (max_clusters >= 66) {
    cudaLaunchKernelEx(&cfg, fused_kernel, all);
  } else {
    const cudaStream_t st = cudaStreamPerThread;
    plain_gemm<<<dim3(HDIM / 64, S_LEN / 64), 256, 0, st>>>(x, wq, (bf16*)pctx, DM, HDIM, HDIM);
    for (int half = 0; half < 2; half++) {
      plain_gemm<<<dim3(HDIM / 128, S_LEN / 64), 256, 0, st>>>(ckv, wuk + half * (HDIM / 2), (bf16*)pk, DC, HDIM, HDIM / 2);
      plain_gemm<<<dim3(HDIM / 128, S_LEN / 64), 256, 0, st>>>(ckv, wuv + half * (HDIM / 2), (bf16*)pv, DC, HDIM, HDIM / 2);
      plain_attn<<<dim3(S_LEN / 8, NH / 2), 256, 0, st>>>(half);
    }
    plain_gemm<<<dim3(DM / 64, S_LEN / 64), 256, 0, st>>>((const bf16*)pctx, wo, out, HDIM, DM, DM);
    plain_gate<<<S_LEN / 8, 256, 0, st>>>(x, gate_w);
    plain_conv<<<DM, 256, 0, st>>>(x, bk, bv, shift_k, ssm_k, ssm_D, out);
  }
}
```

```cpp
#include <cuda_runtime.h>
#include <cuda_bf16.h>
#include <cuda.h>
#include <stdint.h>

typedef __nv_bfloat16 bf16;
#define INPLACE 3

constexpr int S_LEN = 2048;
constexpr int DM = 1024;
constexpr int NH = 32;
constexpr int HD = 128;
constexpr int DC = 512;
constexpr int HDIM = NH * HD;

__device__ __align__(1024) bf16 g_k[S_LEN * HDIM / 2];
__device__ __align__(1024) bf16 g_v[S_LEN * HDIM / 2];
__device__ __align__(1024) bf16 g_ctx[S_LEN * HDIM];
__device__ __align__(1024) bf16 g_kvT[DM * S_LEN];
#define g_y2T g_kvT
__device__ __align__(1024) float g_gate[S_LEN];
enum { CNT_KV = 0, CNT_PREP = 2, CNT_CTX = 4, CNT_Y2 = 6, CNT_DONE = 8, CNT_N };
__device__ unsigned int g_cnt[CNT_N * 32];

#define TL(k, i)
#define TL2(k, i)
#define TD(i)
#define LT(i, thr)
#define PT_DECL
#define PT
#define CLK_DECL
#define CLK_SAMPLE
#define CLK_END
#define CT(i)
#define GT(i)
#define GS(i)
#define GA(i)
#define ST(i)

__device__ __forceinline__ uint32_t smem_u32(const void* p) { return (uint32_t)__cvta_generic_to_shared(p); }

__device__ __forceinline__ void mbar_init(uint32_t bar, uint32_t count) {
  asm volatile("mbarrier.init.shared::cta.b64 [%0], %1;" ::"r"(bar), "r"(count));
}
__device__ __forceinline__ void mbar_expect_tx(uint32_t bar, uint32_t bytes) {
  asm volatile("mbarrier.arrive.expect_tx.shared::cta.b64 _, [%0], %1;" ::"r"(bar), "r"(bytes) : "memory");
}
__device__ __forceinline__ void mbar_arrive(uint32_t bar) {
  asm volatile("mbarrier.arrive.shared::cta.b64 _, [%0];" ::"r"(bar) : "memory");
}
__device__ __forceinline__ void mbar_wait(uint32_t bar, uint32_t parity) {
  uint32_t done;
  uint32_t spins = 0;
  do {
    asm volatile(
        "{\n.reg .pred p;\n"
        "mbarrier.try_wait.parity.shared::cta.b64 p, [%1], %2;\n"
        "selp.u32 %0, 1, 0, p;\n}\n"
        : "=r"(done)
        : "r"(bar), "r"(parity)
        : "memory");
    if (++spins > (1u << 22)) break;
  } while (!done);
}
__device__ __forceinline__ bool mbar_try(uint32_t bar, uint32_t parity) {
  uint32_t done;
  asm volatile(
      "{\n.reg .pred p;\n"
      "mbarrier.try_wait.parity.shared::cta.b64 p, [%1], %2;\n"
      "selp.u32 %0, 1, 0, p;\n}\n"
      : "=r"(done)
      : "r"(bar), "r"(parity)
      : "memory");
  return done != 0;
}
__device__ __forceinline__ bool elect_one() {
  uint32_t pred;
  asm volatile("{\n.reg .pred p;\nelect.sync _|p, 0xffffffff;\nselp.u32 %0, 1, 0, p;\n}\n" : "=r"(pred));
  return pred != 0;
}
__device__ __forceinline__ void mbar_arrive_if(uint32_t bar, bool pred) {
  asm volatile(
      "{\n.reg .pred p;\nsetp.ne.b32 p, %1, 0;\n"
      "@p mbarrier.arrive.shared::cta.b64 _, [%0];\n}\n" ::"r"(bar),
      "r"((uint32_t)pred)
      : "memory");
}
__device__ __forceinline__ void mbar_wait_sleep(uint32_t bar, uint32_t parity) {
  uint32_t done;
  uint32_t spins = 0;
  do {
    asm volatile(
        "{\n.reg .pred p;\n"
        "mbarrier.try_wait.parity.shared::cta.b64 p, [%1], %2, %3;\n"
        "selp.u32 %0, 1, 0, p;\n}\n"
        : "=r"(done)
        : "r"(bar), "r"(parity), "r"(20000u)
        : "memory");
    if (++spins > (1u << 16)) break;
  } while (!done);
}
__device__ __forceinline__ void fence_barrier_init() {
  asm volatile("fence.mbarrier_init.release.cluster;" ::: "memory");
}
__device__ __forceinline__ void fence_proxy_async() {
  asm volatile("fence.proxy.async.shared::cta;" ::: "memory");
}
__device__ __forceinline__ void named_bar_sync(int id, int nthreads) {
  asm volatile("bar.sync %0, %1;" ::"r"(id), "r"(nthreads) : "memory");
}
__device__ __forceinline__ void named_bar_arrive(int id, int nthreads) {
  asm volatile("bar.arrive %0, %1;" ::"r"(id), "r"(nthreads) : "memory");
}
__device__ __forceinline__ void tma_load_2d(uint32_t dst, const CUtensorMap* m, uint32_t bar, int c0, int c1) {
  asm volatile(
      "cp.async.bulk.tensor.2d.shared::cluster.global.mbarrier::complete_tx::bytes [%0], [%1, {%3, %4}], [%2];" ::"r"(dst),
      "l"(reinterpret_cast<uint64_t>(m)), "r"(bar), "r"(c0), "r"(c1)
      : "memory");
}
__device__ __forceinline__ void tma_load_3d(uint32_t dst, const CUtensorMap* m, uint32_t bar, int c0, int c1, int c2) {
  asm volatile(
      "cp.async.bulk.tensor.3d.shared::cluster.global.mbarrier::complete_tx::bytes [%0], [%1, {%3, %4, %5}], [%2];" ::"r"(dst),
      "l"(reinterpret_cast<uint64_t>(m)), "r"(bar), "r"(c0), "r"(c1), "r"(c2)
      : "memory");
}
__device__ __forceinline__ void tma_store_2d(const CUtensorMap* m, uint32_t src, int c0, int c1) {
  asm volatile("cp.async.bulk.tensor.2d.global.shared::cta.bulk_group [%0, {%2, %3}], [%1];" ::"l"(
                   reinterpret_cast<uint64_t>(m)),
               "r"(src), "r"(c0), "r"(c1)
               : "memory");
}
__device__ __forceinline__ void tma_load_4d(uint32_t dst, const CUtensorMap* m, uint32_t bar, int c0, int tile) {
  asm volatile(
      "cp.async.bulk.tensor.4d.shared::cluster.global.mbarrier::complete_tx::bytes [%0], [%1, {%3, %4, %4, %5}], [%2];" ::"r"(dst),
      "l"(reinterpret_cast<uint64_t>(m)), "r"(bar), "r"(c0), "r"(0), "r"(2 * tile)
      : "memory");
}
__device__ __forceinline__ void tma_store_4d(const CUtensorMap* m, uint32_t src, int c0, int c2, int group) {
  asm volatile("cp.async.bulk.tensor.4d.global.shared::cta.bulk_group [%0, {%2, %3, %4, %5}], [%1];" ::"l"(
                   reinterpret_cast<uint64_t>(m)),
               "r"(src), "r"(c0), "r"(0), "r"(c2), "r"(group)
               : "memory");
}
__device__ __forceinline__ void bulk_load(uint32_t dst, const void* src, uint32_t bytes, uint32_t bar) {
  asm volatile("cp.async.bulk.shared::cluster.global.mbarrier::complete_tx::bytes [%0], [%1], %2, [%3];" ::"r"(dst),
               "l"(src), "r"(bytes), "r"(bar)
               : "memory");
}
__device__ __forceinline__ void tma_load_2d_mc(uint32_t dst, const CUtensorMap* m, uint32_t bar, int c0, int c1,
                                               uint16_t mask) {
  asm volatile(
      "cp.async.bulk.tensor.2d.shared::cluster.global.mbarrier::complete_tx::bytes.multicast::cluster [%0], [%1, {%3, "
      "%4}], [%2], %5;" ::"r"(dst),
      "l"(reinterpret_cast<uint64_t>(m)), "r"(bar), "r"(c0), "r"(c1), "h"(mask)
      : "memory");
}
__device__ __forceinline__ void mbar_arrive_cluster_if(uint32_t bar, uint32_t cta, bool pred) {
  asm volatile(
      "{\n.reg .b32 ra;\n.reg .pred p;\nsetp.ne.b32 p, %2, 0;\n"
      "mapa.shared::cluster.u32 ra, %0, %1;\n"
      "@p mbarrier.arrive.shared::cluster.b64 _, [ra];\n}\n" ::"r"(bar),
      "r"(cta), "r"((uint32_t)pred)
      : "memory");
}
__device__ __forceinline__ uint64_t policy_evict_first() {
  uint64_t pol;
  asm volatile("createpolicy.fractional.L2::evict_first.b64 %0, 1.0;" : "=l"(pol));
  return pol;
}
__device__ __forceinline__ void tma_load_2d_hint(uint32_t dst, const CUtensorMap* m, uint32_t bar, int c0, int c1,
                                                 uint64_t pol) {
  asm volatile(
      "cp.async.bulk.tensor.2d.shared::cluster.global.mbarrier::complete_tx::bytes.L2::cache_hint [%0], [%1, {%3, %4}], "
      "[%2], %5;" ::"r"(dst),
      "l"(reinterpret_cast<uint64_t>(m)), "r"(bar), "r"(c0), "r"(c1), "l"(pol)
      : "memory");
}
__device__ __forceinline__ void tma_load_3d_hint(uint32_t dst, const CUtensorMap* m, uint32_t bar, int c0, int c1,
                                                 int c2, uint64_t pol) {
  asm volatile(
      "cp.async.bulk.tensor.3d.shared::cluster.global.mbarrier::complete_tx::bytes.L2::cache_hint [%0], [%1, {%3, %4, "
      "%5}], [%2], %6;" ::"r"(dst),
      "l"(reinterpret_cast<uint64_t>(m)), "r"(bar), "r"(c0), "r"(c1), "r"(c2), "l"(pol)
      : "memory");
}
__device__ __forceinline__ void bulk_load_hint(uint32_t dst, const void* src, uint32_t bytes, uint32_t bar, uint64_t pol) {
  asm volatile(
      "cp.async.bulk.shared::cluster.global.mbarrier::complete_tx::bytes.L2::cache_hint [%0], [%1], %2, [%3], %4;" ::"r"(dst),
      "l"(src), "r"(bytes), "r"(bar), "l"(pol)
      : "memory");
}
__device__ __forceinline__ void cnt_signal_release(int which, uint32_t n) {
  asm volatile("red.release.gpu.global.add.u32 [%0], %1;" ::"l"(g_cnt + which * 32), "r"(n) : "memory");
}
__device__ __forceinline__ void cnt_wait(int which, uint32_t target) {
  uint32_t v, spins = 0;
  while (true) {
    asm volatile("ld.acquire.gpu.global.u32 %0, [%1];" : "=r"(v) : "l"(g_cnt + which * 32) : "memory");
    if (v >= target || ++spins > (1u << 18)) break;
    __nanosleep(64);
  }
  asm volatile("fence.proxy.async.global;" ::: "memory");
}
__device__ __forceinline__ void tma_store_commit() { asm volatile("cp.async.bulk.commit_group;" ::: "memory"); }
template <int N>
__device__ __forceinline__ void tma_store_wait_read() {
  asm volatile("cp.async.bulk.wait_group.read %0;" ::"n"(N) : "memory");
}
template <int N>
__device__ __forceinline__ void tma_store_wait() {
  asm volatile("cp.async.bulk.wait_group %0;" ::"n"(N) : "memory");
}
__device__ __forceinline__ void wgmma_fence() { asm volatile("wgmma.fence.sync.aligned;" ::: "memory"); }
__device__ __forceinline__ void wgmma_commit() { asm volatile("wgmma.commit_group.sync.aligned;" ::: "memory"); }
template <int N>
__device__ __forceinline__ void wgmma_wait() {
  asm volatile("wgmma.wait_group.sync.aligned %0;" ::"n"(N) : "memory");
}
template <int R>
__device__ __forceinline__ void reg_alloc() { asm volatile("setmaxnreg.inc.sync.aligned.u32 %0;" ::"n"(R)); }
template <int R>
__device__ __forceinline__ void reg_dealloc() { asm volatile("setmaxnreg.dec.sync.aligned.u32 %0;" ::"n"(R)); }

__device__ __forceinline__ void stmatrix_x4(uint32_t addr, uint32_t r0, uint32_t r1, uint32_t r2, uint32_t r3) {
  asm volatile("stmatrix.sync.aligned.m8n8.x4.shared.b16 [%0], {%1, %2, %3, %4};" ::"r"(addr), "r"(r0), "r"(r1),
               "r"(r2), "r"(r3)
               : "memory");
}
__device__ __forceinline__ uint32_t pack_bf16(float lo, float hi) {
  uint32_t r;
  asm("cvt.rn.bf16x2.f32 %0, %1, %2;" : "=r"(r) : "f"(hi), "f"(lo));
  return r;
}
__device__ __forceinline__ float bf16_round(float x) { return __bfloat162float(__float2bfloat16_rn(x)); }
__device__ __forceinline__ float bf_lo(uint32_t v) { return __uint_as_float(v << 16); }
__device__ __forceinline__ float bf_hi(uint32_t v) { return __uint_as_float(v & 0xffff0000u); }
__device__ __forceinline__ uint4 lds128(uint32_t a) {
  uint4 v;
  asm volatile("ld.shared.v4.u32 {%0, %1, %2, %3}, [%4];" : "=r"(v.x), "=r"(v.y), "=r"(v.z), "=r"(v.w) : "r"(a));
  return v;
}
__device__ __forceinline__ void sts128(uint32_t a, uint4 v) {
  asm volatile("st.shared.v4.u32 [%0], {%1, %2, %3, %4};" ::"r"(a), "r"(v.x), "r"(v.y), "r"(v.z), "r"(v.w) : "memory");
}
__device__ __forceinline__ uint32_t mul_bf2(uint32_t a, uint32_t b) {
  uint32_t r;
  asm("mul.rn.bf16x2 %0, %1, %2;" : "=r"(r) : "r"(a), "r"(b));
  return r;
}
__device__ __forceinline__ uint32_t add_bf2(uint32_t a, uint32_t b) {
  uint32_t r;
  asm("add.rn.bf16x2 %0, %1, %2;" : "=r"(r) : "r"(a), "r"(b));
  return r;
}
__device__ __forceinline__ float ex2(float x) {
  float y;
  asm("ex2.approx.ftz.f32 %0, %1;" : "=f"(y) : "f"(x));
  return y;
}
__device__ __forceinline__ float rcp(float x) {
  float y;
  asm("rcp.approx.ftz.f32 %0, %1;" : "=f"(y) : "f"(x));
  return y;
}
template <int N>
__device__ __forceinline__ void fence_regs(float (&r)[N]) {
#pragma unroll
  for (int i = 0; i < N; i++) asm volatile("" : "+f"(r[i])::"memory");
}

template <int N>
__device__ __forceinline__ void undef_regs(float (&r)[N]) {
#pragma unroll
  for (int i = 0; i < N; i++) asm volatile("" : "=f"(r[i]));
}
template <int N>
__device__ __forceinline__ void fence_regs_u(uint32_t (&r)[N]) {
#pragma unroll
  for (int i = 0; i < N; i++) asm volatile("" : "+r"(r[i])::"memory");
}

constexpr uint64_t DESC_SW128 = 1ull << 62;
__device__ __forceinline__ uint64_t make_desc(uint32_t addr, uint32_t lbo_bytes, uint32_t sbo_bytes, uint64_t swz) {
  return (uint64_t)((addr & 0x3FFFF) >> 4) | ((uint64_t)((lbo_bytes & 0x3FFFF) >> 4) << 16) |
         ((uint64_t)((sbo_bytes & 0x3FFFF) >> 4) << 32) | swz;
}

__device__ __forceinline__ uint64_t desc_add(uint64_t d, uint32_t off16) {
  return (d & 0xFFFFFFFF00000000ull) | (uint64_t)((uint32_t)d + off16);
}

__device__ __forceinline__ void wgmma_m64n256_ss_tb(float (&d)[128], uint64_t da, uint64_t db, int sd) {
  asm volatile(
    "{\n.reg .pred p;\nsetp.ne.b32 p, %130, 0;\n"
    "wgmma.mma_async.sync.aligned.m64n256k16.f32.bf16.bf16 "
    "{%0, %1, %2, %3, %4, %5, %6, %7, %8, %9, %10, %11, %12, %13, %14, %15, %16, %17, %18, %19, %20, %21, %22, %23, %24, %25, %26, %27, %28, %29, %30, %31, %32, %33, %34, %35, %36, %37, %38, %39, %40, %41, %42, %43, %44, %45, %46, %47, %48, %49, %50, %51, %52, %53, %54, %55, %56, %57, %58, %59, %60, %61, %62, %63, %64, %65, %66, %67, %68, %69, %70, %71, %72, %73, %74, %75, %76, %77, %78, %79, %80, %81, %82, %83, %84, %85, %86, %87, %88, %89, %90, %91, %92, %93, %94, %95, %96, %97, %98, %99, %100, %101, %102, %103, %104, %105, %106, %107, %108, %109, %110, %111, %112, %113, %114, %115, %116, %117, %118, %119, %120, %121, %122, %123, %124, %125, %126, %127}, %128, %129, p, 1, 1, 0, 1;\n}\n"
    : "+f"(d[0]), "+f"(d[1]), "+f"(d[2]), "+f"(d[3]), "+f"(d[4]), "+f"(d[5]), "+f"(d[6]), "+f"(d[7]), "+f"(d[8]), "+f"(d[9]), "+f"(d[10]), "+f"(d[11]), "+f"(d[12]), "+f"(d[13]), "+f"(d[14]), "+f"(d[15]), "+f"(d[16]), "+f"(d[17]), "+f"(d[18]), "+f"(d[19]), "+f"(d[20]), "+f"(d[21]), "+f"(d[22]), "+f"(d[23]), "+f"(d[24]), "+f"(d[25]), "+f"(d[26]), "+f"(d[27]), "+f"(d[28]), "+f"(d[29]), "+f"(d[30]), "+f"(d[31]), "+f"(d[32]), "+f"(d[33]), "+f"(d[34]), "+f"(d[35]), "+f"(d[36]), "+f"(d[37]), "+f"(d[38]), "+f"(d[39]), "+f"(d[40]), "+f"(d[41]), "+f"(d[42]), "+f"(d[43]), "+f"(d[44]), "+f"(d[45]), "+f"(d[46]), "+f"(d[47]), "+f"(d[48]), "+f"(d[49]), "+f"(d[50]), "+f"(d[51]), "+f"(d[52]), "+f"(d[53]), "+f"(d[54]), "+f"(d[55]), "+f"(d[56]), "+f"(d[57]), "+f"(d[58]), "+f"(d[59]), "+f"(d[60]), "+f"(d[61]), "+f"(d[62]), "+f"(d[63]), "+f"(d[64]), "+f"(d[65]), "+f"(d[66]), "+f"(d[67]), "+f"(d[68]), "+f"(d[69]), "+f"(d[70]), "+f"(d[71]), "+f"(d[72]), "+f"(d[73]), "+f"(d[74]), "+f"(d[75]), "+f"(d[76]), "+f"(d[77]), "+f"(d[78]), "+f"(d[79]), "+f"(d[80]), "+f"(d[81]), "+f"(d[82]), "+f"(d[83]), "+f"(d[84]), "+f"(d[85]), "+f"(d[86]), "+f"(d[87]), "+f"(d[88]), "+f"(d[89]), "+f"(d[90]), "+f"(d[91]), "+f"(d[92]), "+f"(d[93]), "+f"(d[94]), "+f"(d[95]), "+f"(d[96]), "+f"(d[97]), "+f"(d[98]), "+f"(d[99]), "+f"(d[100]), "+f"(d[101]), "+f"(d[102]), "+f"(d[103]), "+f"(d[104]), "+f"(d[105]), "+f"(d[106]), "+f"(d[107]), "+f"(d[108]), "+f"(d[109]), "+f"(d[110]), "+f"(d[111]), "+f"(d[112]), "+f"(d[113]), "+f"(d[114]), "+f"(d[115]), "+f"(d[116]), "+f"(d[117]), "+f"(d[118]), "+f"(d[119]), "+f"(d[120]), "+f"(d[121]), "+f"(d[122]), "+f"(d[123]), "+f"(d[124]), "+f"(d[125]), "+f"(d[126]), "+f"(d[127])
    : "l"(da), "l"(db), "r"(sd));
}

__device__ __forceinline__ void wgmma_m64n128_ss(float (&d)[64], uint64_t da, uint64_t db, int sd) {
  asm volatile(
    "{\n.reg .pred p;\nsetp.ne.b32 p, %66, 0;\n"
    "wgmma.mma_async.sync.aligned.m64n128k16.f32.bf16.bf16 "
    "{%0, %1, %2, %3, %4, %5, %6, %7, %8, %9, %10, %11, %12, %13, %14, %15, %16, %17, %18, %19, %20, %21, %22, %23, %24, %25, %26, %27, %28, %29, %30, %31, %32, %33, %34, %35, %36, %37, %38, %39, %40, %41, %42, %43, %44, %45, %46, %47, %48, %49, %50, %51, %52, %53, %54, %55, %56, %57, %58, %59, %60, %61, %62, %63}, %64, %65, p, 1, 1, 0, 0;\n}\n"
    : "+f"(d[0]), "+f"(d[1]), "+f"(d[2]), "+f"(d[3]), "+f"(d[4]), "+f"(d[5]), "+f"(d[6]), "+f"(d[7]), "+f"(d[8]), "+f"(d[9]), "+f"(d[10]), "+f"(d[11]), "+f"(d[12]), "+f"(d[13]), "+f"(d[14]), "+f"(d[15]), "+f"(d[16]), "+f"(d[17]), "+f"(d[18]), "+f"(d[19]), "+f"(d[20]), "+f"(d[21]), "+f"(d[22]), "+f"(d[23]), "+f"(d[24]), "+f"(d[25]), "+f"(d[26]), "+f"(d[27]), "+f"(d[28]), "+f"(d[29]), "+f"(d[30]), "+f"(d[31]), "+f"(d[32]), "+f"(d[33]), "+f"(d[34]), "+f"(d[35]), "+f"(d[36]), "+f"(d[37]), "+f"(d[38]), "+f"(d[39]), "+f"(d[40]), "+f"(d[41]), "+f"(d[42]), "+f"(d[43]), "+f"(d[44]), "+f"(d[45]), "+f"(d[46]), "+f"(d[47]), "+f"(d[48]), "+f"(d[49]), "+f"(d[50]), "+f"(d[51]), "+f"(d[52]), "+f"(d[53]), "+f"(d[54]), "+f"(d[55]), "+f"(d[56]), "+f"(d[57]), "+f"(d[58]), "+f"(d[59]), "+f"(d[60]), "+f"(d[61]), "+f"(d[62]), "+f"(d[63])
    : "l"(da), "l"(db), "r"(sd));
}

__device__ __forceinline__ void wgmma_m64n128_ss_tb(float (&d)[64], uint64_t da, uint64_t db, int sd) {
  asm volatile(
    "{\n.reg .pred p;\nsetp.ne.b32 p, %66, 0;\n"
    "wgmma.mma_async.sync.aligned.m64n128k16.f32.bf16.bf16 "
    "{%0, %1, %2, %3, %4, %5, %6, %7, %8, %9, %10, %11, %12, %13, %14, %15, %16, %17, %18, %19, %20, %21, %22, %23, %24, %25, %26, %27, %28, %29, %30, %31, %32, %33, %34, %35, %36, %37, %38, %39, %40, %41, %42, %43, %44, %45, %46, %47, %48, %49, %50, %51, %52, %53, %54, %55, %56, %57, %58, %59, %60, %61, %62, %63}, %64, %65, p, 1, 1, 0, 1;\n}\n"
    : "+f"(d[0]), "+f"(d[1]), "+f"(d[2]), "+f"(d[3]), "+f"(d[4]), "+f"(d[5]), "+f"(d[6]), "+f"(d[7]), "+f"(d[8]), "+f"(d[9]), "+f"(d[10]), "+f"(d[11]), "+f"(d[12]), "+f"(d[13]), "+f"(d[14]), "+f"(d[15]), "+f"(d[16]), "+f"(d[17]), "+f"(d[18]), "+f"(d[19]), "+f"(d[20]), "+f"(d[21]), "+f"(d[22]), "+f"(d[23]), "+f"(d[24]), "+f"(d[25]), "+f"(d[26]), "+f"(d[27]), "+f"(d[28]), "+f"(d[29]), "+f"(d[30]), "+f"(d[31]), "+f"(d[32]), "+f"(d[33]), "+f"(d[34]), "+f"(d[35]), "+f"(d[36]), "+f"(d[37]), "+f"(d[38]), "+f"(d[39]), "+f"(d[40]), "+f"(d[41]), "+f"(d[42]), "+f"(d[43]), "+f"(d[44]), "+f"(d[45]), "+f"(d[46]), "+f"(d[47]), "+f"(d[48]), "+f"(d[49]), "+f"(d[50]), "+f"(d[51]), "+f"(d[52]), "+f"(d[53]), "+f"(d[54]), "+f"(d[55]), "+f"(d[56]), "+f"(d[57]), "+f"(d[58]), "+f"(d[59]), "+f"(d[60]), "+f"(d[61]), "+f"(d[62]), "+f"(d[63])
    : "l"(da), "l"(db), "r"(sd));
}

__device__ __forceinline__ void wgmma_m64n128_rs_tb(float* d, uint32_t a0, uint32_t a1, uint32_t a2, uint32_t a3, uint64_t db, int sd) {
  asm volatile(
    "{\n.reg .pred p;\nsetp.ne.b32 p, %69, 0;\n"
    "wgmma.mma_async.sync.aligned.m64n128k16.f32.bf16.bf16 "
    "{%0, %1, %2, %3, %4, %5, %6, %7, %8, %9, %10, %11, %12, %13, %14, %15, %16, %17, %18, %19, %20, %21, %22, %23, %24, %25, %26, %27, %28, %29, %30, %31, %32, %33, %34, %35, %36, %37, %38, %39, %40, %41, %42, %43, %44, %45, %46, %47, %48, %49, %50, %51, %52, %53, %54, %55, %56, %57, %58, %59, %60, %61, %62, %63}, {%64, %65, %66, %67}, %68, p, 1, 1, 1;\n}\n"
    : "+f"(d[0]), "+f"(d[1]), "+f"(d[2]), "+f"(d[3]), "+f"(d[4]), "+f"(d[5]), "+f"(d[6]), "+f"(d[7]), "+f"(d[8]), "+f"(d[9]), "+f"(d[10]), "+f"(d[11]), "+f"(d[12]), "+f"(d[13]), "+f"(d[14]), "+f"(d[15]), "+f"(d[16]), "+f"(d[17]), "+f"(d[18]), "+f"(d[19]), "+f"(d[20]), "+f"(d[21]), "+f"(d[22]), "+f"(d[23]), "+f"(d[24]), "+f"(d[25]), "+f"(d[26]), "+f"(d[27]), "+f"(d[28]), "+f"(d[29]), "+f"(d[30]), "+f"(d[31]), "+f"(d[32]), "+f"(d[33]), "+f"(d[34]), "+f"(d[35]), "+f"(d[36]), "+f"(d[37]), "+f"(d[38]), "+f"(d[39]), "+f"(d[40]), "+f"(d[41]), "+f"(d[42]), "+f"(d[43]), "+f"(d[44]), "+f"(d[45]), "+f"(d[46]), "+f"(d[47]), "+f"(d[48]), "+f"(d[49]), "+f"(d[50]), "+f"(d[51]), "+f"(d[52]), "+f"(d[53]), "+f"(d[54]), "+f"(d[55]), "+f"(d[56]), "+f"(d[57]), "+f"(d[58]), "+f"(d[59]), "+f"(d[60]), "+f"(d[61]), "+f"(d[62]), "+f"(d[63])
    : "r"(a0), "r"(a1), "r"(a2), "r"(a3), "l"(db), "r"(sd));
}

__device__ __forceinline__ void wgmma_m64n64_rs(float (&d)[32], const uint32_t* a, uint64_t db, int sd) {
  asm volatile(
    "{\n.reg .pred p;\nsetp.ne.b32 p, %37, 0;\n"
    "wgmma.mma_async.sync.aligned.m64n64k16.f32.bf16.bf16 "
    "{%0, %1, %2, %3, %4, %5, %6, %7, %8, %9, %10, %11, %12, %13, %14, %15, %16, %17, %18, %19, %20, %21, %22, %23, %24, %25, %26, %27, %28, %29, %30, %31}, {%32, %33, %34, %35}, %36, p, 1, 1, 0;\n}\n"
    : "+f"(d[0]), "+f"(d[1]), "+f"(d[2]), "+f"(d[3]), "+f"(d[4]), "+f"(d[5]), "+f"(d[6]), "+f"(d[7]), "+f"(d[8]), "+f"(d[9]), "+f"(d[10]), "+f"(d[11]), "+f"(d[12]), "+f"(d[13]), "+f"(d[14]), "+f"(d[15]), "+f"(d[16]), "+f"(d[17]), "+f"(d[18]), "+f"(d[19]), "+f"(d[20]), "+f"(d[21]), "+f"(d[22]), "+f"(d[23]), "+f"(d[24]), "+f"(d[25]), "+f"(d[26]), "+f"(d[27]), "+f"(d[28]), "+f"(d[29]), "+f"(d[30]), "+f"(d[31])
    : "r"(a[0]), "r"(a[1]), "r"(a[2]), "r"(a[3]), "l"(db), "r"(sd));
}

constexpr int G_STAGES = 4;
constexpr int G_A_BYTES = 128 * 64 * 2;
constexpr int G_B_BYTES = 256 * 64 * 2;
constexpr int G_STAGE_BYTES = G_A_BYTES + G_B_BYTES;
constexpr int G_STG_OFF = G_STAGES * G_STAGE_BYTES;
constexpr int BAR_OFF = G_STG_OFF + 32768 + 2048;
constexpr int SMEM_BYTES = BAR_OFF + 1024;
constexpr int B_GFULL = 0, B_GEMPTY = 32, B_OY2 = 64, B_PFULL = 224;
constexpr int B_KFULL = 80, B_KEMPTY = 96, B_VFULL = 112, B_VEMPTY = 128, B_QFULL = 144, B_QEMPTY = 160,
              B_QPEER = 184;
constexpr int B_CFULL = 192;
constexpr int B_OFREE = 256, B_OFULL = 272, B_OEMPTY = 320, B_OY = 368;
constexpr int B_SFULL = 392, B_SFREE = 424, B_PEND = 456, B_SCMD = 512;

#define PHASE_PROLOGUE                                                                \
  uint32_t tid, rt_zero;                                                              \
  asm volatile("mov.u32 %0, %%tid.x;" : "=r"(tid));                                   \
  asm volatile("mov.u32 %0, %%nctaid.y;" : "=r"(rt_zero));                            \
  asm volatile("" : "+r"(smem0));                                                     \
  rt_zero = __shfl_sync(0xffffffffu, rt_zero >> 8, 0);   \
  const uint32_t sbase = __shfl_sync(0xffffffffu, smem0, 0);                          \
  const uint32_t bar = sbase + BAR_OFF;                                               \
  const int wg = __shfl_sync(0xffffffffu, tid >> 7, 0);                               \
  const int warp = (tid >> 5) & 3, lane = tid & 31, wtid = tid & 127;                 \
  (void)rt_zero; (void)bar; (void)warp; (void)lane; (void)wtid;

constexpr int A_ITEMS = 256;
enum { ST_BOX1, ST_BOX1P, ST_BOX2, ST_BOX2W, ST_BOX2L, ST_PEER };
__device__ __forceinline__ void st_post(uint32_t bar, int wg, int wtid, uint32_t n, int kind, int dst, uint32_t src,
                                        int c0, int c1, int sig) {
  if (wtid == 0) sts128(bar + B_SCMD + wg * 32 + (n & 1) * 16, make_uint4(kind + dst * 8 + sig * 32, src, c0, c1));
  fence_proxy_async();
  __syncwarp();
  mbar_arrive_if(bar + B_SFULL + wg * 16 + (n & 1) * 8, (wtid & 31) == 0);
}
__device__ __forceinline__ void st_wait(uint32_t bar, int wg, uint32_t n) {
  const uint32_t b = bar + B_SFREE + wg * 16 + (n & 1) * 8;
  if (!mbar_try(b, ~(n >> 1) & 1)) mbar_wait(b, ~(n >> 1) & 1);
}
__device__ __forceinline__ void note(uint32_t bar, uint32_t cnt) {
  asm volatile("red.release.cta.shared.add.u32 [%0], 1;" ::"r"(bar + B_PEND + 4 * cnt) : "memory");
}
__device__ __forceinline__ void store_agent(const CUtensorMap* maps, uint32_t bar, int wg, uint32_t n) {
  const uint32_t fr = bar + B_SFREE + wg * 16;
  mbar_arrive(fr + (~n & 1) * 8);
  if (n == 0) mbar_arrive(fr);
  for (;; n++) {
    mbar_wait_sleep(bar + B_SFULL + wg * 16 + (n & 1) * 8, (n >> 1) & 1);
    uint4 c = lds128(bar + B_SCMD + wg * 32 + (n & 1) * 16);
    const CUtensorMap* dst = maps + ((c.x >> 3) & 3);
    const int sig = (int)c.x >> 5;
    c.x &= 7;
    if (c.x == ST_PEER) {
      mbar_wait_sleep(bar + B_QPEER, c.z);
      asm volatile(
          "{\n.reg .b32 d, b;\nmapa.shared::cluster.u32 d, %0, %2;\nmapa.shared::cluster.u32 b, %1, %2;\n"
          "cp.async.bulk.shared::cluster.shared::cta.mbarrier::complete_tx::bytes [d], [%3], 8192, [b];\n"
          "cp.async.bulk.shared::cluster.shared::cta.mbarrier::complete_tx::bytes [d + 16384], [%3 + 8192], 8192, [b];\n}\n" ::"r"(
              bar - BAR_OFF + 32768 + wg * 8192),
          "r"(bar + B_QFULL + 8), "r"(~blockIdx.x & 1), "r"(c.y)
          : "memory");
      mbar_wait_sleep(bar + B_QFULL + 8, 0);
      mbar_arrive_cluster_if(fr + (n & 1) * 8, ~blockIdx.x & 1, true);
      continue;
    }
    tma_store_2d(dst, c.y, c.z, c.w);
    if (c.x >= ST_BOX2) tma_store_2d(dst, c.y + 8192, c.z + 64, c.w);
    tma_store_commit();
    tma_store_wait_read<0>();
    if (c.x != ST_BOX1P) mbar_arrive(fr + (n & 1) * 8);
    if (c.x == ST_BOX2L) mbar_arrive(bar + B_OFREE + 8 * wg);
    if (sig >= 0) {
      tma_store_wait<0>();
      asm volatile("fence.proxy.async.global;" ::: "memory");
      note(bar, sig);
      if (c.x == ST_BOX2W) cnt_wait(CNT_CTX, 2 * A_ITEMS);
      if (c.x == ST_BOX2L) note(bar, CNT_DONE);
      if (c.x == ST_BOX2L || c.x == ST_BOX1P) break;
    }
  }
}

struct Maps {
  const bf16 *shift_k, *x, *gate_w, *ssm_k, *ssm_D;
  uint8_t id[128][4];
  CUtensorMap a[2];
  CUtensorMap b[3];
  CUtensorMap c[3];
  CUtensorMap bk, bv;
  CUtensorMap k, v;
  CUtensorMap oa, ob, oc, ox;
  CUtensorMap y, y2;
};

constexpr int P_SLOT = 67 * 128, P_V = 35 * 128, P_TAPS = 2 * P_SLOT;
__device__ __forceinline__ void ldsm4t(uint32_t (&r)[4], uint32_t a) {
  asm volatile("ldmatrix.sync.aligned.m8n8.x4.trans.shared.b16 {%0, %1, %2, %3}, [%4];"
               : "=r"(r[0]), "=r"(r[1]), "=r"(r[2]), "=r"(r[3])
               : "r"(a));
}
__device__ __forceinline__ uint32_t fma_bf2(uint32_t a, uint32_t b, uint32_t c) {
  uint32_t r;
  asm("fma.rn.bf16x2 %0, %1, %2, %3;" : "=r"(r) : "r"(a), "r"(b), "r"(c));
  return r;
}
__device__ __forceinline__ void agent_warp(const Maps& maps, uint32_t smem0) {
  mbar_wait_sleep(smem0 + BAR_OFF + B_GFULL + 8 * (G_STAGES - 1), 0);
#pragma unroll 1
  for (int j = 0; j < 7; j++) {
    PHASE_PROLOGUE
    const int w = __shfl_sync(0xffffffffu, warp, 0), i = j >> 1;
    const uint32_t pb = bar + B_PFULL + w * 16, sw = sbase + G_STG_OFF + w * (P_TAPS + 512);
    const int d0 = (blockIdx.x >> 4) * 128 + (j < 3 ? 64 : 0), t0 = (blockIdx.x & 15) * 128 + w * 64;
    const bool work = (0x56 >> j) & 1;
    GA(80 + 2 * j)
    if (work) mbar_wait_sleep(pb + (i & 1) * 8, i >> 1);
    GA(81 + 2 * j)
    if (((0x2b >> j) & 1) && elect_one()) {
      const uint32_t l = ((j + 1) >> 1) & 1, b = pb + l * 8, dst = sw + l * P_SLOT;
      mbar_expect_tx(b, work ? P_SLOT : P_SLOT + 512);
      const uint64_t pol = policy_evict_first();
      tma_load_2d_hint(dst, &maps.bk, b, d0, t0 + 32 * l - 3, pol);
      tma_load_2d_hint(dst + P_V, &maps.bv, b, d0, t0 + 32 * l, pol);
      if (!work) bulk_load(sbase + G_STG_OFF + P_TAPS, maps.shift_k + d0 * 4, 512, b);
    }
    if (!work) continue;
    const uint32_t so = sw + (i & 1) * P_SLOT;
    uint32_t ak[4];
#pragma unroll
    for (int r = 0; r < 4; r++) {
      const uint32_t a = so / 128 + r + 4 * (lane & 6) + (((((lane >> 2) ^ lane) & 6) + (lane & 1)) ^ 7);
      ak[r] = a * 128 + (a & 7) * 16;
    }
    bf16* dst = g_kvT + (size_t)(d0 + (lane >> 2)) * S_LEN + t0 + ((lane & 3) + 4 * (i & 1)) * 8;
#pragma unroll 1
    for (int cg = 0; cg < 128; cg += 16) {
      uint32_t t01, t23, k[4][4], v[4];
      asm volatile("ld.shared.v2.u32 {%0, %1}, [%2];"
                   : "=r"(t01), "=r"(t23)
                   : "r"(sbase + G_STG_OFF + P_TAPS + cg * 4 + (lane >> 2) * 8));
#pragma unroll
      for (int r = 0; r < 4; r++) ldsm4t(k[r], ak[r] ^ cg);
      ldsm4t(v, (ak[3] ^ cg) + 4096);
      const uint32_t w0 = __byte_perm(t01, 0, 0x1010), w1 = __byte_perm(t01, 0, 0x3232);
      const uint32_t w2 = __byte_perm(t23, 0, 0x1010), w3 = __byte_perm(t23, 0, 0x3232);
#pragma unroll
      for (int j = 0; j < 4; j++)
        v[j] = mul_bf2(fma_bf2(k[3][j], w0, fma_bf2(k[2][j], w1, fma_bf2(k[1][j], w2, mul_bf2(k[0][j], w3)))), v[j]);
      const bool s1 = lane & 1, s2 = lane & 2;
      const uint32_t a0 = s1 ? v[1] : v[0], a1 = s1 ? v[0] : v[1], a2 = s1 ? v[3] : v[2], a3 = s1 ? v[2] : v[3];
      *reinterpret_cast<uint4*>(dst) = make_uint4(s2 ? a2 : a0, s2 ? a3 : a1, s2 ? a0 : a2, s2 ? a1 : a3);
      dst += 8 * S_LEN;
    }
    fence_proxy_async();
    __syncwarp();
    if (j == 1) continue;
    GA(94)
    if (elect_one()) {
      note(bar, CNT_PREP + (j > 2));
      store_agent(maps.c, bar, w, (0x130800 >> (4 * j - 8)) & 255);
    }
    __syncwarp();
  }
}

__device__ __forceinline__ void qkv_tile(const Maps& maps, int it, int& m_tile, int& group) {
  const int b = maps.id[blockIdx.x][it >> 1];
  m_tile = b & 15;
  group = b >> 4;
}

constexpr int G_NTILES = 3;
__device__ __forceinline__ void qkv_producer(const Maps& maps, uint32_t sbase, int pass, bool first) {
  const uint32_t bar = sbase + BAR_OFF;
  uint32_t stage = 0, phase = pass;
#pragma unroll 1
  for (int it = 0; it < (first ? 1 : G_NTILES); it++) {
    int m_tile, group;
    qkv_tile(maps, it, m_tile, group);
    const CUtensorMap* ma = &maps.a[it >> 1];
    const CUtensorMap* mb = &maps.b[it];
    const int nk = first ? G_STAGES : it == 2 ? 16 : 8;
#pragma unroll 1
    for (int kt = (it == 0 && !first && !pass) ? G_STAGES : 0; kt < nk; kt++) {
      if (pass && it == 0 && kt < G_STAGES) {
        constexpr uint32_t LASTB = (B_QEMPTY + 8) | (B_KEMPTY << 8) | ((B_VEMPTY + 8) << 16) | (B_VEMPTY << 24);
        mbar_wait_sleep(bar + ((LASTB >> (8 * kt)) & 255), kt == 2);
      }
      if (!first) mbar_wait_sleep(bar + B_GEMPTY + 8 * stage, phase);
      const uint32_t fb = bar + B_GFULL + 8 * stage;
      const uint32_t sa = sbase + stage * G_STAGE_BYTES;
      mbar_expect_tx(fb, G_STAGE_BYTES);
      tma_load_2d(sa, ma, fb, kt * 64, m_tile * 128);
      tma_load_3d(sa + G_A_BYTES, mb, fb, 0, kt * 64, group * 8 + pass * 4);
      if (++stage == G_STAGES) { stage = 0; phase ^= 1; }
      {
        const int b = maps.id[blockIdx.x][1];
        if (it == 1 && kt == (b & 7))
          asm volatile("cp.async.bulk.prefetch.tensor.3d.L2.global.tile [%0, {%1, %2, %3}];" ::"l"(&maps.b[2]), "r"(0),
                       "r"((b & 15) * 64), "r"((b >> 4) * 8 + pass * 4)
                       : "memory");
      }
      if (pass && it == 0 && kt == G_STAGES - 1) {
#pragma unroll 1
        for (int i = 0; i < 12; i++) {
          asm volatile("mbarrier.inval.shared::cta.b64 [%0];" ::"r"(bar + B_KFULL + 8 * i) : "memory");
          mbar_init(bar + B_KFULL + 8 * i, 1 + ((i >> 1) & 1));
        }
        fence_proxy_async();
      }
    }
  }
}

__device__ __noinline__ void publisher(uint32_t bar, int lane, uint32_t nsrc) {
  uint32_t done = 0;
  CLK_DECL
#pragma unroll 1
  for (uint32_t spins = 0; done < nsrc && spins < (1u << 20); spins++) {
    CLK_SAMPLE
    uint32_t v = 0;
    if (lane < CNT_N)
      asm volatile("atom.acquire.cta.shared.exch.b32 %0, [%1], 0;" : "=r"(v) : "r"(bar + B_PEND + 4 * lane) : "memory");
    done += __shfl_sync(0xffffffffu, v, CNT_DONE);
    if (lane == CNT_DONE) v = 0;
    if (done == nsrc && lane < CNT_DONE) {
      uint32_t w;
      asm volatile("atom.acquire.cta.shared.exch.b32 %0, [%1], 0;" : "=r"(w) : "r"(bar + B_PEND + 4 * lane) : "memory");
      v += w;
    }
    if (v && lane == 0) { TD(0) }
    if (v) cnt_signal_release(lane, v);
    if (v && lane == 0) { TD(1) }
    if (!__any_sync(0xffffffffu, v != 0)) __nanosleep(200);
  }
  CLK_END
  __threadfence();
  __syncwarp();
}

__device__ __forceinline__ void gate_rows(const Maps& maps, uint32_t sbase, int w48, int w12, int lane) {
  const uint32_t buf = sbase + w12 * 16384, gb = sbase + BAR_OFF + 768 + w12 * 16;
  if (lane == 0) {
    mbar_init(gb, 1);
    mbar_init(gb + 8, 1);
    fence_barrier_init();
    for (int i = 0; i < 2; i++) {
      mbar_expect_tx(gb + 8 * i, 8192);
      bulk_load(buf + i * 8192, maps.x + (size_t)(w48 + 48 * i) * 4 * DM, 8192, gb + 8 * i);
    }
  }
  __syncwarp();
  uint4 wv[4];
#pragma unroll
  for (int i = 0; i < 4; i++) wv[i] = __ldg(reinterpret_cast<const uint4*>(maps.gate_w + (i * 32 + lane) * 8));
  int it = 0;
#pragma unroll 1
  for (int row = w48 * 4; row < S_LEN; row += 48 * 4, it++) {
    mbar_wait(gb + 8 * (it & 1), (it >> 1) & 1);
    uint4 xv[4][4];
#pragma unroll
    for (int r = 0; r < 4; r++)
#pragma unroll
      for (int i = 0; i < 4; i++) xv[r][i] = lds128(buf + (it & 1) * 8192 + r * 2048 + (i * 32 + lane) * 16);
    float d[2][4];
#pragma unroll
    for (int pr = 0; pr < 2; pr++) {
      d[pr][0] = d[pr][1] = d[pr][2] = d[pr][3] = 0.f;
      auto acc = [&](uint32_t a0, uint32_t a2, uint32_t b0, uint32_t b2, uint32_t w0, uint32_t w2) {
        asm volatile(
            "mma.sync.aligned.m16n8k16.row.col.f32.bf16.bf16.f32 {%0, %1, %2, %3}, {%4, %5, %6, %7}, {%8, %8}, "
            "{%0, %1, %2, %3};"
            : "+f"(d[pr][0]), "+f"(d[pr][1]), "+f"(d[pr][2]), "+f"(d[pr][3])
            : "r"(mul_bf2(a0, w0)), "r"(mul_bf2(b0, w0)), "r"(mul_bf2(a2, w2)), "r"(mul_bf2(b2, w2)), "r"(0x3f803f80u));
      };
#pragma unroll
      for (int i = 0; i < 4; i++) {
        acc(xv[2 * pr][i].x, xv[2 * pr][i].y, xv[2 * pr + 1][i].x, xv[2 * pr + 1][i].y, wv[i].x, wv[i].y);
        acc(xv[2 * pr][i].z, xv[2 * pr][i].w, xv[2 * pr + 1][i].z, xv[2 * pr + 1][i].w, wv[i].z, wv[i].w);
      }
    }
    float sum = (lane & 2) ? ((lane & 1) ? d[1][2] : d[1][0]) : ((lane & 1) ? d[0][2] : d[0][0]);
#pragma unroll
    for (int off = 16; off >= 4; off >>= 1) sum += __shfl_xor_sync(0xffffffffu, sum, off);
    if (lane < 4) g_gate[row + lane] = bf16_round(rcp(1.0f + __expf(-bf16_round(sum))));
    if (lane == 0 && row + 2 * 48 * 4 < S_LEN) {
      mbar_expect_tx(gb + 8 * (it & 1), 8192);
      bulk_load(buf + (it & 1) * 8192, maps.x + (size_t)(row + 2 * 48 * 4) * DM, 8192, gb + 8 * (it & 1));
    }
  }
}

constexpr float Q_SCALE = 0.08838834764831845f * 1.4426950408889634f;
__device__ __forceinline__ uint32_t qkv_consumer(const Maps& maps, uint32_t smem0, uint32_t sn, uint32_t (&p)[32]) {
  PHASE_PROLOGUE
  float acc[128];
#pragma unroll
  for (int i = 0; i < 128; i++) asm volatile("mov.b32 %0, 0;" : "=f"(acc[i]));
  uint32_t stage = 0, phase = 0, prev_stage = 0;
  const uint32_t stg = sbase + G_STG_OFF + wg * 18432;
  const int st_row = warp * 16 + (lane & 7) + ((lane >> 3) & 1) * 8;
  const int st_cb = lane >> 4;
  uint32_t pend[32];
  int m_tile, group;
  qkv_tile(maps, 0, m_tile, group);
  auto put_box = [&](uint32_t buf, const uint32_t* v) {
#pragma unroll
    for (int jp = 0; jp < 4; jp++) {
      const int chunk = jp * 2 + st_cb;
      const uint32_t addr = buf + st_row * 128 + ((chunk ^ (st_row & 7)) << 4);
      stmatrix_x4(addr, v[jp * 4], v[jp * 4 + 1], v[jp * 4 + 2], v[jp * 4 + 3]);
    }
  };
  GT(gti++)
#pragma unroll
  for (int i = 0; i < 32; i++) pend[i] = 0;
#pragma unroll 1
  for (int it = 0;; it++) {
    const int nk = it == 2 ? 16 : 8;
#pragma unroll 1
    for (int kt = 0; kt < nk; kt++) {
      mbar_wait((bar + B_GFULL) + 8 * stage, phase);
      GT(gti++)
      const uint64_t da0 = make_desc(sbase + stage * G_STAGE_BYTES + wg * 8192, 16, 1024, DESC_SW128);
      const uint64_t db0 = make_desc(sbase + stage * G_STAGE_BYTES + G_A_BYTES, 8192, 1024, DESC_SW128);
      asm volatile("{\n.reg .pred p;\nsetp.ne.u32 p, %0, 0;\n@p bar.sync 3, 256;\n}\n" ::"r"((uint32_t)(wg && kt == nk - 1))
                   : "memory");
      wgmma_fence();
#pragma unroll
      for (int kk = 0; kk < 4; kk++) {
        wgmma_m64n256_ss_tb(acc, desc_add(da0, kk * 2), desc_add(db0, kk * 128), (kt | kk) != 0);
      }
      wgmma_commit();
      asm volatile("{\n.reg .pred p;\nsetp.ne.u32 p, %0, 0;\n@p bar.arrive 3, 256;\n}\n" ::"r"((uint32_t)(!wg && kt == nk - 1))
                   : "memory");
      const uint32_t when = it == 0 ? 0 : wg ? 0xAA : 0x55;
      if ((when >> kt) & 1) {
        const int c = kt >> 1;
        st_wait(bar, wg, sn - (it + c == 1 ? 1 : 2));
        const uint32_t buf = stg + (c & 1) * 8192;
        switch (c) {
          case 0: put_box(buf, p); break;
          case 1: put_box(buf, p + 16); break;
          case 2: put_box(buf, pend); break;
          default: put_box(buf, pend + 16); break;
        }
        st_post(bar, wg, wtid, sn, it + c == 5 ? ST_BOX1P : ST_BOX1, it - 1, buf, group * 256 + c * 64,
                m_tile * 128 + wg * 64, c == 3 ? CNT_KV + (sn > 8) : -1);
        sn++;
      }
      wgmma_wait<1>();
      mbar_arrive_if((bar + B_GEMPTY) + 8 * prev_stage, wtid == 32 && kt > 0);
      prev_stage = stage;
      if (++stage == G_STAGES) { stage = 0; phase ^= 1; }
    }
    wgmma_wait<0>();
    fence_regs(acc);
    GT(gti++)
    mbar_arrive_if((bar + B_GEMPTY) + 8 * prev_stage, wtid == 32);
    if (it == G_NTILES - 1) break;
#pragma unroll
    for (int j = 0; j < 32; j++) {
      p[j] = pack_bf16(acc[2 * j], acc[2 * j + 1]);
      pend[j] = pack_bf16(acc[64 + 2 * j], acc[64 + 2 * j + 1]);
    }
  }
  ST(19)
  st_wait(bar, wg, sn - 1);
  mbar_wait(bar + B_GEMPTY, 1);
#pragma unroll
  for (int j = 0; j < 32; j++) pend[j] = pack_bf16(acc[2 * j] * Q_SCALE, acc[2 * j + 1] * Q_SCALE);
  put_box(sbase + wg * 8192, pend);
  put_box(sbase + 16384 + wg * 8192, pend + 16);
#pragma unroll
  for (int j = 0; j < 32; j++) p[j] = pack_bf16(acc[64 + 2 * j] * Q_SCALE, acc[65 + 2 * j] * Q_SCALE);
  put_box(stg, p);
  put_box(stg + 8192, p + 16);
  st_post(bar, wg, wtid, sn, ST_PEER, 0, stg, sn >> 4, 0, 0);
  sn++;
  GT(gti++)
  return sn;
}

constexpr int A_TILE = 128 * 128 * 2;
constexpr int A_Q_OFF = 0;
constexpr int A_K_OFF = 2 * A_TILE;
constexpr int A_V_OFF = 4 * A_TILE;
constexpr int A_O_OFF = 6 * A_TILE;

constexpr uint32_t A_STEPS = 17;
__device__ __forceinline__ int item_m(uint32_t it) { return it & 15; }
__device__ __forceinline__ int item_h(uint32_t it) { return it >> 4; }

constexpr int C_H0 = 16, C_U = C_H0 + 4096 + 112, C_SLOT = C_U + 4096;
constexpr int C_H1 = 2 * C_SLOT + 80;
constexpr int C_X_OFF = C_H1 + 4096 + 48;

__device__ __forceinline__ uint32_t item_of(const Maps& maps, uint32_t r) {
  const uint32_t b = maps.id[blockIdx.x & 127][1];
  return (b >> 4) * 64 + r * 16 + ((b ^ ((r & 1) * 15)) & 15);
}

constexpr uint32_t C_SIDE = 48;
__device__ __forceinline__ uint32_t conv_first(const Maps& maps) {
  const uint32_t b = maps.id[blockIdx.x & 127][1];
  return (b >> 4) * 128 + (b & 15);
}

__device__ __forceinline__ void conv_consumer(const Maps& maps, uint32_t smem0, uint32_t first, uint32_t step,
                                              uint32_t end) {
  PHASE_PROLOGUE
  const uint32_t full = bar + B_CFULL + wg * 16;
  const uint32_t ca = sbase + (wg ? A_V_OFF + A_TILE : A_Q_OFF);
  const int w4 = __shfl_sync(0xffffffffu, warp, 0);
  auto fetch = [&](uint32_t c, uint32_t slot) {
    if (w4 == 2 && c < end) {
      if (elect_one()) {
        const uint32_t sb = ca + slot * C_SLOT, fb = full + 8 * slot;
        const uint64_t pol = policy_evict_first();
        mbar_expect_tx(fb, 2 * 4096);
        bulk_load_hint(sb + C_H0, maps.ssm_k + (size_t)c * S_LEN, 4096, fb, pol);
        bulk_load_hint(sb + C_U, g_kvT + (size_t)c * S_LEN, 4096, fb, pol);
      }
    }
  };
  auto shift_h = [&](uint32_t so) {
    const uint32_t a = ca + so + C_H0 + wtid * 16;
#pragma unroll
    for (int i = 0; i < 2; i++) {
      uint32_t p;
      const uint4 v = lds128(a + i * 2048);
      asm volatile("ld.shared.u32 %0, [%1];" : "=r"(p) : "r"(a + i * 2048 - 4));
      sts128(ca + C_H1 + wtid * 16 + i * 2048, make_uint4(__byte_perm(p, v.x, 0x5432), __byte_perm(v.x, v.y, 0x5432),
                                                      __byte_perm(v.y, v.z, 0x5432), __byte_perm(v.z, v.w, 0x5432)));
    }
  };
  if (wtid == 96 && wg) { TD(15) }
  fetch(first, 0);
  if (wtid < 17)
    sts128(ca + (wtid >> 3) * C_SLOT + (wtid & 7 ? 4096 + (wtid & 7) * 16 : (wtid & 16) * 4), make_uint4(0, 0, 0, 0));
  fence_proxy_async();
  const uint32_t ha = ca + ((lane & 4) ? C_H1 : C_H0) + 4 * ((lane & 3) - (lane >> 3)) + w4 * 256;
  const uint32_t ua = ca + C_U + w4 * 256 + (lane >> 4) * 1024 + (lane & 15) * 16;
  const uint32_t xa = ca + C_X_OFF + lane * 8, xw = xa + w4 * 3072;
  uint32_t xg[3];
#pragma unroll
  for (int k = 0; k < 3; k++) {
    const int w = (w4 + k + 1) & 3;
    xg[k] = xa + (w * 12 + w4 - w - (w < w4 ? 1 : 0)) * 256;
  }
  const bool pp = step != 16;
  uint32_t h[2][16];
  const uint32_t hs = (lane & 4) ? 0 : C_SLOT;
  auto load_h = [&](uint32_t so, int a) {
#pragma unroll
    for (int i = 0; i < 16; i++)
      asm volatile("ld.shared.u32 %0, [%1];"
                   : "=r"(h[a & 1][i])
                   : "r"(ha + so + 1024 * a + 32 * (i >> 2) + (i & 1) * 128 + (~i & 2) * 8));
  };
  mbar_wait(full, 0);
  named_bar_sync(1 + wg, 128);
  shift_h(0);
  named_bar_sync(1 + wg, 128);
  fetch(first + step, 1);
  load_h(0, 0);
  load_h(0, 1);
  mbar_wait(bar + B_OFREE, 0);
  mbar_wait(bar + B_OFREE + 8, 0);
  uint32_t n = 0, ch = first;
  for (; ch < end; n++, ch += step) {
    CT(0)
    const uint32_t so = (n & 1) * C_SLOT, ho = (n & 1) * hs;
    uint32_t db = (uint32_t)make_desc(ca + so + C_U - 16, 16, 0, 0);
    asm volatile("" : "+r"(db));
    uint32_t dsk = __ldg(reinterpret_cast<const unsigned short*>(maps.ssm_D) + (ch | (lane & rt_zero)));
    float d[4][32], own[16];
    auto mma = [&](int a) {
      wgmma_fence();
#pragma unroll
      for (int c = a; c < 4; c++)
#pragma unroll
        for (int b = 0; b < 4; b++)
          wgmma_m64n64_rs(d[c], &h[a & 1][4 * b], (8ull << 32) | (db + 64 * (c - a) - 2 * b), (a | b) != 0);
      wgmma_commit();
    };
    auto put = [&](int c) {
      fence_regs(d[c]);
#pragma unroll
      for (int e = 0; e < 2; e++) {
        if (c == 0) asm volatile("mov.b32 %0, %1;" : "=f"(own[e]) : "f"(d[c][e]));
        else own[4 * c + e] += d[c][e];
        own[4 * c + 2 + e] = d[c][4 + e] + d[c][2 + e];
        if (c < 3) asm volatile("mov.b32 %0, %1;" : "=f"(own[4 * c + 4 + e]) : "f"(d[c][30 + e]));
      }
#pragma unroll
      for (int j = 1; j < 4; j++)
        asm volatile("{\n.reg .pred p;\nsetp.lt.s32 p, %3, 4;\n@p st.shared.v2.u32 [%0], {%1, %2};\n}\n" ::"r"(
                         xw + (3 * c + j - 1) * 256),
                     "r"(pack_bf16(d[c][8 * j] + d[c][8 * j - 2], d[c][8 * j + 1] + d[c][8 * j - 1])),
                     "r"(pack_bf16(d[c][8 * j + 4] + d[c][8 * j + 2], d[c][8 * j + 5] + d[c][8 * j + 3])),
                     "r"(c < 3 ? 0 : w4 + j)
                     : "memory");
    };
    named_bar_sync(pp ? 4 + wg : 1 + wg, pp ? 256 : 128);
    CT(1)
    mma(0);
    mma(1);
    wgmma_wait<1>();
    load_h(ho, 2);
    put(0);
    mma(2);
    CT(2)
    wgmma_wait<1>();
    load_h(ho, 3);
    put(1);
    mma(3);
    asm volatile("{\n.reg .pred p;\nsetp.ne.u32 p, %1, 0;\n@p bar.arrive %0, 256;\n}\n" ::"r"(5 - wg), "r"((uint32_t)pp) : "memory");
    CT(3)
    uint32_t sk[8];
    asm volatile("ldmatrix.sync.aligned.m8n8.x4.trans.shared.b16 {%0, %1, %2, %3}, [%4];"
                 : "=r"(sk[0]), "=r"(sk[1]), "=r"(sk[2]), "=r"(sk[3])
                 : "r"(ua + so));
    asm volatile("ldmatrix.sync.aligned.m8n8.x4.trans.shared.b16 {%0, %1, %2, %3}, [%4];"
                 : "=r"(sk[4]), "=r"(sk[5]), "=r"(sk[6]), "=r"(sk[7])
                 : "r"(ua + so + 2048));
    mbar_wait(full + 8 * (~n & 1), (((n + 1) >> 1) & 1) ^ (ch + step < end ? 0 : 1));
    named_bar_sync(1 + wg, 128);
    shift_h(C_SLOT - so);
    wgmma_wait<1>();
    put(2);
    uint32_t dep = 0;
#pragma unroll
    for (int i = 0; i < 8; i++) dep |= sk[i] = mul_bf2(sk[i], dsk | (dsk << 16));
    CT(4)
    wgmma_wait<0>();
    put(3);
    named_bar_sync((1 + wg) | (dep & rt_zero), 128);
    CT(5)
    fetch(ch + 2 * step, n & 1);
    if (wtid == 96 && n) note(bar, CNT_Y2 + (((ch - step) & 127) >= 112));
    uint2 q[12];
#pragma unroll
    for (int i = 0; i < 12; i++) {
      if (i >= 3) {
        asm volatile("ld.shared.v2.u32 {%0, %1}, [%2];" : "=r"(q[i].x), "=r"(q[i].y) : "r"(xg[i % 3] + (i / 3) * 768));
      } else {
        q[i] = make_uint2(0, 0);
        asm volatile("{\n.reg .pred p;\nsetp.gt.s32 p, %3, 2;\n@p ld.shared.v2.u32 {%0, %1}, [%2];\n}\n"
                     : "+r"(q[i].x), "+r"(q[i].y)
                     : "r"(xg[i]), "r"(w4 + i));
      }
    }
    load_h(hs - ho, 0);
    load_h(hs - ho, 1);
    CT(6)
    uint32_t* dst = reinterpret_cast<uint32_t*>(g_y2T + (size_t)ch * S_LEN) + 64 * w4 + (lane ^ 28);
#pragma unroll
    for (int f = 0; f < 4; f++) {
#pragma unroll
      for (int k = 0; k < 3; k++) {
        own[4 * f] += bf_lo(q[3 * f + k].x);
        own[4 * f + 1] += bf_hi(q[3 * f + k].x);
        own[4 * f + 2] += bf_lo(q[3 * f + k].y);
        own[4 * f + 3] += bf_hi(q[3 * f + k].y);
      }
#pragma unroll
      for (int i = 0; i < 2; i++) {
        dst[256 * f + 32 * i] = add_bf2(pack_bf16(own[4 * f + 2 * i], own[4 * f + 2 * i + 1]), sk[2 * f + i]);
      }
    }
    CT(7)
  }
  named_bar_sync(1 + wg, 128);
  if (wtid == 96 && wg) { TD(8) }
  if (wtid == 96) cnt_signal_release(CNT_Y2 + (((ch - step) & 127) >= 112), 1);
  if (wtid == 64) note(bar, CNT_DONE);
  if (wtid == 96 && wg) { TD(9) }
}

__device__ __forceinline__ void attn_producer(const Maps& maps, uint32_t sbase, int pass, bool dry) {
  const uint32_t bar = sbase + BAR_OFF;
  const uint32_t q_full = bar + B_QFULL, q_empty = bar + B_QEMPTY;
  const uint32_t k_full = bar + B_KFULL, k_empty = bar + B_KEMPTY, v_full = bar + B_VFULL, v_empty = bar + B_VEMPTY;
  int ndrained = 0;
  auto wait = [&](uint32_t b, uint32_t par) {
    if (!dry) mbar_wait_sleep(b, par);
  };
  auto drained = [&](int upto) {
#pragma unroll 1
    for (; ndrained <= upto; ndrained++) wait(bar + B_GEMPTY + 8 * ndrained, 1);
  };
  uint32_t st = 0, ph = 1, vs = 0, vp = 1;
  int pend_j = -1, pend_h = 0;
  PT_DECL
  cnt_wait(CNT_KV + pass, dry ? 0 : 512);
  drained(1);
  if (!dry) {
    mbar_arrive(q_full);
    mbar_expect_tx(q_full + 8, A_TILE);
  }
  mbar_arrive_cluster_if(bar + B_QPEER, ~blockIdx.x & 1, !dry);
#pragma unroll 1
  for (int round = dry; round < 3; round++) {
    const uint32_t item = item_of(maps, round);
    const int m = round == 2 ? -1 : dry ? 0 : item_m(item), h = (item >> 6) * 4 + round * 2;
    const int tpost = m >= 3 ? m - 1 : m;
#pragma unroll 1
    for (int t = m < 0 ? -1 : 0; t <= m; t++) {
      const int j = (t < m && round) ? m - 1 - t : t;
      if (t >= 0) {
        drained(1 + st);
        wait(k_empty + 8 * st, ph);
        if (!dry) {
          PT
          mbar_expect_tx(k_full + 8 * st, A_TILE);
          tma_load_3d(sbase + A_K_OFF + st * A_TILE, &maps.k, k_full + 8 * st, 0, j * 128, h);
        }
        if (++st == 2) { st = 0; ph ^= 1; }
      }
      if (pend_j >= 0) {
        drained(3);
        wait(v_empty + 8 * vs, vp);
        if (!dry) {
          mbar_expect_tx(v_full + 8 * vs, A_TILE);
          tma_load_3d(sbase + A_V_OFF + (vs ^ 1) * A_TILE, &maps.v, v_full + 8 * vs, 0, pend_j * 128, pend_h);
        }
        if (++vs == 2) { vs = 0; vp ^= 1; }
      }
      pend_j = j;
      pend_h = h;
      if (t == tpost && round == 1) {
        if (pass) {
          cnt_wait(CNT_PREP + 1, dry ? 0 : 516);
          cnt_wait(CNT_CTX, dry ? 0 : 2 * A_ITEMS);
          asm volatile("cp.async.bulk.prefetch.L2.global [%0], 4096;" ::"l"(maps.ssm_k + (size_t)conv_first(maps) * S_LEN));
          if (!dry)
            asm volatile("cp.async.bulk.prefetch.L2.global [%0], 4096;" ::"l"(g_kvT + (size_t)conv_first(maps) * S_LEN));
        }
        wait(q_empty, 0);
        if (!dry) mbar_arrive(q_full);
      }
    }
  }
}

__device__ __forceinline__ uint32_t attn_consumer(const Maps& maps, uint32_t smem0, uint32_t sn, uint32_t (&p)[32]) {
  PHASE_PROLOGUE
  float s[64], o[64], e[32];
  const uint32_t q_full = bar + B_QFULL, q_empty = bar + B_QEMPTY;
  const uint32_t k_full = bar + B_KFULL, k_empty = bar + B_KEMPTY, v_full = bar + B_VFULL;
  uint32_t dep = 0;
  constexpr int MIDJ = 5;
  float l0 = 0.f, l1 = 0.f, b0 = 0.f, b1 = 0.f;
  const int sched_own = 4 + wg, sched_other = 5 - wg;

  const uint32_t qd0 = (uint32_t)make_desc(sbase + A_Q_OFF + wg * 8192, 16, 0, 0);
  const uint32_t kd0 = (uint32_t)make_desc(sbase + A_K_OFF, 16, 0, 0);
  const uint32_t vd0 = (uint32_t)make_desc(sbase + A_V_OFF, 16384, 0, 0);
  constexpr uint64_t DHI = DESC_SW128 | ((uint64_t)(1024 >> 4) << 32);
  constexpr uint32_t DST = A_TILE >> 4;
  auto issue_qk = [&](uint32_t qd, uint32_t kd, uint32_t z = 0) {
#pragma unroll
    for (int kk = 0; kk < 8; kk++) {
      const uint32_t off = ((kk >> 2) * 16384 + (kk & 3) * 32) >> 4;
      wgmma_m64n128_ss(s, DHI | (qd + off), DHI | (kd + off), kk ? 1 : z);
    }
    wgmma_commit();
  };
  auto issue_pv = [&](uint32_t vd, bool accumulate, int nk) {
#pragma unroll
    for (int kk = 0; kk < 8; kk++) {
      if (kk < nk)
        wgmma_m64n128_rs_tb(o, p[4 * kk], p[4 * kk + 1], p[4 * kk + 2], p[4 * kk + 3], DHI | (vd + kk * 128),
                            accumulate || (kk != 0));
    }
    wgmma_commit();
  };
  auto exp_lo = [&](float& a0, float& a1) {
#pragma unroll
    for (int j = 0; j < 8; j++) {
      e[4 * j] = ex2(s[4 * j]);
      e[4 * j + 1] = ex2(s[4 * j + 1]);
      e[4 * j + 2] = ex2(s[4 * j + 2]);
      e[4 * j + 3] = ex2(s[4 * j + 3]);
      a0 += e[4 * j];
      a0 += e[4 * j + 1];
      a1 += e[4 * j + 2];
      a1 += e[4 * j + 3];
      if (j == MIDJ) dep = (__float_as_uint(a0) | __float_as_uint(a1)) & rt_zero;
    }
  };
  auto pack_lo = [&]() {
#pragma unroll
    for (int j = 0; j < 16; j++) p[j] = pack_bf16(e[2 * j], e[2 * j + 1]);
  };
  auto finish_p = [&](float& a0, float& a1) {
    pack_lo();
#pragma unroll
    for (int j = 8; j < 16; j++) {
      const float e0 = ex2(s[4 * j]), e1 = ex2(s[4 * j + 1]), e2 = ex2(s[4 * j + 2]), e3 = ex2(s[4 * j + 3]);
      a0 += e0;
      a0 += e1;
      a1 += e2;
      a1 += e3;
      p[2 * j] = pack_bf16(e0, e1);
      p[2 * j + 1] = pack_bf16(e2, e3);
      if (j == 8 + MIDJ) dep = __float_as_uint(a0) & rt_zero;
    }
  };
  auto quad_sum = [&](float t) {
    t += __shfl_xor_sync(0xffffffffu, t, 1);
    return t + __shfl_xor_sync(0xffffffffu, t, 2);
  };
  auto write_o = [&](const float (&o)[64], float i0, float i1) {
    st_wait(bar, wg, sn - 1);
    const int st_row = warp * 16 + (lane & 7) + ((lane >> 3) & 1) * 8;
    const uint32_t so = sbase + A_O_OFF + wg * 18432 + st_row * 128;
#pragma unroll
    for (int j = 0; j < 16; j += 2)
      stmatrix_x4(so + (j >> 3) * 8192 + ((((j & 7) + (lane >> 4)) ^ (lane & 7)) << 4),
                  pack_bf16(o[4 * j] * i0, o[4 * j + 1] * i0), pack_bf16(o[4 * j + 2] * i1, o[4 * j + 3] * i1),
                  pack_bf16(o[4 * j + 4] * i0, o[4 * j + 5] * i0), pack_bf16(o[4 * j + 6] * i1, o[4 * j + 7] * i1));
  };
  auto store_o = [&](uint32_t r, int kind) {
    const uint32_t pass = sn >> 4, it = item_of(maps, 2 * pass + r);
    st_post(bar, wg, wtid, sn, kind, 2, sbase + A_O_OFF + wg * 18432, item_h(it) * 128,
            item_m(it) * 128 + wg * 64, CNT_CTX + pass);
    sn++;
  };
  auto mask_half = [&](float* sh) {
    const int u = warp * 16 + (lane >> 2) - (lane & 3) * 2;
#pragma unroll
    for (int j = 0; j < 8; j++) {
      if (8 * j > u) sh[4 * j] = -INFINITY;
      if (8 * j + 1 > u) sh[4 * j + 1] = -INFINITY;
      if (8 * j - 8 > u) sh[4 * j + 2] = -INFINITY;
      if (8 * j - 7 > u) sh[4 * j + 3] = -INFINITY;
    }
  };
  ST(0)
  mbar_wait(k_full, 0);
  ST(20)
  named_bar_sync(sched_own, 256);
  ST(21)
#pragma unroll
  for (int i = 0; i < 64; i++) asm volatile("mov.b32 %0, 0;" : "=f"(s[i]));
  wgmma_fence();
  issue_qk(qd0, kd0, rt_zero);
  named_bar_arrive(sched_other, 256);
  ST(36) ST(37) ST(38)
  ST(22)
#pragma unroll
  for (int i = 0; i < 64; i++) asm volatile("mov.b32 %0, 0;" : "=f"(o[i]));
  wgmma_wait<0>();
  fence_regs(s);
  mbar_arrive_if(k_empty, wtid == 32);
  uint32_t g = 0;
  uint32_t rnd = 0;
  int rem = item_m(item_of(maps, 0));
  uint32_t first = 1;
  uint32_t fl = 0;
#define LOWT (first ? (g == A_STEPS - 1 ? INFINITY : 9.094947e-13f) : -1.f)
#define redo (fl & 1)
#define shifted (fl & 2)
  float d0 = 0.f, d1 = 0.f;
  float pi0 = 1.f, pi1 = 1.f;
  ST(1)
  for (;;) {
    if (shifted) {
#pragma unroll
      for (int j = 0; j < 16; j++) {
        s[4 * j] -= d0;
        s[4 * j + 1] -= d0;
        s[4 * j + 2] -= d1;
        s[4 * j + 3] -= d1;
      }
    }
    if (rem == 0 && !redo) {
      mbar_arrive_if(q_empty + 8 * (rnd & 1), wtid == 96);
      rnd++;
      if (wg == 0) mask_half(s);
      else mask_half(s + 32);
    }
    for (;;) {
      const bool kill = rem == 0 && wg == 0;
      const uint32_t kd = kd0 + ((g + 1) & 1) * DST, vd = vd0 + (~g & 1) * DST;
      float a0 = 0.f, a1 = 0.f;
      exp_lo(a0, a1);
      fence_regs(e);
      const uint32_t kb = k_full + 8 * ((g + 1) & 1);
      const uint32_t kpar = ((((g + 1) >> 1) & 1) ^ (g == A_STEPS - 1 ? 1u : 0u)) | dep;
      if (!mbar_try(kb, kpar)) mbar_wait(kb, kpar | ((__float_as_uint(a0) | __float_as_uint(a1)) & rt_zero));
      wgmma_wait<0>();
      fence_regs(o);
      ST(g < 4 ? 24 + 3 * g : 39)
      if (kill) {
        mbar_arrive_if(kb + (B_VEMPTY - B_KFULL), wtid == 64 && !redo && g > 0);
        fence_regs(e);
        pack_lo();
#pragma unroll
        for (int j = 16; j < 32; j++) asm volatile("mov.u32 %0, 0;" : "=r"(p[j]));
        goto check;
      }
#pragma unroll
      for (int i = 32; i < 64; i++) asm volatile("" : "+f"(s[i])::"memory");
      mbar_arrive_if(kb + (B_VEMPTY - B_KFULL), wtid == 64 && !redo && g > 0);
      finish_p(a0, a1);
      if (__any_sync(0xffffffffu, !(mbar_try(v_full + 8 * (g & 1), ((g >> 1) & 1) | dep) &
                                    mbar_try(q_full + 8 * (rnd & 1), ((rnd >> 1) & 1) | dep)) ||
                                      !(a0 + a1 < 1.0995116e12f) || !(fminf(a0, a1) > LOWT))) {
      check:
        bool bad = !(a0 + a1 < 1.0995116e12f);
        if (first) bad |= !(fminf(quad_sum(a0), quad_sum(a1)) > 9.094947e-13f);
        if (!redo && __any_sync(0xffffffffu, bad)) {
          d0 = d1 = first ? -INFINITY : 0.f;
#pragma unroll
          for (int j = 0; j < 16; j++) {
            if (j < 8 || !kill) {
              d0 = fmaxf(d0, fmaxf(s[4 * j], s[4 * j + 1]));
              d1 = fmaxf(d1, fmaxf(s[4 * j + 2], s[4 * j + 3]));
            }
          }
#pragma unroll
          for (int x = 1; x <= 2; x++) {
            d0 = fmaxf(d0, __shfl_xor_sync(0xffffffffu, d0, x));
            d1 = fmaxf(d1, __shfl_xor_sync(0xffffffffu, d1, x));
          }
          b0 += d0;
          b1 += d1;
          if (!first) {
            const float al0 = ex2(-d0), al1 = ex2(-d1);
            l0 *= al0;
            l1 *= al1;
#pragma unroll
            for (int j = 0; j < 16; j++) {
              o[4 * j] *= al0;
              o[4 * j + 1] *= al0;
              o[4 * j + 2] *= al1;
              o[4 * j + 3] *= al1;
            }
          }
          fl = 3;
          break;
        }
        if (first && g == A_STEPS - 1) {
          write_o(o, pi0, pi1);
          store_o(0, ST_BOX2);
        }
        mbar_wait(v_full + 8 * (g & 1), (g >> 1) & 1);
        mbar_wait(q_full + 8 * (rnd & 1), (rnd >> 1) & 1);
      }
      ST(g < 4 ? 25 + 3 * g : 39)
      named_bar_sync(sched_own, 256);
      ST(g < 4 ? 26 + 3 * g : 39)
      if (g == A_STEPS - 1) {
        fence_regs(o);
        if (kill) {
          wgmma_fence();
          issue_pv(vd, !first, 4);
        } else {
          wgmma_fence();
          issue_pv(vd, !first, 8);
        }
        named_bar_arrive(sched_other, 256);
        pi0 = rcp(quad_sum(l0 + a0));
        pi1 = rcp(quad_sum(l1 + a1));
        goto done;
      }
      wgmma_fence();
      issue_qk(qd0 + (rnd & 1) * DST, kd);
      if (first && g) write_o(o, pi0, pi1);
      fence_regs(o);
      if (kill) {
        wgmma_fence();
        issue_pv(vd, !first, 4);
      } else {
        wgmma_fence();
        issue_pv(vd, !first, 8);
      }
      named_bar_arrive(sched_other, 256);
      fl &= 2;
      l0 += a0;
      l1 += a1;
      if (rem == 0 || first) {
        if (first && g) store_o(0, ST_BOX2);
        first = rem == 0;
        if (first) {
          pi0 = rcp(quad_sum(l0));
          pi1 = rcp(quad_sum(l1));
          l0 = l1 = b0 = b1 = 0.f;
          fl = 0;
          rem = item_m(item_of(maps, 1)) + 1;
        }
      }
      rem--;
      g++;
      wgmma_wait<1>();
      fence_regs(s);
      mbar_arrive_if(kb + (B_KEMPTY - B_KFULL), wtid == 32);
      ST(g + 1)
      if (rem == 0 || shifted) {
        d0 = b0;
        d1 = b1;
        break;
      }
    }
  }
done:
#undef redo
#undef shifted
  wgmma_wait<0>();
  fence_regs(o);
  mbar_arrive_if(bar + B_VEMPTY, wtid == 64);
  write_o(o, pi0, pi1);
  store_o(1, ST_BOX2W + (sn >> 4));
  ST(18)
  return sn;
}

constexpr int O_STAGES = 5;
constexpr int O_STAGE_BYTES = 32768;
constexpr int O_Y_OFF = 5 * 32768;
constexpr int O_X_OFF = 6 * 32768 + 2048;
constexpr int O_NK = HDIM / 64;

__device__ __forceinline__ uint32_t out_stage(uint32_t st) { return ((0x41230u >> (4 * st)) & 7) * O_STAGE_BYTES; }

__device__ __forceinline__ void out_producer(const Maps& maps, uint32_t sbase, bool dry) {
  const uint32_t bar = sbase + BAR_OFF;
  const uint32_t rank = blockIdx.x & 1;
  const int m_tile = maps.id[blockIdx.x][2] & 15, n_tile = maps.id[blockIdx.x][2] >> 4;
  uint32_t stage = 0, phase = 0;
  const int kx = dry ? O_STAGES : 17 + (blockIdx.x >> 1) % 12;
#pragma unroll 1
  for (int ki = 0; ki <= O_STAGES; ki++) {
    if (ki < O_STAGES) {
      constexpr uint32_t LASTB = (B_KEMPTY + 8) | (B_KEMPTY << 8) | ((B_QEMPTY + 8) << 16) | ((B_VEMPTY + 8) << 24);
      if (ki > 0 && !dry) mbar_wait_sleep(bar + ((LASTB >> (8 * ki - 8)) & 255), (0x12 >> ki) & 1);
      mbar_arrive_cluster_if(bar + B_OEMPTY + 8 * ki, 0, !dry);
      mbar_arrive_cluster_if(bar + B_OEMPTY + 8 * ki, 1, !dry);
      if (!dry) {
        mbar_expect_tx(bar + B_OFULL + 8 * ki, O_STAGE_BYTES);
        tma_load_4d(sbase + out_stage(ki), &maps.oa, bar + B_OFULL + 8 * ki, ((ki & 14) * 4 + (ki & 1)) * 64, m_tile);
      }
    }
    if (ki > 0 && !dry) {
      const int k = ki - 1;
      mbar_wait_sleep(bar + B_OEMPTY + 8 * k, 0);
      tma_load_2d_mc(sbase + out_stage(k) + 16384 + rank * 8192, &maps.ob, bar + B_OFULL + 8 * k, n_tile * 128 + rank * 64,
                     ((k & 14) * 4 + (k & 1)) * 64, (uint16_t)3);
    }
    if (dry) ki += O_STAGES - 1;
  }
  phase = 1;
#pragma unroll 1
  for (int ki = O_STAGES; ki < (dry ? O_STAGES + 1 : O_NK); ki++) {
    const int kt = (ki & 14) * 4 + (ki >> 4) * 2 + (ki & 1);
    const uint32_t fb = bar + B_OFULL + 8 * stage, eb = bar + B_OEMPTY + 8 * stage;
    const uint32_t sa = sbase + out_stage(stage);
    if (ki == (dry ? O_STAGES : 16)) cnt_wait(CNT_CTX + 1, dry ? 0 : 2 * A_ITEMS);
    if (ki == kx) {
      if (!dry) {
        mbar_wait_sleep(bar + B_OFREE, 0);
        mbar_wait_sleep(bar + B_OFREE + 8, 0);
        mbar_expect_tx(bar + B_OY, 32768);
        tma_load_4d(sbase + O_X_OFF, &maps.ox, bar + B_OY, n_tile * 128, m_tile);
        tma_load_4d(sbase + O_X_OFF + 16384, &maps.ox, bar + B_OY, n_tile * 128 + 64, m_tile);
      }
    }
    if (!dry) {
      mbar_wait_sleep(eb, phase);
      mbar_expect_tx(fb, O_STAGE_BYTES);
      tma_load_4d(sa, &maps.oa, fb, kt * 64, m_tile);
      tma_load_2d_mc(sa + 16384 + rank * 8192, &maps.ob, fb, n_tile * 128 + rank * 64, kt * 64, (uint16_t)3);
    }
    if (++stage == O_STAGES) { stage = 0; phase ^= 1; }
  }
  if (!dry) mbar_wait_sleep(bar + B_OY2, 0);
}

constexpr int OWNQ = 2;
__device__ __forceinline__ void out_side(const Maps& maps, uint32_t smem0, const float (&gv)[4]) {
  PHASE_PROLOGUE
  const int m_tile = maps.id[blockIdx.x][2] & 15, n_tile = maps.id[blockIdx.x][2] >> 4;
  const int w4 = __shfl_sync(0xffffffffu, warp, 0);
  if (w4 == 0) {
    if (elect_one()) {
      mbar_expect_tx(bar + B_OY, 32768 - 4096);
      TD(10)
      GS(0)
      cnt_wait(CNT_Y2, DM - 128);
      GS(1)
      TD(7)
      for (const uint32_t t = clock(); (uint32_t)clock() - t < (blockIdx.x & 14) * 200;) __nanosleep(32);
      TD(11)
      GS(2)
      fence_proxy_async();
      tma_load_2d(sbase + O_Y_OFF, &maps.y, bar + B_OY, m_tile * 128, n_tile * 128);
      tma_load_2d(sbase + O_Y_OFF + 16384, &maps.y, bar + B_OY, m_tile * 128 + 64, n_tile * 128);
    }
  }
  mbar_wait_sleep(bar + B_OY, 0);
  const int st_row = warp * 16 + (lane & 7) + ((lane >> 3) & 1) * 8;
  const int mrow = (lane & 7) + ((lane >> 4) & 1) * 8;
  const int mchunk = warp * 2 + ((lane >> 3) & 1);
  const uint32_t xrow = sbase + O_X_OFF + st_row * 128;
  const uint32_t yrow = sbase + O_Y_OFF + mrow * 128 + ((mchunk ^ (lane & 7)) << 4);
  uint32_t y[7][4], x[7][4], om[4];
#pragma unroll
  for (int i = 0; i < 4; i++) om[i] = pack_bf16(1.0f - gv[i], 1.0f - gv[i]);
  auto xa = [&](int h, int i) { return xrow + h * 8192 + (i >> 2) * 16384 + ((((i & 3) * 2 + (lane >> 4)) ^ (lane & 7)) << 4); };
  auto load = [&](int r, int h, int i) {
    ldsm4t(y[r], yrow + h * 16384 + i * 2048);
    asm volatile("ldmatrix.sync.aligned.m8n8.x4.shared.b16 {%0, %1, %2, %3}, [%4];"
                 : "=r"(x[r][0]), "=r"(x[r][1]), "=r"(x[r][2]), "=r"(x[r][3])
                 : "r"(xa(h, i)));
  };
  auto store = [&](int r, int h, int i, uint32_t om0, uint32_t om1) {
    stmatrix_x4(xa(h, i), mul_bf2(om0, mul_bf2(x[r][0], y[r][0])), mul_bf2(om1, mul_bf2(x[r][1], y[r][1])),
                mul_bf2(om0, mul_bf2(x[r][2], y[r][2])), mul_bf2(om1, mul_bf2(x[r][3], y[r][3])));
  };
  if (wtid == 0) { TD(12) GS(3) }
#pragma unroll 1
  for (int h = 0; h < 2; h++) {
#pragma unroll
    for (int i = 0; i < 7; i++) load(i, h, i);
#pragma unroll
    for (int i = 0; i < 7; i++) store(i, h, i, h ? om[2] : om[0], h ? om[3] : om[1]);
  }
  if (wtid == 0) { TD(4) GS(4) }
  mbar_wait_sleep(bar + B_OY2, 0);
#pragma unroll
  for (int h = 0; h < 2; h++) load(h, h, 7);
#pragma unroll
  for (int h = 0; h < 2; h++) store(h, h, 7, om[2 * h], om[2 * h + 1]);
  __syncwarp();
  mbar_arrive_if(bar + B_OY + 8, lane == 0);
  if (wtid == 0) { TD(13) GS(6) }
#pragma unroll
  for (int i = 0; i < 4 - OWNQ; i++) {
    const int h = i >> 1, c = i & 1;
    named_bar_sync(6 + i, 256);
    if (elect_one()) {
      fence_proxy_async();
      tma_store_4d(&maps.oc, sbase + O_X_OFF + c * 16384 + h * 8192 + w4 * 2048, n_tile * 128 + c * 64, 2 * w4,
                   2 * m_tile + h);
      tma_store_commit();
    }
  }
}

__device__ __forceinline__ void out_gemm(const Maps& maps, uint32_t smem0) {
  PHASE_PROLOGUE
  const int o_id = maps.id[blockIdx.x][2], m_tile = o_id & 15;
  float acc[2][64];
  undef_regs(acc[0]);
  undef_regs(acc[1]);
  uint32_t stage = 0, phase = 0, prev_stage = 0;
  GT(gti++)
  const float* gp = g_gate + m_tile * 128 + warp * 2 + (lane >> 2) * 8;
  const float gv[4] = {__ldcg(gp), __ldcg(gp + 1), __ldcg(gp + 64), __ldcg(gp + 65)};
  if (wg == 1) {
    out_side(maps, smem0, gv);
    return;
  }
  constexpr uint64_t DHI = DESC_SW128 | ((uint64_t)(1024 >> 4) << 32);
#pragma unroll 1
  for (int kt = 0; kt < O_NK - 1; kt++) {
    uint32_t da = (uint32_t)make_desc(sbase + out_stage(stage), 16, 0, 0);
    uint32_t db = (uint32_t)make_desc(sbase + out_stage(stage) + 16384, 8192, 0, 0);
    asm volatile("" : "+r"(da), "+r"(db));
    mbar_wait(bar + B_OFULL + 8 * stage, phase);
    GT(gti++)
    constexpr int OWAIT = 2;
#pragma unroll
    for (int kk = 0; kk < 4; kk++) {
      wgmma_wait<OWAIT>();
      if (kk == OWAIT)
        mbar_arrive_cluster_if(bar + B_OEMPTY + 8 * prev_stage, wtid >> 6,
                               (wtid & 63) == 32 && kt > 0 && kt - 1 + O_STAGES < O_NK);
      wgmma_fence();
      wgmma_m64n128_ss_tb(acc[0], DHI | (da + kk * 2), DHI | (db + kk * 128), (kt | kk) != 0);
      wgmma_m64n128_ss_tb(acc[1], DHI | (da + 512 + kk * 2), DHI | (db + kk * 128), (kt | kk) != 0);
      wgmma_commit();
    }
    prev_stage = stage;
    if (++stage == O_STAGES) { stage = 0; phase ^= 1; }
  }
  {
    const uint32_t da = (uint32_t)make_desc(sbase + out_stage((O_NK - 1) % O_STAGES), 16, 0, 0);
    const uint32_t db = (uint32_t)make_desc(sbase + out_stage((O_NK - 1) % O_STAGES) + 16384, 8192, 0, 0);
    mbar_wait(bar + B_OFULL + 8 * ((O_NK - 1) % O_STAGES), ((O_NK - 1) / O_STAGES) & 1);
    GT(gti++)
#pragma unroll
    for (int h = 0; h < 2; h++) {
      wgmma_fence();
#pragma unroll
      for (int kk = 0; kk < 4; kk++)
        wgmma_m64n128_ss_tb(acc[h], DHI | (da + h * 512 + kk * 2), DHI | (db + kk * 128), 1);
      wgmma_commit();
    }
  }
  if (tid == 0) { TD(14) }
  const int st_row = warp * 16 + (lane & 7) + ((lane >> 3) & 1) * 8;
  const uint32_t rowa = sbase + O_X_OFF + st_row * 128;
  auto oa = [&](int i) { return rowa + (i >> 3) * 8192 + (i & 4) * 4096 + ((((i & 3) * 2 + (lane >> 4)) ^ (st_row & 7)) << 4); };
  uint32_t b[16][4];
  LT(6, 0)
  mbar_wait(bar + B_OY + 8, 0);
  LT(7, 0)
#pragma unroll
  for (int i = 0; i < 16; i++)
    asm volatile("ldmatrix.sync.aligned.m8n8.x4.shared.b16 {%0, %1, %2, %3}, [%4];"
                 : "=r"(b[i][0]), "=r"(b[i][1]), "=r"(b[i][2]), "=r"(b[i][3])
                 : "r"(oa(i)));
  uint32_t gg[4];
#pragma unroll
  for (int i = 0; i < 4; i++) gg[i] = pack_bf16(gv[i], gv[i]);
#pragma unroll
  for (int i = 0; i < 16; i++) {
    const int h = i >> 3;
    if (i == 0) wgmma_wait<1>();
    if (i == 8) wgmma_wait<0>();
    if (i % 8 == 0) fence_regs(acc[h]);
    const float* a = acc[h] + 8 * (i & 7);
    const uint32_t gg0 = gg[2 * h], gg1 = gg[2 * h + 1];
    stmatrix_x4(oa(i), fma_bf2(gg0, pack_bf16(a[0], a[1]), b[i][0]), fma_bf2(gg1, pack_bf16(a[2], a[3]), b[i][1]),
                fma_bf2(gg0, pack_bf16(a[4], a[5]), b[i][2]), fma_bf2(gg1, pack_bf16(a[6], a[7]), b[i][3]));
    if (i % 4 == 3 && i / 4 < 4 - OWNQ) named_bar_arrive(6 + i / 4, 256);
    if (i % 4 == 3 && i / 4 >= 4 - OWNQ) {
      fence_proxy_async();
      __syncwarp();
      if (elect_one()) {
        const int w4 = warp;
        tma_store_4d(&maps.oc, sbase + O_X_OFF + ((i / 4) & 1) * 16384 + h * 8192 + w4 * 2048,
                     (o_id >> 4) * 128 + ((i / 4) & 1) * 64, 2 * w4, 2 * m_tile + h);
        tma_store_commit();
      }
    }
  }
  GT(gti++)
}

__device__ __noinline__ void leave_kernel() {
  if (atomicAdd(g_cnt + CNT_DONE * 32, 1u) == 2 * gridDim.x - 1) {
    for (int i = 0; i < CNT_N; i++) g_cnt[i * 32] = 0;
  }
}

__device__ __noinline__ void side_jobs(const Maps& maps, uint32_t sbase) {
  const int w12 = __shfl_sync(0xffffffffu, threadIdx.x >> 5, 0);
  gate_rows(maps, sbase, (blockIdx.x - 128) * 12 + w12, w12, threadIdx.x & 31);
  fence_proxy_async();
  __syncthreads();
  if (threadIdx.x == 320) cnt_signal_release(CNT_PREP + 1, 1);
}

__global__ void __launch_bounds__(384, 1) fused_kernel(const __grid_constant__ Maps maps) {
  extern __shared__ __align__(1024) uint8_t smem_raw[];
  {
    const uint32_t sbase = __shfl_sync(0xffffffffu, smem_u32(smem_raw), 0);
    const uint32_t bar = sbase + BAR_OFF;
    const int tid = threadIdx.x;
    TL(0, 0) LT(0, 0)
    if (__shfl_sync(0xffffffffu, tid >> 5, 0) == 1 && blockIdx.x < 128) {
      if (elect_one()) {
        for (int i = 0; i < G_STAGES; i++) mbar_init(bar + B_GFULL + 8 * i, 1);
        fence_barrier_init();
        qkv_producer(maps, sbase, 0, true);
      }
    }
    if (tid == 0) {
      for (int i = 0; i < G_STAGES; i++) {
        mbar_init(bar + B_GEMPTY + 8 * i, 2);
        mbar_init(bar + B_SFULL + 8 * i, 4);
        mbar_init(bar + B_SFREE + 8 * i, 1);
      }
      for (int i = 0; i < 2; i++) {
        mbar_init(bar + B_OFREE + 8 * i, 1);
        mbar_init(bar + B_QFULL + 8 * i, 1);
        mbar_init(bar + B_QEMPTY + 8 * i, 2);
        mbar_init(bar + B_KFULL + 8 * i, 1);
        mbar_init(bar + B_KEMPTY + 8 * i, 2);
        mbar_init(bar + B_VFULL + 8 * i, 1);
        mbar_init(bar + B_VEMPTY + 8 * i, 2);
      }
      for (int i = 0; i < O_STAGES; i++) {
        mbar_init(bar + B_OFULL + 8 * i, 1);
        mbar_init(bar + B_OEMPTY + 8 * i, 2);
      }
      mbar_init(bar + B_OY, 2);
      mbar_init(bar + B_OY2, 1);
      mbar_init(bar + B_OY + 8, 4);
      mbar_init(bar + B_QPEER, 1);
      for (int i = 0; i < 8; i++) mbar_init(bar + B_CFULL + 8 * i, 1);
      for (int i = 0; i < CNT_N; i++) asm volatile("st.shared.u32 [%0], 0;" ::"r"(bar + B_PEND + 4 * i) : "memory");
      fence_barrier_init();
    }
    __syncthreads();
    asm volatile("barrier.cluster.arrive.relaxed.aligned;" ::: "memory");
    if (blockIdx.x >= 128) side_jobs(maps, sbase);
  }
  uint32_t smem0 = smem_u32(smem_raw);
  PHASE_PROLOGUE
  const bool mainc = blockIdx.x < 128;
  TL(0, 1)

  if (wg != 2) {
    reg_alloc<232>();
    if (wg == 1) named_bar_arrive(4, 256);
    mbar_wait(bar + B_OFREE + 8, mainc);
    if (mainc) {
      uint32_t sn = 0, p[32];
#pragma unroll
      for (int i = 0; i < 32; i++) asm volatile("" : "=r"(p[i]));
#pragma unroll 1
      do {
        sn = qkv_consumer(maps, smem_u32(smem_raw), sn, p);
        LT(1 + 2 * (sn >> 4), 0)
        sn = attn_consumer(maps, smem_u32(smem_raw), sn, p);
        LT(2 + 2 * (sn >> 4), 0)
      } while (sn < 16);
    }
    asm volatile("barrier.cluster.wait.acquire.aligned;" ::: "memory");
    if (mainc && __shfl_sync(0xffffffffu, threadIdx.x, 0) < 128) {
      named_bar_arrive(3, 256);
    } else {
      named_bar_sync(3, 256);
      const uint32_t b2 = blockIdx.x * 2 + (threadIdx.x >> 7);
      const uint32_t first = __shfl_sync(0xffffffffu, mainc ? conv_first(maps) : (b2 - 255) * 128 - C_SIDE, 0);
      conv_consumer(maps, smem_u32(smem_raw), first, mainc ? 16 : 1, (first | 127) + 1 - (mainc ? C_SIDE : 0));
    }
    if (mainc) out_gemm(maps, smem_u32(smem_raw));
    tma_store_wait_read<0>();
    TL2(3, 2) LT(5, 128)
  } else {
    reg_dealloc<40>();
    asm volatile("barrier.cluster.wait.acquire.aligned;" ::: "memory");
    const int w = __shfl_sync(0xffffffffu, tid >> 5, 0) - 8;
    if (w < 2) {
      if (mainc) agent_warp(maps, smem_u32(smem_raw));
      if (mainc && w == 0 && elect_one()) {
        mbar_wait_sleep(bar + B_OY, 0);
        mbar_expect_tx(bar + B_OY2, 4096);
        cnt_wait(CNT_Y2 + 1, 128);
        GS(5)
        const int id = maps.id[blockIdx.x][2];
        for (int i = 0; i < 2; i++)
          tma_load_2d(sbase + O_Y_OFF + i * 16384 + 112 * 128, &maps.y2, bar + B_OY2, (id & 15) * 128 + i * 64,
                      (id >> 4) * 128 + 112);
      }
    } else {
      if (mainc && elect_one()) {
        const bool dry = w == 2;
#pragma unroll 1
        for (int pass = dry; pass < 2; pass++) {
          if (!dry) qkv_producer(maps, sbase, pass, false);
          attn_producer(maps, sbase, pass, dry);
        }
        out_producer(maps, sbase, dry);
      }
      if (!mainc && tid == 352) {
        cnt_wait(CNT_PREP, 256);
        mbar_arrive(bar + B_OFREE);
        mbar_arrive(bar + B_OFREE + 8);
      }
      __syncwarp();
      if (w == 2) publisher(bar, tid & 31, mainc ? 3 : 2);
      if ((tid & 31) == 0) leave_kernel();
    }
  }
}

__device__ __forceinline__ float ldf(const bf16* p) { return __bfloat162float(*p); }
__global__ void __launch_bounds__(256) plain_gemm(const bf16* A, const bf16* B, bf16* C, int k, int ldb, int n) {
  __shared__ float sa[16][65], sb[16][64];
  const int tx = threadIdx.x & 15, ty = threadIdx.x >> 4, m0 = blockIdx.y * 64, n0 = blockIdx.x * 64;
  float acc[4][4] = {};
  for (int k0 = 0; k0 < k; k0 += 16) {
    for (int i = threadIdx.x; i < 1024; i += 256) {
      sa[i & 15][i >> 4] = ldf(A + (size_t)(m0 + (i >> 4)) * k + k0 + (i & 15));
      sb[i >> 6][i & 63] = ldf(B + (size_t)(k0 + (i >> 6)) * ldb + n0 + (i & 63));
    }
    __syncthreads();
    for (int kk = 0; kk < 16; kk++)
      for (int i = 0; i < 4; i++)
        for (int j = 0; j < 4; j++) acc[i][j] += sa[kk][ty * 4 + i] * sb[kk][tx + 16 * j];
    __syncthreads();
  }
  for (int i = 0; i < 4; i++)
    for (int j = 0; j < 4; j++) C[(size_t)(m0 + ty * 4 + i) * n + n0 + tx + 16 * j] = __float2bfloat16_rn(acc[i][j]);
}
__global__ void __launch_bounds__(256) plain_attn(int half) {
  const int lane = threadIdx.x & 31, t = blockIdx.x * 8 + (threadIdx.x >> 5), c = blockIdx.y * HD + lane * 4;
  bf16* io = g_ctx + (size_t)t * HDIM + half * (HDIM / 2) + c;
  float q[4], o[4] = {}, m = -INFINITY, l = 0.f;
  for (int i = 0; i < 4; i++) q[i] = ldf(io + i) * 0.08838834764831845f;
  for (int j = 0; j <= t; j++) {
    float s = 0.f;
    for (int i = 0; i < 4; i++) s += q[i] * ldf(g_k + (size_t)j * (HDIM / 2) + c + i);
    for (int x = 16; x; x >>= 1) s += __shfl_xor_sync(0xffffffffu, s, x);
    const float mn = fmaxf(m, s), al = __expf(m - mn), p = __expf(s - mn);
    for (int i = 0; i < 4; i++) o[i] = o[i] * al + p * ldf(g_v + (size_t)j * (HDIM / 2) + c + i);
    l = l * al + p;
    m = mn;
  }
  for (int i = 0; i < 4; i++) io[i] = __float2bfloat16_rn(o[i] / l);
}
__global__ void __launch_bounds__(256) plain_gate(const bf16* x, const bf16* w) {
  const int lane = threadIdx.x & 31, t = blockIdx.x * 8 + (threadIdx.x >> 5);
  float s = 0.f;
  for (int i = lane; i < DM; i += 32) s += bf16_round(ldf(x + (size_t)t * DM + i) * ldf(w + i));
  for (int o = 16; o; o >>= 1) s += __shfl_xor_sync(0xffffffffu, s, o);
  if (lane == 0) g_gate[t] = bf16_round(1.0f / (1.0f + __expf(-bf16_round(s))));
}
__global__ void __launch_bounds__(256) plain_conv(const bf16* x, const bf16* k, const bf16* v, const bf16* shift_k,
                                                  const bf16* ssm_k, const bf16* ssm_D, bf16* out) {
  __shared__ float u[S_LEN], h[S_LEN];
  const int c = blockIdx.x;
  for (int t = threadIdx.x; t < S_LEN; t += 256) {
    float s = 0.f;
    for (int i = 3; i >= 0; i--)
      if (t >= i) s = bf16_round(s + bf16_round(ldf(k + (size_t)(t - i) * DM + c) * ldf(shift_k + c * 4 + i)));
    u[t] = bf16_round(s * ldf(v + (size_t)t * DM + c));
    h[t] = ldf(ssm_k + (size_t)c * S_LEN + t);
  }
  __syncthreads();
  for (int t = threadIdx.x; t < S_LEN; t += 256) {
    float y = 0.f;
    for (int i = 0; i <= t; i++) y += h[i] * u[t - i];
    y = bf16_round(bf16_round(y) + bf16_round(u[t] * ldf(ssm_D + c)));
    const float g = g_gate[t], b = bf16_round(ldf(x + (size_t)t * DM + c) * y);
    bf16* o = out + (size_t)t * DM + c;
    *o = __float2bfloat16_rn(bf16_round(g * ldf(o)) + bf16_round(bf16_round(1.0f - g) * b));
  }
}

typedef CUresult (*PFN_tmapEncode)(CUtensorMap*, CUtensorMapDataType, cuuint32_t, void*, const cuuint64_t*,
                                   const cuuint64_t*, const cuuint32_t*, const cuuint32_t*, CUtensorMapInterleave,
                                   CUtensorMapSwizzle, CUtensorMapL2promotion, CUtensorMapFloatOOBfill);
static PFN_tmapEncode s_encode = nullptr;

static void make_map_2d(CUtensorMap* m, const void* ptr, int rows, int cols, int box_rows,
                        CUtensorMapL2promotion prom = CU_TENSOR_MAP_L2_PROMOTION_L2_256B) {
  cuuint64_t dims[2] = {(cuuint64_t)cols, (cuuint64_t)rows};
  cuuint64_t strides[1] = {(cuuint64_t)cols * 2};
  cuuint32_t box[2] = {64, (cuuint32_t)box_rows};
  cuuint32_t es[2] = {1, 1};
  s_encode(m, CU_TENSOR_MAP_DATA_TYPE_BFLOAT16, 2, const_cast<void*>(ptr), dims, strides, box, es,
           CU_TENSOR_MAP_INTERLEAVE_NONE, CU_TENSOR_MAP_SWIZZLE_128B, prom,
           CU_TENSOR_MAP_FLOAT_OOB_FILL_NONE);
}
static void make_map_3d(CUtensorMap* m, const void* ptr, int rows, int cols, int box_rows, int box_chunks) {
  cuuint64_t dims[3] = {64, (cuuint64_t)rows, (cuuint64_t)(cols / 64)};
  cuuint64_t strides[2] = {(cuuint64_t)cols * 2, 128};
  cuuint32_t box[3] = {64, (cuuint32_t)box_rows, (cuuint32_t)box_chunks};
  cuuint32_t es[3] = {1, 1, 1};
  s_encode(m, CU_TENSOR_MAP_DATA_TYPE_BFLOAT16, 3, const_cast<void*>(ptr), dims, strides, box, es,
           CU_TENSOR_MAP_INTERLEAVE_NONE, CU_TENSOR_MAP_SWIZZLE_128B, CU_TENSOR_MAP_L2_PROMOTION_L2_256B,
           CU_TENSOR_MAP_FLOAT_OOB_FILL_NONE);
}

static void make_map_4d(CUtensorMap* m, const void* ptr, int rows, int cols, int b2, int groups) {
  cuuint64_t dims[4] = {(cuuint64_t)cols, 8, 8, (cuuint64_t)(rows / 64)};
  cuuint64_t strides[3] = {(cuuint64_t)cols * 16, (cuuint64_t)cols * 2, (cuuint64_t)cols * 128};
  cuuint32_t box[4] = {64, 8, (cuuint32_t)b2, (cuuint32_t)groups};
  cuuint32_t es[4] = {1, 1, 1, 1};
  s_encode(m, CU_TENSOR_MAP_DATA_TYPE_BFLOAT16, 4, const_cast<void*>(ptr), dims, strides, box, es,
           CU_TENSOR_MAP_INTERLEAVE_NONE, CU_TENSOR_MAP_SWIZZLE_128B, CU_TENSOR_MAP_L2_PROMOTION_L2_256B,
           CU_TENSOR_MAP_FLOAT_OOB_FILL_NONE);
}

static cudaLaunchConfig_t fused_cfg(cudaLaunchAttribute* at) {
  cudaLaunchConfig_t cfg = {};
  cfg.gridDim = dim3(132);
  cfg.blockDim = dim3(384);
  cfg.dynamicSmemBytes = SMEM_BYTES;
  cfg.stream = cudaStreamPerThread;
  at[0].id = cudaLaunchAttributeClusterDimension;
  at[0].val.clusterDim.x = 2;
  at[0].val.clusterDim.y = 1;
  at[0].val.clusterDim.z = 1;
  cfg.attrs = at;
  cfg.numAttrs = 1;
  return cfg;
}

extern "C" void kernel_launch(void* const* d_in, const int* in_sizes, int n_in, void* d_out, int out_size) {
  const bf16* x = (const bf16*)d_in[0];
  const bf16* ckv = (const bf16*)d_in[1];
  const bf16* wq = (const bf16*)d_in[2];
  const bf16* wuk = (const bf16*)d_in[3];
  const bf16* wuv = (const bf16*)d_in[4];
  const bf16* wo = (const bf16*)d_in[5];
  const bf16* bk = (const bf16*)d_in[7];
  const bf16* bv = (const bf16*)d_in[8];
  const bf16* shift_k = (const bf16*)d_in[9];
  const bf16* ssm_k = (const bf16*)d_in[10];
  const bf16* ssm_D = (const bf16*)d_in[11];
  const bf16* gate_w = (const bf16*)d_in[12];
  bf16* out = (bf16*)d_out;

  static void *pk = nullptr, *pv = nullptr, *pctx = nullptr, *pb = nullptr;
  static int max_clusters = 0;
  if (!s_encode) {
    void* fn = nullptr;
    cudaDriverEntryPointQueryResult qres;
    cudaGetDriverEntryPoint("cuTensorMapEncodeTiled", &fn, cudaEnableDefault, &qres);
    s_encode = (PFN_tmapEncode)fn;
    cudaGetSymbolAddress(&pk, g_k);
    cudaGetSymbolAddress(&pv, g_v);
    cudaGetSymbolAddress(&pctx, g_ctx);
    cudaGetSymbolAddress(&pb, g_y2T);
    cudaFuncSetAttribute(fused_kernel, cudaFuncAttributeMaxDynamicSharedMemorySize, SMEM_BYTES);
    cudaLaunchAttribute at[1];
    cudaLaunchConfig_t cfg = fused_cfg(at);
    if (cudaOccupancyMaxActiveClusters(&max_clusters, fused_kernel, &cfg) != cudaSuccess) max_clusters = 0;
  }

  Maps all = {};
  make_map_2d(&all.a[0], ckv, S_LEN, DC, 128);
  make_map_2d(&all.a[1], x, S_LEN, DM, 128);
  make_map_3d(&all.b[0], wuk, DC, HDIM, 64, 4);
  make_map_3d(&all.b[1], wuv, DC, HDIM, 64, 4);
  make_map_3d(&all.b[2], wq, DM, HDIM, 64, 4);
  make_map_2d(&all.c[0], pk, S_LEN, HDIM / 2, 64);
  make_map_2d(&all.c[1], pv, S_LEN, HDIM / 2, 64);
  make_map_3d(&all.k, pk, S_LEN, HDIM / 2, 128, 2);
  make_map_3d(&all.v, pv, S_LEN, HDIM / 2, 128, 2);
  make_map_2d(&all.c[2], pctx, S_LEN, HDIM, 64);
  all.ssm_k = ssm_k;
  all.ssm_D = ssm_D;
  make_map_4d(&all.oa, pctx, S_LEN, HDIM, 8, 2);
  make_map_4d(&all.ox, x, S_LEN, DM, 8, 2);
  make_map_2d(&all.ob, wo, HDIM, DM, 64);
  make_map_4d(&all.oc, out, S_LEN, DM, 2, 1);
  make_map_2d(&all.y, pb, DM, S_LEN, 112);
  make_map_2d(&all.y2, pb, DM, S_LEN, 16);

  make_map_2d(&all.bk, bk, S_LEN, DM, 35, CU_TENSOR_MAP_L2_PROMOTION_L2_128B);
  make_map_2d(&all.bv, bv, S_LEN, DM, 32, CU_TENSOR_MAP_L2_PROMOTION_L2_128B);
  for (int b = 0; b < 128; b++) {
    const int c = b >> 1, r = b & 1;
    const int G = c < 4 ? 0 : c < 36 ? (c - 4) % 8 : 1 + (c - 36) % 7;
    const int i = c < 4 ? 4 + c : c < 36 ? (c - 4) / 8 : 4 + (c - 36) / 7;
    all.id[b][0] = r + 2 * (i & 1) + 4 * (G & 3) + 16 * (i >> 1) + 64 * (G >> 2);
    all.id[b][1] = (r ? 15 - i : i) + 16 * G;
    all.id[b][2] = r + 2 * G + 16 * i;
  }
  all.shift_k = shift_k;
  all.x = x;
  all.gate_w = gate_w;
  cudaLaunchAttribute at[1];
  cudaLaunchConfig_t cfg = fused_cfg(at);
  if (max_clusters >= 66) {
    cudaLaunchKernelEx(&cfg, fused_kernel, all);
  } else {
    const cudaStream_t st = cudaStreamPerThread;
    plain_gemm<<<dim3(HDIM / 64, S_LEN / 64), 256, 0, st>>>(x, wq, (bf16*)pctx, DM, HDIM, HDIM);
    for (int half = 0; half < 2; half++) {
      plain_gemm<<<dim3(HDIM / 128, S_LEN / 64), 256, 0, st>>>(ckv, wuk + half * (HDIM / 2), (bf16*)pk, DC, HDIM, HDIM / 2);
      plain_gemm<<<dim3(HDIM / 128, S_LEN / 64), 256, 0, st>>>(ckv, wuv + half * (HDIM / 2), (bf16*)pv, DC, HDIM, HDIM / 2);
      plain_attn<<<dim3(S_LEN / 8, NH / 2), 256, 0, st>>>(half);
    }
    plain_gemm<<<dim3(DM / 64, S_LEN / 64), 256, 0, st>>>((const bf16*)pctx, wo, out, HDIM, DM, DM);
    plain_gate<<<S_LEN / 8, 256, 0, st>>>(x, gate_w);
    plain_conv<<<DM, 256, 0, st>>>(x, bk, bv, shift_k, ssm_k, ssm_D, out);
  }
}
```

```cpp
#include <cuda_runtime.h>
#include <cuda_bf16.h>
#include <cuda.h>
#include <stdint.h>

typedef __nv_bfloat16 bf16;
#define INPLACE 3

constexpr int S_LEN = 2048;
constexpr int DM = 1024;
constexpr int NH = 32;
constexpr int HD = 128;
constexpr int DC = 512;
constexpr int HDIM = NH * HD;

__device__ __align__(1024) bf16 g_k[S_LEN * HDIM / 2];
__device__ __align__(1024) bf16 g_v[S_LEN * HDIM / 2];
__device__ __align__(1024) bf16 g_ctx[S_LEN * HDIM];
__device__ __align__(1024) bf16 g_kvT[DM * S_LEN];
#define g_y2T g_kvT
__device__ __align__(1024) float g_gate[S_LEN];
enum { CNT_KV = 0, CNT_PREP = 2, CNT_CTX = 4, CNT_Y2 = 6, CNT_DONE = 8, CNT_N };
__device__ unsigned int g_cnt[CNT_N * 32];

#define TL(k, i)
#define TL2(k, i)
#define TD(i)
#define LT(i, thr)
#define PT_DECL
#define PT
#define CLK_DECL
#define CLK_SAMPLE
#define CLK_END
#define CT(i)
#define GT(i)
#define GS(i)
#define GA(i)
#define ST(i)

__device__ __forceinline__ uint32_t smem_u32(const void* p) { return (uint32_t)__cvta_generic_to_shared(p); }

__device__ __forceinline__ void mbar_init(uint32_t bar, uint32_t count) {
  asm volatile("mbarrier.init.shared::cta.b64 [%0], %1;" ::"r"(bar), "r"(count));
}
__device__ __forceinline__ void mbar_expect_tx(uint32_t bar, uint32_t bytes) {
  asm volatile("mbarrier.arrive.expect_tx.shared::cta.b64 _, [%0], %1;" ::"r"(bar), "r"(bytes) : "memory");
}
__device__ __forceinline__ void mbar_arrive(uint32_t bar) {
  asm volatile("mbarrier.arrive.shared::cta.b64 _, [%0];" ::"r"(bar) : "memory");
}
__device__ __forceinline__ void mbar_wait(uint32_t bar, uint32_t parity) {
  uint32_t done;
  uint32_t spins = 0;
  do {
    asm volatile(
        "{\n.reg .pred p;\n"
        "mbarrier.try_wait.parity.shared::cta.b64 p, [%1], %2;\n"
        "selp.u32 %0, 1, 0, p;\n}\n"
        : "=r"(done)
        : "r"(bar), "r"(parity)
        : "memory");
    if (++spins > (1u << 22)) break;
  } while (!done);
}
__device__ __forceinline__ bool mbar_try(uint32_t bar, uint32_t parity) {
  uint32_t done;
  asm volatile(
      "{\n.reg .pred p;\n"
      "mbarrier.try_wait.parity.shared::cta.b64 p, [%1], %2;\n"
      "selp.u32 %0, 1, 0, p;\n}\n"
      : "=r"(done)
      : "r"(bar), "r"(parity)
      : "memory");
  return done != 0;
}
__device__ __forceinline__ bool elect_one() {
  uint32_t pred;
  asm volatile("{\n.reg .pred p;\nelect.sync _|p, 0xffffffff;\nselp.u32 %0, 1, 0, p;\n}\n" : "=r"(pred));
  return pred != 0;
}
__device__ __forceinline__ void mbar_arrive_if(uint32_t bar, bool pred) {
  asm volatile(
      "{\n.reg .pred p;\nsetp.ne.b32 p, %1, 0;\n"
      "@p mbarrier.arrive.shared::cta.b64 _, [%0];\n}\n" ::"r"(bar),
      "r"((uint32_t)pred)
      : "memory");
}
__device__ __forceinline__ void mbar_wait_sleep(uint32_t bar, uint32_t parity) {
  uint32_t done;
  uint32_t spins = 0;
  do {
    asm volatile(
        "{\n.reg .pred p;\n"
        "mbarrier.try_wait.parity.shared::cta.b64 p, [%1], %2, %3;\n"
        "selp.u32 %0, 1, 0, p;\n}\n"
        : "=r"(done)
        : "r"(bar), "r"(parity), "r"(20000u)
        : "memory");
    if (++spins > (1u << 16)) break;
  } while (!done);
}
__device__ __forceinline__ void fence_barrier_init() {
  asm volatile("fence.mbarrier_init.release.cluster;" ::: "memory");
}
__device__ __forceinline__ void fence_proxy_async() {
  asm volatile("fence.proxy.async.shared::cta;" ::: "memory");
}
__device__ __forceinline__ void named_bar_sync(int id, int nthreads) {
  asm volatile("bar.sync %0, %1;" ::"r"(id), "r"(nthreads) : "memory");
}
__device__ __forceinline__ void named_bar_arrive(int id, int nthreads) {
  asm volatile("bar.arrive %0, %1;" ::"r"(id), "r"(nthreads) : "memory");
}
__device__ __forceinline__ void tma_load_2d(uint32_t dst, const CUtensorMap* m, uint32_t bar, int c0, int c1) {
  asm volatile(
      "cp.async.bulk.tensor.2d.shared::cluster.global.mbarrier::complete_tx::bytes [%0], [%1, {%3, %4}], [%2];" ::"r"(dst),
      "l"(reinterpret_cast<uint64_t>(m)), "r"(bar), "r"(c0), "r"(c1)
      : "memory");
}
__device__ __forceinline__ void tma_load_3d(uint32_t dst, const CUtensorMap* m, uint32_t bar, int c0, int c1, int c2) {
  asm volatile(
      "cp.async.bulk.tensor.3d.shared::cluster.global.mbarrier::complete_tx::bytes [%0], [%1, {%3, %4, %5}], [%2];" ::"r"(dst),
      "l"(reinterpret_cast<uint64_t>(m)), "r"(bar), "r"(c0), "r"(c1), "r"(c2)
      : "memory");
}
__device__ __forceinline__ void tma_store_2d(const CUtensorMap* m, uint32_t src, int c0, int c1) {
  asm volatile("cp.async.bulk.tensor.2d.global.shared::cta.bulk_group [%0, {%2, %3}], [%1];" ::"l"(
                   reinterpret_cast<uint64_t>(m)),
               "r"(src), "r"(c0), "r"(c1)
               : "memory");
}
__device__ __forceinline__ void tma_load_4d(uint32_t dst, const CUtensorMap* m, uint32_t bar, int c0, int tile) {
  asm volatile(
      "cp.async.bulk.tensor.4d.shared::cluster.global.mbarrier::complete_tx::bytes [%0], [%1, {%3, %4, %4, %5}], [%2];" ::"r"(dst),
      "l"(reinterpret_cast<uint64_t>(m)), "r"(bar), "r"(c0), "r"(0), "r"(2 * tile)
      : "memory");
}
__device__ __forceinline__ void tma_store_4d(const CUtensorMap* m, uint32_t src, int c0, int c2, int group) {
  asm volatile("cp.async.bulk.tensor.4d.global.shared::cta.bulk_group [%0, {%2, %3, %4, %5}], [%1];" ::"l"(
                   reinterpret_cast<uint64_t>(m)),
               "r"(src), "r"(c0), "r"(0), "r"(c2), "r"(group)
               : "memory");
}
__device__ __forceinline__ void bulk_load(uint32_t dst, const void* src, uint32_t bytes, uint32_t bar) {
  asm volatile("cp.async.bulk.shared::cluster.global.mbarrier::complete_tx::bytes [%0], [%1], %2, [%3];" ::"r"(dst),
               "l"(src), "r"(bytes), "r"(bar)
               : "memory");
}
__device__ __forceinline__ void tma_load_2d_mc(uint32_t dst, const CUtensorMap* m, uint32_t bar, int c0, int c1,
                                               uint16_t mask) {
  asm volatile(
      "cp.async.bulk.tensor.2d.shared::cluster.global.mbarrier::complete_tx::bytes.multicast::cluster [%0], [%1, {%3, "
      "%4}], [%2], %5;" ::"r"(dst),
      "l"(reinterpret_cast<uint64_t>(m)), "r"(bar), "r"(c0), "r"(c1), "h"(mask)
      : "memory");
}
__device__ __forceinline__ void mbar_arrive_cluster_if(uint32_t bar, uint32_t cta, bool pred) {
  asm volatile(
      "{\n.reg .b32 ra;\n.reg .pred p;\nsetp.ne.b32 p, %2, 0;\n"
      "mapa.shared::cluster.u32 ra, %0, %1;\n"
      "@p mbarrier.arrive.shared::cluster.b64 _, [ra];\n}\n" ::"r"(bar),
      "r"(cta), "r"((uint32_t)pred)
      : "memory");
}
__device__ __forceinline__ uint64_t policy_evict_first() {
  uint64_t pol;
  asm volatile("createpolicy.fractional.L2::evict_first.b64 %0, 1.0;" : "=l"(pol));
  return pol;
}
__device__ __forceinline__ void tma_load_2d_hint(uint32_t dst, const CUtensorMap* m, uint32_t bar, int c0, int c1,
                                                 uint64_t pol) {
  asm volatile(
      "cp.async.bulk.tensor.2d.shared::cluster.global.mbarrier::complete_tx::bytes.L2::cache_hint [%0], [%1, {%3, %4}], "
      "[%2], %5;" ::"r"(dst),
      "l"(reinterpret_cast<uint64_t>(m)), "r"(bar), "r"(c0), "r"(c1), "l"(pol)
      : "memory");
}
__device__ __forceinline__ void tma_load_3d_hint(uint32_t dst, const CUtensorMap* m, uint32_t bar, int c0, int c1,
                                                 int c2, uint64_t pol) {
  asm volatile(
      "cp.async.bulk.tensor.3d.shared::cluster.global.mbarrier::complete_tx::bytes.L2::cache_hint [%0], [%1, {%3, %4, "
      "%5}], [%2], %6;" ::"r"(dst),
      "l"(reinterpret_cast<uint64_t>(m)), "r"(bar), "r"(c0), "r"(c1), "r"(c2), "l"(pol)
      : "memory");
}
__device__ __forceinline__ void bulk_load_hint(uint32_t dst, const void* src, uint32_t bytes, uint32_t bar, uint64_t pol) {
  asm volatile(
      "cp.async.bulk.shared::cluster.global.mbarrier::complete_tx::bytes.L2::cache_hint [%0], [%1], %2, [%3], %4;" ::"r"(dst),
      "l"(src), "r"(bytes), "r"(bar), "l"(pol)
      : "memory");
}
__device__ __forceinline__ void cnt_signal_release(int which, uint32_t n) {
  asm volatile("red.release.gpu.global.add.u32 [%0], %1;" ::"l"(g_cnt + which * 32), "r"(n) : "memory");
}
__device__ __forceinline__ void cnt_wait(int which, uint32_t target) {
  uint32_t v, spins = 0;
  while (true) {
    asm volatile("ld.acquire.gpu.global.u32 %0, [%1];" : "=r"(v) : "l"(g_cnt + which * 32) : "memory");
    if (v >= target || ++spins > (1u << 18)) break;
    __nanosleep(64);
  }
  asm volatile("fence.proxy.async.global;" ::: "memory");
}
__device__ __forceinline__ void tma_store_commit() { asm volatile("cp.async.bulk.commit_group;" ::: "memory"); }
template <int N>
__device__ __forceinline__ void tma_store_wait_read() {
  asm volatile("cp.async.bulk.wait_group.read %0;" ::"n"(N) : "memory");
}
template <int N>
__device__ __forceinline__ void tma_store_wait() {
  asm volatile("cp.async.bulk.wait_group %0;" ::"n"(N) : "memory");
}
__device__ __forceinline__ void wgmma_fence() { asm volatile("wgmma.fence.sync.aligned;" ::: "memory"); }
__device__ __forceinline__ void wgmma_commit() { asm volatile("wgmma.commit_group.sync.aligned;" ::: "memory"); }
template <int N>
__device__ __forceinline__ void wgmma_wait() {
  asm volatile("wgmma.wait_group.sync.aligned %0;" ::"n"(N) : "memory");
}
template <int R>
__device__ __forceinline__ void reg_alloc() { asm volatile("setmaxnreg.inc.sync.aligned.u32 %0;" ::"n"(R)); }
template <int R>
__device__ __forceinline__ void reg_dealloc() { asm volatile("setmaxnreg.dec.sync.aligned.u32 %0;" ::"n"(R)); }

__device__ __forceinline__ void stmatrix_x4(uint32_t addr, uint32_t r0, uint32_t r1, uint32_t r2, uint32_t r3) {
  asm volatile("stmatrix.sync.aligned.m8n8.x4.shared.b16 [%0], {%1, %2, %3, %4};" ::"r"(addr), "r"(r0), "r"(r1),
               "r"(r2), "r"(r3)
               : "memory");
}
__device__ __forceinline__ uint32_t pack_bf16(float lo, float hi) {
  uint32_t r;
  asm("cvt.rn.bf16x2.f32 %0, %1, %2;" : "=r"(r) : "f"(hi), "f"(lo));
  return r;
}
__device__ __forceinline__ float bf16_round(float x) { return __bfloat162float(__float2bfloat16_rn(x)); }
__device__ __forceinline__ float bf_lo(uint32_t v) { return __uint_as_float(v << 16); }
__device__ __forceinline__ float bf_hi(uint32_t v) { return __uint_as_float(v & 0xffff0000u); }
__device__ __forceinline__ uint4 lds128(uint32_t a) {
  uint4 v;
  asm volatile("ld.shared.v4.u32 {%0, %1, %2, %3}, [%4];" : "=r"(v.x), "=r"(v.y), "=r"(v.z), "=r"(v.w) : "r"(a));
  return v;
}
__device__ __forceinline__ void sts128(uint32_t a, uint4 v) {
  asm volatile("st.shared.v4.u32 [%0], {%1, %2, %3, %4};" ::"r"(a), "r"(v.x), "r"(v.y), "r"(v.z), "r"(v.w) : "memory");
}
__device__ __forceinline__ uint32_t mul_bf2(uint32_t a, uint32_t b) {
  uint32_t r;
  asm("mul.rn.bf16x2 %0, %1, %2;" : "=r"(r) : "r"(a), "r"(b));
  return r;
}
__device__ __forceinline__ uint32_t add_bf2(uint32_t a, uint32_t b) {
  uint32_t r;
  asm("add.rn.bf16x2 %0, %1, %2;" : "=r"(r) : "r"(a), "r"(b));
  return r;
}
__device__ __forceinline__ float ex2(float x) {
  float y;
  asm("ex2.approx.ftz.f32 %0, %1;" : "=f"(y) : "f"(x));
  return y;
}
__device__ __forceinline__ float rcp(float x) {
  float y;
  asm("rcp.approx.ftz.f32 %0, %1;" : "=f"(y) : "f"(x));
  return y;
}
template <int N>
__device__ __forceinline__ void fence_regs(float (&r)[N]) {
#pragma unroll
  for (int i = 0; i < N; i++) asm volatile("" : "+f"(r[i])::"memory");
}

template <int N>
__device__ __forceinline__ void undef_regs(float (&r)[N]) {
#pragma unroll
  for (int i = 0; i < N; i++) asm volatile("" : "=f"(r[i]));
}
template <int N>
__device__ __forceinline__ void fence_regs_u(uint32_t (&r)[N]) {
#pragma unroll
  for (int i = 0; i < N; i++) asm volatile("" : "+r"(r[i])::"memory");
}

constexpr uint64_t DESC_SW128 = 1ull << 62;
__device__ __forceinline__ uint64_t make_desc(uint32_t addr, uint32_t lbo_bytes, uint32_t sbo_bytes, uint64_t swz) {
  return (uint64_t)((addr & 0x3FFFF) >> 4) | ((uint64_t)((lbo_bytes & 0x3FFFF) >> 4) << 16) |
         ((uint64_t)((sbo_bytes & 0x3FFFF) >> 4) << 32) | swz;
}

__device__ __forceinline__ uint64_t desc_add(uint64_t d, uint32_t off16) {
  return (d & 0xFFFFFFFF00000000ull) | (uint64_t)((uint32_t)d + off16);
}

__device__ __forceinline__ void wgmma_m64n256_ss_tb(float (&d)[128], uint64_t da, uint64_t db, int sd) {
  asm volatile(
    "{\n.reg .pred p;\nsetp.ne.b32 p, %130, 0;\n"
    "wgmma.mma_async.sync.aligned.m64n256k16.f32.bf16.bf16 "
    "{%0, %1, %2, %3, %4, %5, %6, %7, %8, %9, %10, %11, %12, %13, %14, %15, %16, %17, %18, %19, %20, %21, %22, %23, %24, %25, %26, %27, %28, %29, %30, %31, %32, %33, %34, %35, %36, %37, %38, %39, %40, %41, %42, %43, %44, %45, %46, %47, %48, %49, %50, %51, %52, %53, %54, %55, %56, %57, %58, %59, %60, %61, %62, %63, %64, %65, %66, %67, %68, %69, %70, %71, %72, %73, %74, %75, %76, %77, %78, %79, %80, %81, %82, %83, %84, %85, %86, %87, %88, %89, %90, %91, %92, %93, %94, %95, %96, %97, %98, %99, %100, %101, %102, %103, %104, %105, %106, %107, %108, %109, %110, %111, %112, %113, %114, %115, %116, %117, %118, %119, %120, %121, %122, %123, %124, %125, %126, %127}, %128, %129, p, 1, 1, 0, 1;\n}\n"
    : "+f"(d[0]), "+f"(d[1]), "+f"(d[2]), "+f"(d[3]), "+f"(d[4]), "+f"(d[5]), "+f"(d[6]), "+f"(d[7]), "+f"(d[8]), "+f"(d[9]), "+f"(d[10]), "+f"(d[11]), "+f"(d[12]), "+f"(d[13]), "+f"(d[14]), "+f"(d[15]), "+f"(d[16]), "+f"(d[17]), "+f"(d[18]), "+f"(d[19]), "+f"(d[20]), "+f"(d[21]), "+f"(d[22]), "+f"(d[23]), "+f"(d[24]), "+f"(d[25]), "+f"(d[26]), "+f"(d[27]), "+f"(d[28]), "+f"(d[29]), "+f"(d[30]), "+f"(d[31]), "+f"(d[32]), "+f"(d[33]), "+f"(d[34]), "+f"(d[35]), "+f"(d[36]), "+f"(d[37]), "+f"(d[38]), "+f"(d[39]), "+f"(d[40]), "+f"(d[41]), "+f"(d[42]), "+f"(d[43]), "+f"(d[44]), "+f"(d[45]), "+f"(d[46]), "+f"(d[47]), "+f"(d[48]), "+f"(d[49]), "+f"(d[50]), "+f"(d[51]), "+f"(d[52]), "+f"(d[53]), "+f"(d[54]), "+f"(d[55]), "+f"(d[56]), "+f"(d[57]), "+f"(d[58]), "+f"(d[59]), "+f"(d[60]), "+f"(d[61]), "+f"(d[62]), "+f"(d[63]), "+f"(d[64]), "+f"(d[65]), "+f"(d[66]), "+f"(d[67]), "+f"(d[68]), "+f"(d[69]), "+f"(d[70]), "+f"(d[71]), "+f"(d[72]), "+f"(d[73]), "+f"(d[74]), "+f"(d[75]), "+f"(d[76]), "+f"(d[77]), "+f"(d[78]), "+f"(d[79]), "+f"(d[80]), "+f"(d[81]), "+f"(d[82]), "+f"(d[83]), "+f"(d[84]), "+f"(d[85]), "+f"(d[86]), "+f"(d[87]), "+f"(d[88]), "+f"(d[89]), "+f"(d[90]), "+f"(d[91]), "+f"(d[92]), "+f"(d[93]), "+f"(d[94]), "+f"(d[95]), "+f"(d[96]), "+f"(d[97]), "+f"(d[98]), "+f"(d[99]), "+f"(d[100]), "+f"(d[101]), "+f"(d[102]), "+f"(d[103]), "+f"(d[104]), "+f"(d[105]), "+f"(d[106]), "+f"(d[107]), "+f"(d[108]), "+f"(d[109]), "+f"(d[110]), "+f"(d[111]), "+f"(d[112]), "+f"(d[113]), "+f"(d[114]), "+f"(d[115]), "+f"(d[116]), "+f"(d[117]), "+f"(d[118]), "+f"(d[119]), "+f"(d[120]), "+f"(d[121]), "+f"(d[122]), "+f"(d[123]), "+f"(d[124]), "+f"(d[125]), "+f"(d[126]), "+f"(d[127])
    : "l"(da), "l"(db), "r"(sd));
}

__device__ __forceinline__ void wgmma_m64n128_ss(float (&d)[64], uint64_t da, uint64_t db, int sd) {
  asm volatile(
    "{\n.reg .pred p;\nsetp.ne.b32 p, %66, 0;\n"
    "wgmma.mma_async.sync.aligned.m64n128k16.f32.bf16.bf16 "
    "{%0, %1, %2, %3, %4, %5, %6, %7, %8, %9, %10, %11, %12, %13, %14, %15, %16, %17, %18, %19, %20, %21, %22, %23, %24, %25, %26, %27, %28, %29, %30, %31, %32, %33, %34, %35, %36, %37, %38, %39, %40, %41, %42, %43, %44, %45, %46, %47, %48, %49, %50, %51, %52, %53, %54, %55, %56, %57, %58, %59, %60, %61, %62, %63}, %64, %65, p, 1, 1, 0, 0;\n}\n"
    : "+f"(d[0]), "+f"(d[1]), "+f"(d[2]), "+f"(d[3]), "+f"(d[4]), "+f"(d[5]), "+f"(d[6]), "+f"(d[7]), "+f"(d[8]), "+f"(d[9]), "+f"(d[10]), "+f"(d[11]), "+f"(d[12]), "+f"(d[13]), "+f"(d[14]), "+f"(d[15]), "+f"(d[16]), "+f"(d[17]), "+f"(d[18]), "+f"(d[19]), "+f"(d[20]), "+f"(d[21]), "+f"(d[22]), "+f"(d[23]), "+f"(d[24]), "+f"(d[25]), "+f"(d[26]), "+f"(d[27]), "+f"(d[28]), "+f"(d[29]), "+f"(d[30]), "+f"(d[31]), "+f"(d[32]), "+f"(d[33]), "+f"(d[34]), "+f"(d[35]), "+f"(d[36]), "+f"(d[37]), "+f"(d[38]), "+f"(d[39]), "+f"(d[40]), "+f"(d[41]), "+f"(d[42]), "+f"(d[43]), "+f"(d[44]), "+f"(d[45]), "+f"(d[46]), "+f"(d[47]), "+f"(d[48]), "+f"(d[49]), "+f"(d[50]), "+f"(d[51]), "+f"(d[52]), "+f"(d[53]), "+f"(d[54]), "+f"(d[55]), "+f"(d[56]), "+f"(d[57]), "+f"(d[58]), "+f"(d[59]), "+f"(d[60]), "+f"(d[61]), "+f"(d[62]), "+f"(d[63])
    : "l"(da), "l"(db), "r"(sd));
}

__device__ __forceinline__ void wgmma_m64n128_ss_tb(float (&d)[64], uint64_t da, uint64_t db, int sd) {
  asm volatile(
    "{\n.reg .pred p;\nsetp.ne.b32 p, %66, 0;\n"
    "wgmma.mma_async.sync.aligned.m64n128k16.f32.bf16.bf16 "
    "{%0, %1, %2, %3, %4, %5, %6, %7, %8, %9, %10, %11, %12, %13, %14, %15, %16, %17, %18, %19, %20, %21, %22, %23, %24, %25, %26, %27, %28, %29, %30, %31, %32, %33, %34, %35, %36, %37, %38, %39, %40, %41, %42, %43, %44, %45, %46, %47, %48, %49, %50, %51, %52, %53, %54, %55, %56, %57, %58, %59, %60, %61, %62, %63}, %64, %65, p, 1, 1, 0, 1;\n}\n"
    : "+f"(d[0]), "+f"(d[1]), "+f"(d[2]), "+f"(d[3]), "+f"(d[4]), "+f"(d[5]), "+f"(d[6]), "+f"(d[7]), "+f"(d[8]), "+f"(d[9]), "+f"(d[10]), "+f"(d[11]), "+f"(d[12]), "+f"(d[13]), "+f"(d[14]), "+f"(d[15]), "+f"(d[16]), "+f"(d[17]), "+f"(d[18]), "+f"(d[19]), "+f"(d[20]), "+f"(d[21]), "+f"(d[22]), "+f"(d[23]), "+f"(d[24]), "+f"(d[25]), "+f"(d[26]), "+f"(d[27]), "+f"(d[28]), "+f"(d[29]), "+f"(d[30]), "+f"(d[31]), "+f"(d[32]), "+f"(d[33]), "+f"(d[34]), "+f"(d[35]), "+f"(d[36]), "+f"(d[37]), "+f"(d[38]), "+f"(d[39]), "+f"(d[40]), "+f"(d[41]), "+f"(d[42]), "+f"(d[43]), "+f"(d[44]), "+f"(d[45]), "+f"(d[46]), "+f"(d[47]), "+f"(d[48]), "+f"(d[49]), "+f"(d[50]), "+f"(d[51]), "+f"(d[52]), "+f"(d[53]), "+f"(d[54]), "+f"(d[55]), "+f"(d[56]), "+f"(d[57]), "+f"(d[58]), "+f"(d[59]), "+f"(d[60]), "+f"(d[61]), "+f"(d[62]), "+f"(d[63])
    : "l"(da), "l"(db), "r"(sd));
}

__device__ __forceinline__ void wgmma_m64n128_rs_tb(float* d, uint32_t a0, uint32_t a1, uint32_t a2, uint32_t a3, uint64_t db, int sd) {
  asm volatile(
    "{\n.reg .pred p;\nsetp.ne.b32 p, %69, 0;\n"
    "wgmma.mma_async.sync.aligned.m64n128k16.f32.bf16.bf16 "
    "{%0, %1, %2, %3, %4, %5, %6, %7, %8, %9, %10, %11, %12, %13, %14, %15, %16, %17, %18, %19, %20, %21, %22, %23, %24, %25, %26, %27, %28, %29, %30, %31, %32, %33, %34, %35, %36, %37, %38, %39, %40, %41, %42, %43, %44, %45, %46, %47, %48, %49, %50, %51, %52, %53, %54, %55, %56, %57, %58, %59, %60, %61, %62, %63}, {%64, %65, %66, %67}, %68, p, 1, 1, 1;\n}\n"
    : "+f"(d[0]), "+f"(d[1]), "+f"(d[2]), "+f"(d[3]), "+f"(d[4]), "+f"(d[5]), "+f"(d[6]), "+f"(d[7]), "+f"(d[8]), "+f"(d[9]), "+f"(d[10]), "+f"(d[11]), "+f"(d[12]), "+f"(d[13]), "+f"(d[14]), "+f"(d[15]), "+f"(d[16]), "+f"(d[17]), "+f"(d[18]), "+f"(d[19]), "+f"(d[20]), "+f"(d[21]), "+f"(d[22]), "+f"(d[23]), "+f"(d[24]), "+f"(d[25]), "+f"(d[26]), "+f"(d[27]), "+f"(d[28]), "+f"(d[29]), "+f"(d[30]), "+f"(d[31]), "+f"(d[32]), "+f"(d[33]), "+f"(d[34]), "+f"(d[35]), "+f"(d[36]), "+f"(d[37]), "+f"(d[38]), "+f"(d[39]), "+f"(d[40]), "+f"(d[41]), "+f"(d[42]), "+f"(d[43]), "+f"(d[44]), "+f"(d[45]), "+f"(d[46]), "+f"(d[47]), "+f"(d[48]), "+f"(d[49]), "+f"(d[50]), "+f"(d[51]), "+f"(d[52]), "+f"(d[53]), "+f"(d[54]), "+f"(d[55]), "+f"(d[56]), "+f"(d[57]), "+f"(d[58]), "+f"(d[59]), "+f"(d[60]), "+f"(d[61]), "+f"(d[62]), "+f"(d[63])
    : "r"(a0), "r"(a1), "r"(a2), "r"(a3), "l"(db), "r"(sd));
}

__device__ __forceinline__ void wgmma_m64n64_rs(float (&d)[32], const uint32_t* a, uint64_t db, int sd) {
  asm volatile(
    "{\n.reg .pred p;\nsetp.ne.b32 p, %37, 0;\n"
    "wgmma.mma_async.sync.aligned.m64n64k16.f32.bf16.bf16 "
    "{%0, %1, %2, %3, %4, %5, %6, %7, %8, %9, %10, %11, %12, %13, %14, %15, %16, %17, %18, %19, %20, %21, %22, %23, %24, %25, %26, %27, %28, %29, %30, %31}, {%32, %33, %34, %35}, %36, p, 1, 1, 0;\n}\n"
    : "+f"(d[0]), "+f"(d[1]), "+f"(d[2]), "+f"(d[3]), "+f"(d[4]), "+f"(d[5]), "+f"(d[6]), "+f"(d[7]), "+f"(d[8]), "+f"(d[9]), "+f"(d[10]), "+f"(d[11]), "+f"(d[12]), "+f"(d[13]), "+f"(d[14]), "+f"(d[15]), "+f"(d[16]), "+f"(d[17]), "+f"(d[18]), "+f"(d[19]), "+f"(d[20]), "+f"(d[21]), "+f"(d[22]), "+f"(d[23]), "+f"(d[24]), "+f"(d[25]), "+f"(d[26]), "+f"(d[27]), "+f"(d[28]), "+f"(d[29]), "+f"(d[30]), "+f"(d[31])
    : "r"(a[0]), "r"(a[1]), "r"(a[2]), "r"(a[3]), "l"(db), "r"(sd));
}

constexpr int G_STAGES = 4;
constexpr int G_A_BYTES = 128 * 64 * 2;
constexpr int G_B_BYTES = 256 * 64 * 2;
constexpr int G_STAGE_BYTES = G_A_BYTES + G_B_BYTES;
constexpr int G_STG_OFF = G_STAGES * G_STAGE_BYTES;
constexpr int BAR_OFF = G_STG_OFF + 32768 + 2048;
constexpr int SMEM_BYTES = BAR_OFF + 1024;
constexpr int B_GFULL = 0, B_GEMPTY = 32, B_OY2 = 64, B_PFULL = 224;
constexpr int B_KFULL = 80, B_KEMPTY = 96, B_VFULL = 112, B_VEMPTY = 128, B_QFULL = 144, B_QEMPTY = 160,
              B_QPEER = 184;
constexpr int B_CFULL = 192;
constexpr int B_OFREE = 256, B_OFULL = 272, B_OEMPTY = 320, B_OY = 368;
constexpr int B_SFULL = 392, B_SFREE = 424, B_PEND = 456, B_SCMD = 512;

#define PHASE_PROLOGUE                                                                \
  uint32_t tid, rt_zero;                                                              \
  asm volatile("mov.u32 %0, %%tid.x;" : "=r"(tid));                                   \
  asm volatile("mov.u32 %0, %%nctaid.y;" : "=r"(rt_zero));                            \
  asm volatile("" : "+r"(smem0));                                                     \
  rt_zero = __shfl_sync(0xffffffffu, rt_zero >> 8, 0);   \
  const uint32_t sbase = __shfl_sync(0xffffffffu, smem0, 0);                          \
  const uint32_t bar = sbase + BAR_OFF;                                               \
  const int wg = __shfl_sync(0xffffffffu, tid >> 7, 0);                               \
  const int warp = (tid >> 5) & 3, lane = tid & 31, wtid = tid & 127;                 \
  (void)rt_zero; (void)bar; (void)warp; (void)lane; (void)wtid;

constexpr int A_ITEMS = 256;
enum { ST_BOX1, ST_BOX1P, ST_BOX2, ST_BOX2W, ST_BOX2L, ST_PEER };
__device__ __forceinline__ void st_post(uint32_t bar, int wg, int wtid, uint32_t n, int kind, int dst, uint32_t src,
                                        int c0, int c1, int sig) {
  if (wtid == 0) sts128(bar + B_SCMD + wg * 32 + (n & 1) * 16, make_uint4(kind + dst * 8 + sig * 32, src, c0, c1));
  fence_proxy_async();
  __syncwarp();
  mbar_arrive_if(bar + B_SFULL + wg * 16 + (n & 1) * 8, (wtid & 31) == 0);
}
__device__ __forceinline__ void st_wait(uint32_t bar, int wg, uint32_t n) {
  const uint32_t b = bar + B_SFREE + wg * 16 + (n & 1) * 8;
  if (!mbar_try(b, ~(n >> 1) & 1)) mbar_wait(b, ~(n >> 1) & 1);
}
__device__ __forceinline__ void note(uint32_t bar, uint32_t cnt) {
  asm volatile("red.release.cta.shared.add.u32 [%0], 1;" ::"r"(bar + B_PEND + 4 * cnt) : "memory");
}
__device__ __forceinline__ void store_agent(const CUtensorMap* maps, uint32_t bar, int wg, uint32_t n) {
  const uint32_t fr = bar + B_SFREE + wg * 16;
  mbar_arrive(fr + (~n & 1) * 8);
  if (n == 0) mbar_arrive(fr);
  for (;; n++) {
    mbar_wait_sleep(bar + B_SFULL + wg * 16 + (n & 1) * 8, (n >> 1) & 1);
    uint4 c = lds128(bar + B_SCMD + wg * 32 + (n & 1) * 16);
    const CUtensorMap* dst = maps + ((c.x >> 3) & 3);
    const int sig = (int)c.x >> 5;
    c.x &= 7;
    if (c.x == ST_PEER) {
      mbar_wait_sleep(bar + B_QPEER, c.z);
      asm volatile(
          "{\n.reg .b32 d, b;\nmapa.shared::cluster.u32 d, %0, %2;\nmapa.shared::cluster.u32 b, %1, %2;\n"
          "cp.async.bulk.shared::cluster.shared::cta.mbarrier::complete_tx::bytes [d], [%3], 8192, [b];\n"
          "cp.async.bulk.shared::cluster.shared::cta.mbarrier::complete_tx::bytes [d + 16384], [%3 + 8192], 8192, [b];\n}\n" ::"r"(
              bar - BAR_OFF + 32768 + wg * 8192),
          "r"(bar + B_QFULL + 8), "r"(~blockIdx.x & 1), "r"(c.y)
          : "memory");
      mbar_wait_sleep(bar + B_QFULL + 8, 0);
      mbar_arrive_cluster_if(fr + (n & 1) * 8, ~blockIdx.x & 1, true);
      continue;
    }
    tma_store_2d(dst, c.y, c.z, c.w);
    if (c.x >= ST_BOX2) tma_store_2d(dst, c.y + 8192, c.z + 64, c.w);
    tma_store_commit();
    tma_store_wait_read<0>();
    if (c.x != ST_BOX1P) mbar_arrive(fr + (n & 1) * 8);
    if (c.x == ST_BOX2L) mbar_arrive(bar + B_OFREE + 8 * wg);
    if (sig >= 0) {
      tma_store_wait<0>();
      asm volatile("fence.proxy.async.global;" ::: "memory");
      note(bar, sig);
      if (c.x == ST_BOX2W) cnt_wait(CNT_CTX, 2 * A_ITEMS);
      if (c.x == ST_BOX2L) note(bar, CNT_DONE);
      if (c.x == ST_BOX2L || c.x == ST_BOX1P) break;
    }
  }
}

struct Maps {
  const bf16 *shift_k, *x, *gate_w, *ssm_k, *ssm_D;
  uint8_t id[128][4];
  CUtensorMap a[2];
  CUtensorMap b[3];
  CUtensorMap c[3];
  CUtensorMap bk, bv;
  CUtensorMap k, v;
  CUtensorMap oa, ob, oc, ox;
  CUtensorMap y, y2;
};

constexpr int P_SLOT = 67 * 128, P_V = 35 * 128, P_TAPS = 2 * P_SLOT;
__device__ __forceinline__ void ldsm4t(uint32_t (&r)[4], uint32_t a) {
  asm volatile("ldmatrix.sync.aligned.m8n8.x4.trans.shared.b16 {%0, %1, %2, %3}, [%4];"
               : "=r"(r[0]), "=r"(r[1]), "=r"(r[2]), "=r"(r[3])
               : "r"(a));
}
__device__ __forceinline__ uint32_t fma_bf2(uint32_t a, uint32_t b, uint32_t c) {
  uint32_t r;
  asm("fma.rn.bf16x2 %0, %1, %2, %3;" : "=r"(r) : "r"(a), "r"(b), "r"(c));
  return r;
}
__device__ __forceinline__ void agent_warp(const Maps& maps, uint32_t smem0) {
  mbar_wait_sleep(smem0 + BAR_OFF + B_GFULL + 8 * (G_STAGES - 1), 0);
#pragma unroll 1
  for (int j = 0; j < 7; j++) {
    PHASE_PROLOGUE
    const int w = __shfl_sync(0xffffffffu, warp, 0), i = j >> 1;
    const uint32_t pb = bar + B_PFULL + w * 16, sw = sbase + G_STG_OFF + w * (P_TAPS + 512);
    const int d0 = (blockIdx.x >> 4) * 128 + (j < 3 ? 64 : 0), t0 = (blockIdx.x & 15) * 128 + w * 64;
    const bool work = (0x56 >> j) & 1;
    GA(80 + 2 * j)
    if (work) mbar_wait_sleep(pb + (i & 1) * 8, i >> 1);
    GA(81 + 2 * j)
    if (((0x2b >> j) & 1) && elect_one()) {
      const uint32_t l = ((j + 1) >> 1) & 1, b = pb + l * 8, dst = sw + l * P_SLOT;
      mbar_expect_tx(b, work ? P_SLOT : P_SLOT + 512);
      const uint64_t pol = policy_evict_first();
      tma_load_2d_hint(dst, &maps.bk, b, d0, t0 + 32 * l - 3, pol);
      tma_load_2d_hint(dst + P_V, &maps.bv, b, d0, t0 + 32 * l, pol);
      if (!work) bulk_load(sbase + G_STG_OFF + P_TAPS, maps.shift_k + d0 * 4, 512, b);
    }
    if (!work) continue;
    const uint32_t so = sw + (i & 1) * P_SLOT;
    uint32_t ak[4];
#pragma unroll
    for (int r = 0; r < 4; r++) {
      const uint32_t a = so / 128 + r + 4 * (lane & 6) + (((((lane >> 2) ^ lane) & 6) + (lane & 1)) ^ 7);
      ak[r] = a * 128 + (a & 7) * 16;
    }
    bf16* dst = g_kvT + (size_t)(d0 + (lane >> 2)) * S_LEN + t0 + ((lane & 3) + 4 * (i & 1)) * 8;
#pragma unroll 1
    for (int cg = 0; cg < 128; cg += 16) {
      uint32_t t01, t23, k[4][4], v[4];
      asm volatile("ld.shared.v2.u32 {%0, %1}, [%2];"
                   : "=r"(t01), "=r"(t23)
                   : "r"(sbase + G_STG_OFF + P_TAPS + cg * 4 + (lane >> 2) * 8));
#pragma unroll
      for (int r = 0; r < 4; r++) ldsm4t(k[r], ak[r] ^ cg);
      ldsm4t(v, (ak[3] ^ cg) + 4096);
      const uint32_t w0 = __byte_perm(t01, 0, 0x1010), w1 = __byte_perm(t01, 0, 0x3232);
      const uint32_t w2 = __byte_perm(t23, 0, 0x1010), w3 = __byte_perm(t23, 0, 0x3232);
#pragma unroll
      for (int j = 0; j < 4; j++)
        v[j] = mul_bf2(fma_bf2(k[3][j], w0, fma_bf2(k[2][j], w1, fma_bf2(k[1][j], w2, mul_bf2(k[0][j], w3)))), v[j]);
      const bool s1 = lane & 1, s2 = lane & 2;
      const uint32_t a0 = s1 ? v[1] : v[0], a1 = s1 ? v[0] : v[1], a2 = s1 ? v[3] : v[2], a3 = s1 ? v[2] : v[3];
      *reinterpret_cast<uint4*>(dst) = make_uint4(s2 ? a2 : a0, s2 ? a3 : a1, s2 ? a0 : a2, s2 ? a1 : a3);
      dst += 8 * S_LEN;
    }
    fence_proxy_async();
    __syncwarp();
    if (j == 1) continue;
    GA(94)
    if (elect_one()) {
      note(bar, CNT_PREP + (j > 2));
      store_agent(maps.c, bar, w, (0x130800 >> (4 * j - 8)) & 255);
    }
    __syncwarp();
  }
}

__device__ __forceinline__ void qkv_tile(const Maps& maps, int it, int& m_tile, int& group) {
  const int b = maps.id[blockIdx.x][it >> 1];
  m_tile = b & 15;
  group = b >> 4;
}

constexpr int G_NTILES = 3;
__device__ __forceinline__ void qkv_producer(const Maps& maps, uint32_t sbase, int pass, bool first) {
  const uint32_t bar = sbase + BAR_OFF;
  uint32_t stage = 0, phase = pass;
#pragma unroll 1
  for (int it = 0; it < (first ? 1 : G_NTILES); it++) {
    int m_tile, group;
    qkv_tile(maps, it, m_tile, group);
    const CUtensorMap* ma = &maps.a[it >> 1];
    const CUtensorMap* mb = &maps.b[it];
    const int nk = first ? G_STAGES : it == 2 ? 16 : 8;
#pragma unroll 1
    for (int kt = (it == 0 && !first && !pass) ? G_STAGES : 0; kt < nk; kt++) {
      if (pass && it == 0 && kt < G_STAGES) {
        constexpr uint32_t LASTB = (B_QEMPTY + 8) | (B_KEMPTY << 8) | ((B_VEMPTY + 8) << 16) | (B_VEMPTY << 24);
        mbar_wait_sleep(bar + ((LASTB >> (8 * kt)) & 255), kt == 2);
      }
      if (!first) mbar_wait_sleep(bar + B_GEMPTY + 8 * stage, phase);
      const uint32_t fb = bar + B_GFULL + 8 * stage;
      const uint32_t sa = sbase + stage * G_STAGE_BYTES;
      mbar_expect_tx(fb, G_STAGE_BYTES);
      tma_load_2d(sa, ma, fb, kt * 64, m_tile * 128);
      tma_load_3d(sa + G_A_BYTES, mb, fb, 0, kt * 64, group * 8 + pass * 4);
      if (++stage == G_STAGES) { stage = 0; phase ^= 1; }
      {
        const int b = maps.id[blockIdx.x][1];
        if (it == 1 && kt == (b & 7))
          asm volatile("cp.async.bulk.prefetch.tensor.3d.L2.global.tile [%0, {%1, %2, %3}];" ::"l"(&maps.b[2]), "r"(0),
                       "r"((b & 15) * 64), "r"((b >> 4) * 8 + pass * 4)
                       : "memory");
      }
      if (pass && it == 0 && kt == G_STAGES - 1) {
#pragma unroll 1
        for (int i = 0; i < 12; i++) {
          asm volatile("mbarrier.inval.shared::cta.b64 [%0];" ::"r"(bar + B_KFULL + 8 * i) : "memory");
          mbar_init(bar + B_KFULL + 8 * i, 1 + ((i >> 1) & 1));
        }
        fence_proxy_async();
      }
    }
  }
}

__device__ __noinline__ void publisher(uint32_t bar, int lane, uint32_t nsrc) {
  uint32_t done = 0;
  CLK_DECL
#pragma unroll 1
  for (uint32_t spins = 0; done < nsrc && spins < (1u << 20); spins++) {
    CLK_SAMPLE
    uint32_t v = 0;
    if (lane < CNT_N)
      asm volatile("atom.acquire.cta.shared.exch.b32 %0, [%1], 0;" : "=r"(v) : "r"(bar + B_PEND + 4 * lane) : "memory");
    done += __shfl_sync(0xffffffffu, v, CNT_DONE);
    if (lane == CNT_DONE) v = 0;
    if (done == nsrc && lane < CNT_DONE) {
      uint32_t w;
      asm volatile("atom.acquire.cta.shared.exch.b32 %0, [%1], 0;" : "=r"(w) : "r"(bar + B_PEND + 4 * lane) : "memory");
      v += w;
    }
    if (v && lane == 0) { TD(0) }
    if (v) cnt_signal_release(lane, v);
    if (v && lane == 0) { TD(1) }
    if (!__any_sync(0xffffffffu, v != 0)) __nanosleep(200);
  }
  CLK_END
  __threadfence();
  __syncwarp();
}

__device__ __forceinline__ void gate_rows(const Maps& maps, uint32_t sbase, int w48, int w12, int lane) {
  const uint32_t buf = sbase + w12 * 16384, gb = sbase + BAR_OFF + 768 + w12 * 16;
  if (lane == 0) {
    mbar_init(gb, 1);
    mbar_init(gb + 8, 1);
    fence_barrier_init();
    for (int i = 0; i < 2; i++) {
      mbar_expect_tx(gb + 8 * i, 8192);
      bulk_load(buf + i * 8192, maps.x + (size_t)(w48 + 48 * i) * 4 * DM, 8192, gb + 8 * i);
    }
  }
  __syncwarp();
  uint4 wv[4];
#pragma unroll
  for (int i = 0; i < 4; i++) wv[i] = __ldg(reinterpret_cast<const uint4*>(maps.gate_w + (i * 32 + lane) * 8));
  int it = 0;
#pragma unroll 1
  for (int row = w48 * 4; row < S_LEN; row += 48 * 4, it++) {
    mbar_wait(gb + 8 * (it & 1), (it >> 1) & 1);
    uint4 xv[4][4];
#pragma unroll
    for (int r = 0; r < 4; r++)
#pragma unroll
      for (int i = 0; i < 4; i++) xv[r][i] = lds128(buf + (it & 1) * 8192 + r * 2048 + (i * 32 + lane) * 16);
    float d[2][4];
#pragma unroll
    for (int pr = 0; pr < 2; pr++) {
      d[pr][0] = d[pr][1] = d[pr][2] = d[pr][3] = 0.f;
      auto acc = [&](uint32_t a0, uint32_t a2, uint32_t b0, uint32_t b2, uint32_t w0, uint32_t w2) {
        asm volatile(
            "mma.sync.aligned.m16n8k16.row.col.f32.bf16.bf16.f32 {%0, %1, %2, %3}, {%4, %5, %6, %7}, {%8, %8}, "
            "{%0, %1, %2, %3};"
            : "+f"(d[pr][0]), "+f"(d[pr][1]), "+f"(d[pr][2]), "+f"(d[pr][3])
            : "r"(mul_bf2(a0, w0)), "r"(mul_bf2(b0, w0)), "r"(mul_bf2(a2, w2)), "r"(mul_bf2(b2, w2)), "r"(0x3f803f80u));
      };
#pragma unroll
      for (int i = 0; i < 4; i++) {
        acc(xv[2 * pr][i].x, xv[2 * pr][i].y, xv[2 * pr + 1][i].x, xv[2 * pr + 1][i].y, wv[i].x, wv[i].y);
        acc(xv[2 * pr][i].z, xv[2 * pr][i].w, xv[2 * pr + 1][i].z, xv[2 * pr + 1][i].w, wv[i].z, wv[i].w);
      }
    }
    float sum = (lane & 2) ? ((lane & 1) ? d[1][2] : d[1][0]) : ((lane & 1) ? d[0][2] : d[0][0]);
#pragma unroll
    for (int off = 16; off >= 4; off >>= 1) sum += __shfl_xor_sync(0xffffffffu, sum, off);
    if (lane < 4) g_gate[row + lane] = bf16_round(rcp(1.0f + __expf(-bf16_round(sum))));
    if (lane == 0 && row + 2 * 48 * 4 < S_LEN) {
      mbar_expect_tx(gb + 8 * (it & 1), 8192);
      bulk_load(buf + (it & 1) * 8192, maps.x + (size_t)(row + 2 * 48 * 4) * DM, 8192, gb + 8 * (it & 1));
    }
  }
}

constexpr float Q_SCALE = 0.08838834764831845f * 1.4426950408889634f;
__device__ __forceinline__ uint32_t qkv_consumer(const Maps& maps, uint32_t smem0, uint32_t sn, uint32_t (&p)[32]) {
  PHASE_PROLOGUE
  float acc[128];
#pragma unroll
  for (int i = 0; i < 128; i++) asm volatile("mov.b32 %0, 0;" : "=f"(acc[i]));
  uint32_t stage = 0, phase = 0, prev_stage = 0;
  const uint32_t stg = sbase + G_STG_OFF + wg * 18432;
  const int st_row = warp * 16 + (lane & 7) + ((lane >> 3) & 1) * 8;
  const int st_cb = lane >> 4;
  uint32_t pend[32];
  int m_tile, group;
  qkv_tile(maps, 0, m_tile, group);
  auto put_box = [&](uint32_t buf, const uint32_t* v) {
#pragma unroll
    for (int jp = 0; jp < 4; jp++) {
      const int chunk = jp * 2 + st_cb;
      const uint32_t addr = buf + st_row * 128 + ((chunk ^ (st_row & 7)) << 4);
      stmatrix_x4(addr, v[jp * 4], v[jp * 4 + 1], v[jp * 4 + 2], v[jp * 4 + 3]);
    }
  };
  GT(gti++)
#pragma unroll
  for (int i = 0; i < 32; i++) pend[i] = 0;
#pragma unroll 1
  for (int it = 0;; it++) {
    const int nk = it == 2 ? 16 : 8;
#pragma unroll 1
    for (int kt = 0; kt < nk; kt++) {
      mbar_wait((bar + B_GFULL) + 8 * stage, phase);
      GT(gti++)
      const uint64_t da0 = make_desc(sbase + stage * G_STAGE_BYTES + wg * 8192, 16, 1024, DESC_SW128);
      const uint64_t db0 = make_desc(sbase + stage * G_STAGE_BYTES + G_A_BYTES, 8192, 1024, DESC_SW128);
      asm volatile("{\n.reg .pred p;\nsetp.ne.u32 p, %0, 0;\n@p bar.sync 3, 256;\n}\n" ::"r"((uint32_t)(wg && kt == nk - 1))
                   : "memory");
      wgmma_fence();
#pragma unroll
      for (int kk = 0; kk < 4; kk++) {
        wgmma_m64n256_ss_tb(acc, desc_add(da0, kk * 2), desc_add(db0, kk * 128), (kt | kk) != 0);
      }
      wgmma_commit();
      asm volatile("{\n.reg .pred p;\nsetp.ne.u32 p, %0, 0;\n@p bar.arrive 3, 256;\n}\n" ::"r"((uint32_t)(!wg && kt == nk - 1))
                   : "memory");
      const uint32_t when = it == 0 ? 0 : wg ? 0xAA : 0x55;
      if ((when >> kt) & 1) {
        const int c = kt >> 1;
        st_wait(bar, wg, sn - (it + c == 1 ? 1 : 2));
        const uint32_t buf = stg + (c & 1) * 8192;
        switch (c) {
          case 0: put_box(buf, p); break;
          case 1: put_box(buf, p + 16); break;
          case 2: put_box(buf, pend); break;
          default: put_box(buf, pend + 16); break;
        }
        st_post(bar, wg, wtid, sn, it + c == 5 ? ST_BOX1P : ST_BOX1, it - 1, buf, group * 256 + c * 64,
                m_tile * 128 + wg * 64, c == 3 ? CNT_KV + (sn > 8) : -1);
        sn++;
      }
      wgmma_wait<1>();
      mbar_arrive_if((bar + B_GEMPTY) + 8 * prev_stage, wtid == 32 && kt > 0);
      prev_stage = stage;
      if (++stage == G_STAGES) { stage = 0; phase ^= 1; }
    }
    wgmma_wait<0>();
    fence_regs(acc);
    GT(gti++)
    mbar_arrive_if((bar + B_GEMPTY) + 8 * prev_stage, wtid == 32);
    if (it == G_NTILES - 1) break;
#pragma unroll
    for (int j = 0; j < 32; j++) {
      p[j] = pack_bf16(acc[2 * j], acc[2 * j + 1]);
      pend[j] = pack_bf16(acc[64 + 2 * j], acc[64 + 2 * j + 1]);
    }
  }
  ST(19)
  st_wait(bar, wg, sn - 1);
  mbar_wait(bar + B_GEMPTY, 1);
#pragma unroll
  for (int j = 0; j < 32; j++) pend[j] = pack_bf16(acc[2 * j] * Q_SCALE, acc[2 * j + 1] * Q_SCALE);
  put_box(sbase + wg * 8192, pend);
  put_box(sbase + 16384 + wg * 8192, pend + 16);
#pragma unroll
  for (int j = 0; j < 32; j++) p[j] = pack_bf16(acc[64 + 2 * j] * Q_SCALE, acc[65 + 2 * j] * Q_SCALE);
  put_box(stg, p);
  put_box(stg + 8192, p + 16);
  st_post(bar, wg, wtid, sn, ST_PEER, 0, stg, sn >> 4, 0, 0);
  sn++;
  GT(gti++)
  return sn;
}

constexpr int A_TILE = 128 * 128 * 2;
constexpr int A_Q_OFF = 0;
constexpr int A_K_OFF = 2 * A_TILE;
constexpr int A_V_OFF = 4 * A_TILE;
constexpr int A_O_OFF = 6 * A_TILE;

constexpr uint32_t A_STEPS = 17;
__device__ __forceinline__ int item_m(uint32_t it) { return it & 15; }
__device__ __forceinline__ int item_h(uint32_t it) { return it >> 4; }

constexpr int C_H0 = 16, C_U = C_H0 + 4096 + 112, C_SLOT = C_U + 4096;
constexpr int C_H1 = 2 * C_SLOT + 80;
constexpr int C_X_OFF = C_H1 + 4096 + 48;

__device__ __forceinline__ uint32_t item_of(const Maps& maps, uint32_t r) {
  const uint32_t b = maps.id[blockIdx.x & 127][1];
  return (b >> 4) * 64 + r * 16 + ((b ^ ((r & 1) * 15)) & 15);
}

constexpr uint32_t C_SIDE = 48;
__device__ __forceinline__ uint32_t conv_first(const Maps& maps) {
  const uint32_t b = maps.id[blockIdx.x & 127][1];
  return (b >> 4) * 128 + (b & 15);
}

__device__ __forceinline__ void conv_consumer(const Maps& maps, uint32_t smem0, uint32_t first, uint32_t step,
                                              uint32_t end) {
  PHASE_PROLOGUE
  const uint32_t full = bar + B_CFULL + wg * 16;
  const uint32_t ca = sbase + (wg ? A_V_OFF + A_TILE : A_Q_OFF);
  const int w4 = __shfl_sync(0xffffffffu, warp, 0);
  auto fetch = [&](uint32_t c, uint32_t slot) {
    if (w4 == 2 && c < end) {
      if (elect_one()) {
        const uint32_t sb = ca + slot * C_SLOT, fb = full + 8 * slot;
        const uint64_t pol = policy_evict_first();
        mbar_expect_tx(fb, 2 * 4096);
        bulk_load_hint(sb + C_H0, maps.ssm_k + (size_t)c * S_LEN, 4096, fb, pol);
        bulk_load_hint(sb + C_U, g_kvT + (size_t)c * S_LEN, 4096, fb, pol);
      }
    }
  };
  auto shift_h = [&](uint32_t so) {
    const uint32_t a = ca + so + C_H0 + wtid * 16;
#pragma unroll
    for (int i = 0; i < 2; i++) {
      uint32_t p;
      const uint4 v = lds128(a + i * 2048);
      asm volatile("ld.shared.u32 %0, [%1];" : "=r"(p) : "r"(a + i * 2048 - 4));
      sts128(ca + C_H1 + wtid * 16 + i * 2048, make_uint4(__byte_perm(p, v.x, 0x5432), __byte_perm(v.x, v.y, 0x5432),
                                                      __byte_perm(v.y, v.z, 0x5432), __byte_perm(v.z, v.w, 0x5432)));
    }
  };
  if (wtid == 96 && wg) { TD(15) }
  fetch(first, 0);
  if (wtid < 17)
    sts128(ca + (wtid >> 3) * C_SLOT + (wtid & 7 ? 4096 + (wtid & 7) * 16 : (wtid & 16) * 4), make_uint4(0, 0, 0, 0));
  fence_proxy_async();
  const uint32_t ha = ca + ((lane & 4) ? C_H1 : C_H0) + 4 * ((lane & 3) - (lane >> 3)) + w4 * 256;
  const uint32_t ua = ca + C_U + w4 * 256 + (lane >> 4) * 1024 + (lane & 15) * 16;
  const uint32_t xa = ca + C_X_OFF + lane * 8, xw = xa + w4 * 3072;
  uint32_t xg[3];
#pragma unroll
  for (int k = 0; k < 3; k++) {
    const int w = (w4 + k + 1) & 3;
    xg[k] = xa + (w * 12 + w4 - w - (w < w4 ? 1 : 0)) * 256;
  }
  const bool pp = step != 16;
  uint32_t h[2][16];
  const uint32_t hs = (lane & 4) ? 0 : C_SLOT;
  auto load_h = [&](uint32_t so, int a) {
#pragma unroll
    for (int i = 0; i < 16; i++)
      asm volatile("ld.shared.u32 %0, [%1];"
                   : "=r"(h[a & 1][i])
                   : "r"(ha + so + 1024 * a + 32 * (i >> 2) + (i & 1) * 128 + (~i & 2) * 8));
  };
  mbar_wait(full, 0);
  named_bar_sync(1 + wg, 128);
  shift_h(0);
  named_bar_sync(1 + wg, 128);
  fetch(first + step, 1);
  load_h(0, 0);
  load_h(0, 1);
  mbar_wait(bar + B_OFREE, 0);
  mbar_wait(bar + B_OFREE + 8, 0);
  uint32_t n = 0, ch = first;
  for (; ch < end; n++, ch += step) {
    CT(0)
    const uint32_t so = (n & 1) * C_SLOT, ho = (n & 1) * hs;
    uint32_t db = (uint32_t)make_desc(ca + so + C_U - 16, 16, 0, 0);
    asm volatile("" : "+r"(db));
    uint32_t dsk = __ldg(reinterpret_cast<const unsigned short*>(maps.ssm_D) + (ch | (lane & rt_zero)));
    float d[4][32], own[16];
    auto mma = [&](int a) {
      wgmma_fence();
#pragma unroll
      for (int c = a; c < 4; c++)
#pragma unroll
        for (int b = 0; b < 4; b++)
          wgmma_m64n64_rs(d[c], &h[a & 1][4 * b], (8ull << 32) | (db + 64 * (c - a) - 2 * b), (a | b) != 0);
      wgmma_commit();
    };
    auto put = [&](int c) {
      fence_regs(d[c]);
#pragma unroll
      for (int e = 0; e < 2; e++) {
        if (c == 0) asm volatile("mov.b32 %0, %1;" : "=f"(own[e]) : "f"(d[c][e]));
        else own[4 * c + e] += d[c][e];
        own[4 * c + 2 + e] = d[c][4 + e] + d[c][2 + e];
        if (c < 3) asm volatile("mov.b32 %0, %1;" : "=f"(own[4 * c + 4 + e]) : "f"(d[c][30 + e]));
      }
#pragma unroll
      for (int j = 1; j < 4; j++)
        asm volatile("{\n.reg .pred p;\nsetp.lt.s32 p, %3, 4;\n@p st.shared.v2.u32 [%0], {%1, %2};\n}\n" ::"r"(
                         xw + (3 * c + j - 1) * 256),
                     "r"(pack_bf16(d[c][8 * j] + d[c][8 * j - 2], d[c][8 * j + 1] + d[c][8 * j - 1])),
                     "r"(pack_bf16(d[c][8 * j + 4] + d[c][8 * j + 2], d[c][8 * j + 5] + d[c][8 * j + 3])),
                     "r"(c < 3 ? 0 : w4 + j)
                     : "memory");
    };
    named_bar_sync(pp ? 4 + wg : 1 + wg, pp ? 256 : 128);
    CT(1)
    mma(0);
    mma(1);
    wgmma_wait<1>();
    load_h(ho, 2);
    put(0);
    mma(2);
    CT(2)
    wgmma_wait<1>();
    load_h(ho, 3);
    put(1);
    mma(3);
    asm volatile("{\n.reg .pred p;\nsetp.ne.u32 p, %1, 0;\n@p bar.arrive %0, 256;\n}\n" ::"r"(5 - wg), "r"((uint32_t)pp) : "memory");
    CT(3)
    uint32_t sk[8];
    asm volatile("ldmatrix.sync.aligned.m8n8.x4.trans.shared.b16 {%0, %1, %2, %3}, [%4];"
                 : "=r"(sk[0]), "=r"(sk[1]), "=r"(sk[2]), "=r"(sk[3])
                 : "r"(ua + so));
    asm volatile("ldmatrix.sync.aligned.m8n8.x4.trans.shared.b16 {%0, %1, %2, %3}, [%4];"
                 : "=r"(sk[4]), "=r"(sk[5]), "=r"(sk[6]), "=r"(sk[7])
                 : "r"(ua + so + 2048));
    mbar_wait(full + 8 * (~n & 1), (((n + 1) >> 1) & 1) ^ (ch + step < end ? 0 : 1));
    named_bar_sync(1 + wg, 128);
    shift_h(C_SLOT - so);
    wgmma_wait<1>();
    put(2);
    uint32_t dep = 0;
#pragma unroll
    for (int i = 0; i < 8; i++) dep |= sk[i] = mul_bf2(sk[i], dsk | (dsk << 16));
    CT(4)
    wgmma_wait<0>();
    put(3);
    named_bar_sync((1 + wg) | (dep & rt_zero), 128);
    CT(5)
    fetch(ch + 2 * step, n & 1);
    if (wtid == 96 && n) note(bar, CNT_Y2 + (((ch - step) & 127) >= 112));
    uint2 q[12];
#pragma unroll
    for (int i = 0; i < 12; i++) {
      if (i >= 3) {
        asm volatile("ld.shared.v2.u32 {%0, %1}, [%2];" : "=r"(q[i].x), "=r"(q[i].y) : "r"(xg[i % 3] + (i / 3) * 768));
      } else {
        q[i] = make_uint2(0, 0);
        asm volatile("{\n.reg .pred p;\nsetp.gt.s32 p, %3, 2;\n@p ld.shared.v2.u32 {%0, %1}, [%2];\n}\n"
                     : "+r"(q[i].x), "+r"(q[i].y)
                     : "r"(xg[i]), "r"(w4 + i));
      }
    }
    load_h(hs - ho, 0);
    load_h(hs - ho, 1);
    CT(6)
    uint32_t* dst = reinterpret_cast<uint32_t*>(g_y2T + (size_t)ch * S_LEN) + 64 * w4 + (lane ^ 28);
#pragma unroll
    for (int f = 0; f < 4; f++) {
#pragma unroll
      for (int k = 0; k < 3; k++) {
        own[4 * f] += bf_lo(q[3 * f + k].x);
        own[4 * f + 1] += bf_hi(q[3 * f + k].x);
        own[4 * f + 2] += bf_lo(q[3 * f + k].y);
        own[4 * f + 3] += bf_hi(q[3 * f + k].y);
      }
#pragma unroll
      for (int i = 0; i < 2; i++) {
        dst[256 * f + 32 * i] = add_bf2(pack_bf16(own[4 * f + 2 * i], own[4 * f + 2 * i + 1]), sk[2 * f + i]);
      }
    }
    CT(7)
  }
  named_bar_sync(1 + wg, 128);
  if (wtid == 96 && wg) { TD(8) }
  if (wtid == 96) cnt_signal_release(CNT_Y2 + (((ch - step) & 127) >= 112), 1);
  if (wtid == 64) note(bar, CNT_DONE);
  if (wtid == 96 && wg) { TD(9) }
}

__device__ __forceinline__ void attn_producer(const Maps& maps, uint32_t sbase, int pass, bool dry) {
  const uint32_t bar = sbase + BAR_OFF;
  const uint32_t q_full = bar + B_QFULL, q_empty = bar + B_QEMPTY;
  const uint32_t k_full = bar + B_KFULL, k_empty = bar + B_KEMPTY, v_full = bar + B_VFULL, v_empty = bar + B_VEMPTY;
  int ndrained = 0;
  auto wait = [&](uint32_t b, uint32_t par) {
    if (!dry) mbar_wait_sleep(b, par);
  };
  auto drained = [&](int upto) {
#pragma unroll 1
    for (; ndrained <= upto; ndrained++) wait(bar + B_GEMPTY + 8 * ndrained, 1);
  };
  uint32_t st = 0, ph = 1, vs = 0, vp = 1;
  int pend_j = -1, pend_h = 0;
  PT_DECL
  cnt_wait(CNT_KV + pass, dry ? 0 : 512);
  drained(1);
  if (!dry) {
    mbar_arrive(q_full);
    mbar_expect_tx(q_full + 8, A_TILE);
  }
  mbar_arrive_cluster_if(bar + B_QPEER, ~blockIdx.x & 1, !dry);
#pragma unroll 1
  for (int round = dry; round < 3; round++) {
    const uint32_t item = item_of(maps, round);
    const int m = round == 2 ? -1 : dry ? 0 : item_m(item), h = (item >> 6) * 4 + round * 2;
    const int tpost = m >= 3 ? m - 1 : m;
#pragma unroll 1
    for (int t = m < 0 ? -1 : 0; t <= m; t++) {
      const int j = (t < m && round) ? m - 1 - t : t;
      if (t >= 0) {
        drained(1 + st);
        wait(k_empty + 8 * st, ph);
        if (!dry) {
          PT
          mbar_expect_tx(k_full + 8 * st, A_TILE);
          tma_load_3d(sbase + A_K_OFF + st * A_TILE, &maps.k, k_full + 8 * st, 0, j * 128, h);
        }
        if (++st == 2) { st = 0; ph ^= 1; }
      }
      if (pend_j >= 0) {
        drained(3);
        wait(v_empty + 8 * vs, vp);
        if (!dry) {
          mbar_expect_tx(v_full + 8 * vs, A_TILE);
          tma_load_3d(sbase + A_V_OFF + (vs ^ 1) * A_TILE, &maps.v, v_full + 8 * vs, 0, pend_j * 128, pend_h);
        }
        if (++vs == 2) { vs = 0; vp ^= 1; }
      }
      pend_j = j;
      pend_h = h;
      if (t == tpost && round == 1) {
        if (pass) {
          cnt_wait(CNT_PREP + 1, dry ? 0 : 516);
          cnt_wait(CNT_CTX, dry ? 0 : 2 * A_ITEMS);
          asm volatile("cp.async.bulk.prefetch.L2.global [%0], 4096;" ::"l"(maps.ssm_k + (size_t)conv_first(maps) * S_LEN));
          if (!dry)
            asm volatile("cp.async.bulk.prefetch.L2.global [%0], 4096;" ::"l"(g_kvT + (size_t)conv_first(maps) * S_LEN));
        }
        wait(q_empty, 0);
        if (!dry) mbar_arrive(q_full);
      }
    }
  }
}

__device__ __forceinline__ uint32_t attn_consumer(const Maps& maps, uint32_t smem0, uint32_t sn, uint32_t (&p)[32]) {
  PHASE_PROLOGUE
  float s[64], o[64], e[32];
  const uint32_t q_full = bar + B_QFULL, q_empty = bar + B_QEMPTY;
  const uint32_t k_full = bar + B_KFULL, k_empty = bar + B_KEMPTY, v_full = bar + B_VFULL;
  uint32_t dep = 0;
  constexpr int MIDJ = 5;
  float l0 = 0.f, l1 = 0.f, b0 = 0.f, b1 = 0.f;
  const int sched_own = 4 + wg, sched_other = 5 - wg;

  const uint32_t qd0 = (uint32_t)make_desc(sbase + A_Q_OFF + wg * 8192, 16, 0, 0);
  const uint32_t kd0 = (uint32_t)make_desc(sbase + A_K_OFF, 16, 0, 0);
  const uint32_t vd0 = (uint32_t)make_desc(sbase + A_V_OFF, 16384, 0, 0);
  constexpr uint64_t DHI = DESC_SW128 | ((uint64_t)(1024 >> 4) << 32);
  constexpr uint32_t DST = A_TILE >> 4;
  auto issue_qk = [&](uint32_t qd, uint32_t kd, uint32_t z = 0) {
#pragma unroll
    for (int kk = 0; kk < 8; kk++) {
      const uint32_t off = ((kk >> 2) * 16384 + (kk & 3) * 32) >> 4;
      wgmma_m64n128_ss(s, DHI | (qd + off), DHI | (kd + off), kk ? 1 : z);
    }
    wgmma_commit();
  };
  auto issue_pv = [&](uint32_t vd, bool accumulate, int nk) {
#pragma unroll
    for (int kk = 0; kk < 8; kk++) {
      if (kk < nk)
        wgmma_m64n128_rs_tb(o, p[4 * kk], p[4 * kk + 1], p[4 * kk + 2], p[4 * kk + 3], DHI | (vd + kk * 128),
                            accumulate || (kk != 0));
    }
    wgmma_commit();
  };
  auto exp_lo = [&](float& a0, float& a1) {
#pragma unroll
    for (int j = 0; j < 8; j++) {
      e[4 * j] = ex2(s[4 * j]);
      e[4 * j + 1] = ex2(s[4 * j + 1]);
      e[4 * j + 2] = ex2(s[4 * j + 2]);
      e[4 * j + 3] = ex2(s[4 * j + 3]);
      a0 += e[4 * j];
      a0 += e[4 * j + 1];
      a1 += e[4 * j + 2];
      a1 += e[4 * j + 3];
      if (j == MIDJ) dep = (__float_as_uint(a0) | __float_as_uint(a1)) & rt_zero;
    }
  };
  auto pack_lo = [&]() {
#pragma unroll
    for (int j = 0; j < 16; j++) p[j] = pack_bf16(e[2 * j], e[2 * j + 1]);
  };
  auto finish_p = [&](float& a0, float& a1) {
    pack_lo();
#pragma unroll
    for (int j = 8; j < 16; j++) {
      const float e0 = ex2(s[4 * j]), e1 = ex2(s[4 * j + 1]), e2 = ex2(s[4 * j + 2]), e3 = ex2(s[4 * j + 3]);
      a0 += e0;
      a0 += e1;
      a1 += e2;
      a1 += e3;
      p[2 * j] = pack_bf16(e0, e1);
      p[2 * j + 1] = pack_bf16(e2, e3);
      if (j == 8 + MIDJ) dep = __float_as_uint(a0) & rt_zero;
    }
  };
  auto quad_sum = [&](float t) {
    t += __shfl_xor_sync(0xffffffffu, t, 1);
    return t + __shfl_xor_sync(0xffffffffu, t, 2);
  };
  auto write_o = [&](const float (&o)[64], float i0, float i1) {
    st_wait(bar, wg, sn - 1);
    const int st_row = warp * 16 + (lane & 7) + ((lane >> 3) & 1) * 8;
    const uint32_t so = sbase + A_O_OFF + wg * 18432 + st_row * 128;
#pragma unroll
    for (int j = 0; j < 16; j += 2)
      stmatrix_x4(so + (j >> 3) * 8192 + ((((j & 7) + (lane >> 4)) ^ (lane & 7)) << 4),
                  pack_bf16(o[4 * j] * i0, o[4 * j + 1] * i0), pack_bf16(o[4 * j + 2] * i1, o[4 * j + 3] * i1),
                  pack_bf16(o[4 * j + 4] * i0, o[4 * j + 5] * i0), pack_bf16(o[4 * j + 6] * i1, o[4 * j + 7] * i1));
  };
  auto store_o = [&](uint32_t r, int kind) {
    const uint32_t pass = sn >> 4, it = item_of(maps, 2 * pass + r);
    st_post(bar, wg, wtid, sn, kind, 2, sbase + A_O_OFF + wg * 18432, item_h(it) * 128,
            item_m(it) * 128 + wg * 64, CNT_CTX + pass);
    sn++;
  };
  auto mask_half = [&](float* sh) {
    const int u = warp * 16 + (lane >> 2) - (lane & 3) * 2;
#pragma unroll
    for (int j = 0; j < 8; j++) {
      if (8 * j > u) sh[4 * j] = -INFINITY;
      if (8 * j + 1 > u) sh[4 * j + 1] = -INFINITY;
      if (8 * j - 8 > u) sh[4 * j + 2] = -INFINITY;
      if (8 * j - 7 > u) sh[4 * j + 3] = -INFINITY;
    }
  };
  ST(0)
  mbar_wait(k_full, 0);
  ST(20)
  named_bar_sync(sched_own, 256);
  ST(21)
#pragma unroll
  for (int i = 0; i < 64; i++) asm volatile("mov.b32 %0, 0;" : "=f"(s[i]));
  wgmma_fence();
  issue_qk(qd0, kd0, rt_zero);
  named_bar_arrive(sched_other, 256);
  ST(36) ST(37) ST(38)
  ST(22)
#pragma unroll
  for (int i = 0; i < 64; i++) asm volatile("mov.b32 %0, 0;" : "=f"(o[i]));
  wgmma_wait<0>();
  fence_regs(s);
  mbar_arrive_if(k_empty, wtid == 32);
  uint32_t g = 0;
  uint32_t rnd = 0;
  int rem = item_m(item_of(maps, 0));
  uint32_t first = 1;
  uint32_t fl = 0;
#define LOWT (first ? (g == A_STEPS - 1 ? INFINITY : 9.094947e-13f) : -1.f)
#define redo (fl & 1)
#define shifted (fl & 2)
  float d0 = 0.f, d1 = 0.f;
  float pi0 = 1.f, pi1 = 1.f;
  ST(1)
  for (;;) {
    if (shifted) {
#pragma unroll
      for (int j = 0; j < 16; j++) {
        s[4 * j] -= d0;
        s[4 * j + 1] -= d0;
        s[4 * j + 2] -= d1;
        s[4 * j + 3] -= d1;
      }
    }
    if (rem == 0 && !redo) {
      mbar_arrive_if(q_empty + 8 * (rnd & 1), wtid == 96);
      rnd++;
      if (wg == 0) mask_half(s);
      else mask_half(s + 32);
    }
    for (;;) {
      const bool kill = rem == 0 && wg == 0;
      const uint32_t kd = kd0 + ((g + 1) & 1) * DST, vd = vd0 + (~g & 1) * DST;
      float a0 = 0.f, a1 = 0.f;
      exp_lo(a0, a1);
      fence_regs(e);
      const uint32_t kb = k_full + 8 * ((g + 1) & 1);
      const uint32_t kpar = ((((g + 1) >> 1) & 1) ^ (g == A_STEPS - 1 ? 1u : 0u)) | dep;
      if (!mbar_try(kb, kpar)) mbar_wait(kb, kpar | ((__float_as_uint(a0) | __float_as_uint(a1)) & rt_zero));
      wgmma_wait<0>();
      fence_regs(o);
      ST(g < 4 ? 24 + 3 * g : 39)
      if (kill) {
        mbar_arrive_if(kb + (B_VEMPTY - B_KFULL), wtid == 64 && !redo && g > 0);
        fence_regs(e);
        pack_lo();
#pragma unroll
        for (int j = 16; j < 32; j++) asm volatile("mov.u32 %0, 0;" : "=r"(p[j]));
        goto check;
      }
#pragma unroll
      for (int i = 32; i < 64; i++) asm volatile("" : "+f"(s[i])::"memory");
      mbar_arrive_if(kb + (B_VEMPTY - B_KFULL), wtid == 64 && !redo && g > 0);
      finish_p(a0, a1);
      if (__any_sync(0xffffffffu, !(mbar_try(v_full + 8 * (g & 1), ((g >> 1) & 1) | dep) &
                                    mbar_try(q_full + 8 * (rnd & 1), ((rnd >> 1) & 1) | dep)) ||
                                      !(a0 + a1 < 1.0995116e12f) || !(fminf(a0, a1) > LOWT))) {
      check:
        bool bad = !(a0 + a1 < 1.0995116e12f);
        if (first) bad |= !(fminf(quad_sum(a0), quad_sum(a1)) > 9.094947e-13f);
        if (!redo && __any_sync(0xffffffffu, bad)) {
          d0 = d1 = first ? -INFINITY : 0.f;
#pragma unroll
          for (int j = 0; j < 16; j++) {
            if (j < 8 || !kill) {
              d0 = fmaxf(d0, fmaxf(s[4 * j], s[4 * j + 1]));
              d1 = fmaxf(d1, fmaxf(s[4 * j + 2], s[4 * j + 3]));
            }
          }
#pragma unroll
          for (int x = 1; x <= 2; x++) {
            d0 = fmaxf(d0, __shfl_xor_sync(0xffffffffu, d0, x));
            d1 = fmaxf(d1, __shfl_xor_sync(0xffffffffu, d1, x));
          }
          b0 += d0;
          b1 += d1;
          if (!first) {
            const float al0 = ex2(-d0), al1 = ex2(-d1);
            l0 *= al0;
            l1 *= al1;
#pragma unroll
            for (int j = 0; j < 16; j++) {
              o[4 * j] *= al0;
              o[4 * j + 1] *= al0;
              o[4 * j + 2] *= al1;
              o[4 * j + 3] *= al1;
            }
          }
          fl = 3;
          break;
        }
        if (first && g == A_STEPS - 1) {
          write_o(o, pi0, pi1);
          store_o(0, ST_BOX2);
        }
        mbar_wait(v_full + 8 * (g & 1), (g >> 1) & 1);
        mbar_wait(q_full + 8 * (rnd & 1), (rnd >> 1) & 1);
      }
      ST(g < 4 ? 25 + 3 * g : 39)
      named_bar_sync(sched_own, 256);
      ST(g < 4 ? 26 + 3 * g : 39)
      if (g == A_STEPS - 1) {
        fence_regs(o);
        if (kill) {
          wgmma_fence();
          issue_pv(vd, !first, 4);
        } else {
          wgmma_fence();
          issue_pv(vd, !first, 8);
        }
        named_bar_arrive(sched_other, 256);
        pi0 = rcp(quad_sum(l0 + a0));
        pi1 = rcp(quad_sum(l1 + a1));
        goto done;
      }
      wgmma_fence();
      issue_qk(qd0 + (rnd & 1) * DST, kd);
      if (first && g) write_o(o, pi0, pi1);
      fence_regs(o);
      if (kill) {
        wgmma_fence();
        issue_pv(vd, !first, 4);
      } else {
        wgmma_fence();
        issue_pv(vd, !first, 8);
      }
      named_bar_arrive(sched_other, 256);
      fl &= 2;
      l0 += a0;
      l1 += a1;
      if (rem == 0 || first) {
        if (first && g) store_o(0, ST_BOX2);
        first = rem == 0;
        if (first) {
          pi0 = rcp(quad_sum(l0));
          pi1 = rcp(quad_sum(l1));
          l0 = l1 = b0 = b1 = 0.f;
          fl = 0;
          rem = item_m(item_of(maps, 1)) + 1;
        }
      }
      rem--;
      g++;
      wgmma_wait<1>();
      fence_regs(s);
      mbar_arrive_if(kb + (B_KEMPTY - B_KFULL), wtid == 32);
      ST(g + 1)
      if (rem == 0 || shifted) {
        d0 = b0;
        d1 = b1;
        break;
      }
    }
  }
done:
#undef redo
#undef shifted
  wgmma_wait<0>();
  fence_regs(o);
  mbar_arrive_if(bar + B_VEMPTY, wtid == 64);
  write_o(o, pi0, pi1);
  store_o(1, ST_BOX2W + (sn >> 4));
  ST(18)
  return sn;
}

constexpr int O_STAGES = 5;
constexpr int O_STAGE_BYTES = 32768;
constexpr int O_Y_OFF = 5 * 32768;
constexpr int O_X_OFF = 6 * 32768 + 2048;
constexpr int O_NK = HDIM / 64;

__device__ __forceinline__ uint32_t out_stage(uint32_t st) { return ((0x41230u >> (4 * st)) & 7) * O_STAGE_BYTES; }

__device__ __forceinline__ void out_producer(const Maps& maps, uint32_t sbase, bool dry) {
  const uint32_t bar = sbase + BAR_OFF;
  const uint32_t rank = blockIdx.x & 1;
  const int m_tile = maps.id[blockIdx.x][2] & 15, n_tile = maps.id[blockIdx.x][2] >> 4;
  uint32_t stage = 0, phase = 0;
  const int kx = dry ? O_STAGES : 17 + (blockIdx.x >> 1) % 12;
#pragma unroll 1
  for (int ki = 0; ki <= O_STAGES; ki++) {
    if (ki < O_STAGES) {
      constexpr uint32_t LASTB = (B_KEMPTY + 8) | (B_KEMPTY << 8) | ((B_QEMPTY + 8) << 16) | ((B_VEMPTY + 8) << 24);
      if (ki > 0 && !dry) mbar_wait_sleep(bar + ((LASTB >> (8 * ki - 8)) & 255), (0x12 >> ki) & 1);
      mbar_arrive_cluster_if(bar + B_OEMPTY + 8 * ki, 0, !dry);
      mbar_arrive_cluster_if(bar + B_OEMPTY + 8 * ki, 1, !dry);
      if (!dry) {
        mbar_expect_tx(bar + B_OFULL + 8 * ki, O_STAGE_BYTES);
        tma_load_4d(sbase + out_stage(ki), &maps.oa, bar + B_OFULL + 8 * ki, ((ki & 14) * 4 + (ki & 1)) * 64, m_tile);
      }
    }
    if (ki > 0 && !dry) {
      const int k = ki - 1;
      mbar_wait_sleep(bar + B_OEMPTY + 8 * k, 0);
      tma_load_2d_mc(sbase + out_stage(k) + 16384 + rank * 8192, &maps.ob, bar + B_OFULL + 8 * k, n_tile * 128 + rank * 64,
                     ((k & 14) * 4 + (k & 1)) * 64, (uint16_t)3);
    }
    if (dry) ki += O_STAGES - 1;
  }
  phase = 1;
#pragma unroll 1
  for (int ki = O_STAGES; ki < (dry ? O_STAGES + 1 : O_NK); ki++) {
    const int kt = (ki & 14) * 4 + (ki >> 4) * 2 + (ki & 1);
    const uint32_t fb = bar + B_OFULL + 8 * stage, eb = bar + B_OEMPTY + 8 * stage;
    const uint32_t sa = sbase + out_stage(stage);
    if (ki == (dry ? O_STAGES : 16)) cnt_wait(CNT_CTX + 1, dry ? 0 : 2 * A_ITEMS);
    if (ki == kx) {
      if (!dry) {
        mbar_wait_sleep(bar + B_OFREE, 0);
        mbar_wait_sleep(bar + B_OFREE + 8, 0);
        mbar_expect_tx(bar + B_OY, 32768);
        tma_load_4d(sbase + O_X_OFF, &maps.ox, bar + B_OY, n_tile * 128, m_tile);
        tma_load_4d(sbase + O_X_OFF + 16384, &maps.ox, bar + B_OY, n_tile * 128 + 64, m_tile);
      }
    }
    if (!dry) {
      mbar_wait_sleep(eb, phase);
      mbar_expect_tx(fb, O_STAGE_BYTES);
      tma_load_4d(sa, &maps.oa, fb, kt * 64, m_tile);
      tma_load_2d_mc(sa + 16384 + rank * 8192, &maps.ob, fb, n_tile * 128 + rank * 64, kt * 64, (uint16_t)3);
    }
    if (++stage == O_STAGES) { stage = 0; phase ^= 1; }
  }
  if (!dry) mbar_wait_sleep(bar + B_OY2, 0);
}

__device__ __forceinline__ void out_side(const Maps& maps, uint32_t smem0) {
  PHASE_PROLOGUE
  const int m_tile = maps.id[blockIdx.x][2] & 15, n_tile = maps.id[blockIdx.x][2] >> 4;
  const int w4 = __shfl_sync(0xffffffffu, warp, 0);
  if (w4 == 0) {
    if (elect_one()) {
      mbar_expect_tx(bar + B_OY, 32768 - 4096);
      TD(10)
      GS(0)
      cnt_wait(CNT_Y2, DM - 128);
      GS(1)
      TD(7)
      for (const uint32_t t = clock(); (uint32_t)clock() - t < (blockIdx.x & 14) * 200;) __nanosleep(32);
      TD(11)
      GS(2)
      fence_proxy_async();
      tma_load_2d(sbase + O_Y_OFF, &maps.y, bar + B_OY, m_tile * 128, n_tile * 128);
      tma_load_2d(sbase + O_Y_OFF + 16384, &maps.y, bar + B_OY, m_tile * 128 + 64, n_tile * 128);
      asm volatile("prefetch.tensormap [%0];" ::"l"(&maps.oc) : "memory");
    }
  }
#pragma unroll
  for (int i = 0; i < 3; i++) {
    const int h = i >> 1, c = i & 1;
    named_bar_sync(6 + i, 256);
    if (elect_one()) {
      fence_proxy_async();
      tma_store_4d(&maps.oc, sbase + O_X_OFF + c * 16384 + h * 8192 + w4 * 2048, n_tile * 128 + c * 64, 2 * w4,
                   2 * m_tile + h);
      tma_store_commit();
    }
  }
}

__device__ __forceinline__ void out_gemm(const Maps& maps, uint32_t smem0) {
  PHASE_PROLOGUE
  const int o_id = maps.id[blockIdx.x][2], m_tile = o_id & 15;
  float acc[2][64];
  undef_regs(acc[0]);
  undef_regs(acc[1]);
  uint32_t stage = 0, phase = 0, prev_stage = 0;
  GT(gti++)
  if (wg == 1) {
    out_side(maps, smem0);
    return;
  }
  const float* gp = g_gate + m_tile * 128 + warp * 2 + (lane >> 2) * 8;
  const float gv[4] = {__ldcg(gp), __ldcg(gp + 1), __ldcg(gp + 64), __ldcg(gp + 65)};
  constexpr uint64_t DHI = DESC_SW128 | ((uint64_t)(1024 >> 4) << 32);
  constexpr int K1 = O_NK - 6, K2 = O_NK - 3;
#pragma unroll 1
  for (int kt = 0; kt < K1; kt++) {
    uint32_t da = (uint32_t)make_desc(sbase + out_stage(stage), 16, 0, 0);
    uint32_t db = (uint32_t)make_desc(sbase + out_stage(stage) + 16384, 8192, 0, 0);
    asm volatile("" : "+r"(da), "+r"(db));
    mbar_wait(bar + B_OFULL + 8 * stage, phase);
    GT(gti++)
#pragma unroll
    for (int kk = 0; kk < 4; kk++) {
      wgmma_wait<2>();
      if (kk == 2) mbar_arrive_cluster_if(bar + B_OEMPTY + 8 * prev_stage, wtid >> 6, (wtid & 63) == 32 && kt > 0);
      wgmma_fence();
      wgmma_m64n128_ss_tb(acc[0], DHI | (da + kk * 2), DHI | (db + kk * 128), (kt | kk) != 0);
      wgmma_m64n128_ss_tb(acc[1], DHI | (da + 512 + kk * 2), DHI | (db + kk * 128), (kt | kk) != 0);
      wgmma_commit();
    }
    prev_stage = stage;
    if (++stage == O_STAGES) { stage = 0; phase ^= 1; }
  }
  const int st_row = warp * 16 + (lane & 7) + ((lane >> 3) & 1) * 8;
  const uint32_t rowa = sbase + O_X_OFF + st_row * 128;
  const uint32_t yrow = sbase + O_Y_OFF + ((lane & 7) + ((lane >> 4) & 1) * 8) * 128 +
                        (((warp * 2 + ((lane >> 3) & 1)) ^ (lane & 7)) << 4);
  auto oa = [&](int i) { return rowa + (i >> 3) * 8192 + (i & 4) * 4096 + ((((i & 3) * 2 + (lane >> 4)) ^ (st_row & 7)) << 4); };
  auto frag = [](int j) { return j < 7 ? j : j < 14 ? j + 1 : j == 14 ? 7 : 15; };
  uint32_t b[16][4] = {}, x[3][4], y[3][4], gg[4], om[4];
#pragma unroll
  for (int i = 0; i < 4; i++) {
    gg[i] = pack_bf16(gv[i], gv[i]);
    om[i] = pack_bf16(1.0f - gv[i], 1.0f - gv[i]);
  }
  auto mul = [&](int j) {
    const int i = frag(j);
#pragma unroll
    for (int k = 0; k < 4; k++) b[i][k] = mul_bf2(om[(i >> 3) * 2 + (k & 1)], mul_bf2(x[j % 3][k], y[j % 3][k]));
  };
  auto load = [&](int j) {
    uint32_t dep = 0;
    if (j >= 3) {
      mul(j - 3);
      const uint32_t* d = b[frag(j - 3)];
      dep = (d[0] | d[1] | d[2] | d[3]) & rt_zero;
    }
    const int i = frag(j);
    ldsm4t(y[j % 3], (yrow | dep) + (i >> 3) * 16384 + (i & 7) * 2048);
    asm volatile("ldmatrix.sync.aligned.m8n8.x4.shared.b16 {%0, %1, %2, %3}, [%4];"
                 : "=r"(x[j % 3][0]), "=r"(x[j % 3][1]), "=r"(x[j % 3][2]), "=r"(x[j % 3][3])
                 : "r"(oa(i)));
  };
  uint32_t da[3], db[3];
  auto descs = [&](int kt) {
    da[kt % 3] = (uint32_t)make_desc(sbase + out_stage(kt % O_STAGES), 16, 0, 0);
    db[kt % 3] = (uint32_t)make_desc(sbase + out_stage(kt % O_STAGES) + 16384, 8192, 0, 0);
    asm volatile("" : "+r"(da[kt % 3]), "+r"(db[kt % 3]));
  };
  auto half = [&](int h, int kt) {
    wgmma_fence();
#pragma unroll
    for (int kk = 0; kk < 4; kk++)
      wgmma_m64n128_ss_tb(acc[h], DHI | (da[kt % 3] + h * 512 + kk * 2), DHI | (db[kt % 3] + kk * 128), 1);
    wgmma_commit();
  };
  LT(6, 0)
  mbar_wait(bar + B_OY, 0);
  LT(7, 0)
#pragma unroll
  for (int kt = K1; kt < K2; kt++) {
    descs(kt);
    mbar_wait(bar + B_OFULL + 8 * (kt % O_STAGES), (kt / O_STAGES) & 1);
    GT(gti++)
#pragma unroll
    for (int kk = 0; kk < 4; kk++) {
      wgmma_wait<2>();
      if (kk == 2 && kt - 1 + O_STAGES < O_NK)
        mbar_arrive_cluster_if(bar + B_OEMPTY + 8 * ((kt - 1) % O_STAGES), wtid >> 6, (wtid & 63) == 32);
      wgmma_fence();
      wgmma_m64n128_ss_tb(acc[0], DHI | (da[kt % 3] + kk * 2), DHI | (db[kt % 3] + kk * 128), 1);
      wgmma_m64n128_ss_tb(acc[1], DHI | (da[kt % 3] + 512 + kk * 2), DHI | (db[kt % 3] + kk * 128), 1);
      wgmma_commit();
      if (kt > K1 || kk > 0) load((kt - K1) * 4 + kk - 1);
    }
  }
#pragma unroll
  for (int kt = K2; kt < O_NK; kt++) descs(kt);
#pragma unroll
  for (int kt = K2; kt < O_NK; kt++) {
    mbar_wait(bar + B_OFULL + 8 * (kt % O_STAGES), (kt / O_STAGES) & 1);
    GT(gti++)
    half(0, kt);
    load(11 + kt - K2);
  }
  half(1, K2);
  mbar_wait(bar + B_OY2, 0);
  load(14);
  load(15);
  half(1, K2 + 1);
  if (tid == 0) { TD(14) }
  mul(13);
#pragma unroll
  for (int i = 0; i < 16; i++) {
    const int h = i >> 3;
    if (i == 4) half(1, K2 + 2);
    if (i == 0) wgmma_wait<2>();
    if (i == 8) wgmma_wait<0>();
    if (i % 8 == 0) fence_regs(acc[h]);
    if (i == 4) {
      const uint32_t dep = __float_as_uint(acc[0][63]) & rt_zero;
#pragma unroll
      for (int k = 0; k < 4; k++) {
        x[14 % 3][k] |= dep;
        x[15 % 3][k] |= dep;
      }
      mul(14);
      mul(15);
    }
    const float* a = acc[h] + 8 * (i & 7);
    const uint32_t gg0 = gg[2 * h], gg1 = gg[2 * h + 1];
    stmatrix_x4(oa(i), fma_bf2(gg0, pack_bf16(a[0], a[1]), b[i][0]), fma_bf2(gg1, pack_bf16(a[2], a[3]), b[i][1]),
                fma_bf2(gg0, pack_bf16(a[4], a[5]), b[i][2]), fma_bf2(gg1, pack_bf16(a[6], a[7]), b[i][3]));
    if (i % 4 == 3 && i < 15) named_bar_arrive(6 + i / 4, 256);
  }
  fence_proxy_async();
  __syncwarp();
  if (elect_one()) {
    tma_store_4d(&maps.oc, sbase + O_X_OFF + 16384 + 8192 + warp * 2048, (o_id >> 4) * 128 + 64, 2 * warp, 2 * m_tile + 1);
    tma_store_commit();
  }
  GT(gti++)
}

__device__ __noinline__ void leave_kernel() {
  if (atomicAdd(g_cnt + CNT_DONE * 32, 1u) == 2 * gridDim.x - 1) {
    for (int i = 0; i < CNT_N; i++) g_cnt[i * 32] = 0;
  }
}

__device__ __noinline__ void side_jobs(const Maps& maps, uint32_t sbase) {
  const int w12 = __shfl_sync(0xffffffffu, threadIdx.x >> 5, 0);
  gate_rows(maps, sbase, (blockIdx.x - 128) * 12 + w12, w12, threadIdx.x & 31);
  fence_proxy_async();
  __syncthreads();
  if (threadIdx.x == 320) cnt_signal_release(CNT_PREP + 1, 1);
}

__global__ void __launch_bounds__(384, 1) fused_kernel(const __grid_constant__ Maps maps) {
  extern __shared__ __align__(1024) uint8_t smem_raw[];
  {
    const uint32_t sbase = __shfl_sync(0xffffffffu, smem_u32(smem_raw), 0);
    const uint32_t bar = sbase + BAR_OFF;
    const int tid = threadIdx.x;
    TL(0, 0) LT(0, 0)
    if (__shfl_sync(0xffffffffu, tid >> 5, 0) == 1 && blockIdx.x < 128) {
      if (elect_one()) {
        for (int i = 0; i < G_STAGES; i++) mbar_init(bar + B_GFULL + 8 * i, 1);
        fence_barrier_init();
        qkv_producer(maps, sbase, 0, true);
      }
    }
    if (tid == 0) {
      for (int i = 0; i < G_STAGES; i++) {
        mbar_init(bar + B_GEMPTY + 8 * i, 2);
        mbar_init(bar + B_SFULL + 8 * i, 4);
        mbar_init(bar + B_SFREE + 8 * i, 1);
      }
      for (int i = 0; i < 2; i++) {
        mbar_init(bar + B_OFREE + 8 * i, 1);
        mbar_init(bar + B_QFULL + 8 * i, 1);
        mbar_init(bar + B_QEMPTY + 8 * i, 2);
        mbar_init(bar + B_KFULL + 8 * i, 1);
        mbar_init(bar + B_KEMPTY + 8 * i, 2);
        mbar_init(bar + B_VFULL + 8 * i, 1);
        mbar_init(bar + B_VEMPTY + 8 * i, 2);
      }
      for (int i = 0; i < O_STAGES; i++) {
        mbar_init(bar + B_OFULL + 8 * i, 1);
        mbar_init(bar + B_OEMPTY + 8 * i, 2);
      }
      mbar_init(bar + B_OY, 2);
      mbar_init(bar + B_OY2, 1);
      mbar_init(bar + B_QPEER, 1);
      for (int i = 0; i < 8; i++) mbar_init(bar + B_CFULL + 8 * i, 1);
      for (int i = 0; i < CNT_N; i++) asm volatile("st.shared.u32 [%0], 0;" ::"r"(bar + B_PEND + 4 * i) : "memory");
      fence_barrier_init();
    }
    __syncthreads();
    asm volatile("barrier.cluster.arrive.relaxed.aligned;" ::: "memory");
    if (blockIdx.x >= 128) side_jobs(maps, sbase);
  }
  uint32_t smem0 = smem_u32(smem_raw);
  PHASE_PROLOGUE
  const bool mainc = blockIdx.x < 128;
  TL(0, 1)

  if (wg != 2) {
    reg_alloc<232>();
    if (wg == 1) named_bar_arrive(4, 256);
    mbar_wait(bar + B_OFREE + 8, mainc);
    if (mainc) {
      uint32_t sn = 0, p[32];
#pragma unroll
      for (int i = 0; i < 32; i++) asm volatile("" : "=r"(p[i]));
#pragma unroll 1
      do {
        sn = qkv_consumer(maps, smem_u32(smem_raw), sn, p);
        LT(1 + 2 * (sn >> 4), 0)
        sn = attn_consumer(maps, smem_u32(smem_raw), sn, p);
        LT(2 + 2 * (sn >> 4), 0)
      } while (sn < 16);
    }
    asm volatile("barrier.cluster.wait.acquire.aligned;" ::: "memory");
    if (mainc && __shfl_sync(0xffffffffu, threadIdx.x, 0) < 128) {
      named_bar_arrive(3, 256);
    } else {
      named_bar_sync(3, 256);
      const uint32_t b2 = blockIdx.x * 2 + (threadIdx.x >> 7);
      const uint32_t first = __shfl_sync(0xffffffffu, mainc ? conv_first(maps) : (b2 - 255) * 128 - C_SIDE, 0);
      conv_consumer(maps, smem_u32(smem_raw), first, mainc ? 16 : 1, (first | 127) + 1 - (mainc ? C_SIDE : 0));
    }
    if (mainc) out_gemm(maps, smem_u32(smem_raw));
    tma_store_wait_read<0>();
    TL2(3, 2) LT(5, 0)
  } else {
    reg_dealloc<40>();
    asm volatile("barrier.cluster.wait.acquire.aligned;" ::: "memory");
    const int w = __shfl_sync(0xffffffffu, tid >> 5, 0) - 8;
    if (w < 2) {
      if (mainc) agent_warp(maps, smem_u32(smem_raw));
      if (mainc && w == 0 && elect_one()) {
        mbar_wait_sleep(bar + B_OY, 0);
        mbar_expect_tx(bar + B_OY2, 4096);
        cnt_wait(CNT_Y2 + 1, 128);
        GS(5)
        const int id = maps.id[blockIdx.x][2];
        for (int i = 0; i < 2; i++)
          tma_load_2d(sbase + O_Y_OFF + i * 16384 + 112 * 128, &maps.y2, bar + B_OY2, (id & 15) * 128 + i * 64,
                      (id >> 4) * 128 + 112);
      }
    } else {
      if (mainc && elect_one()) {
        const bool dry = w == 2;
#pragma unroll 1
        for (int pass = dry; pass < 2; pass++) {
          if (!dry) qkv_producer(maps, sbase, pass, false);
          attn_producer(maps, sbase, pass, dry);
        }
        out_producer(maps, sbase, dry);
      }
      if (!mainc && tid == 352) {
        cnt_wait(CNT_PREP, 256);
        mbar_arrive(bar + B_OFREE);
        mbar_arrive(bar + B_OFREE + 8);
      }
      __syncwarp();
      if (w == 2) publisher(bar, tid & 31, mainc ? 3 : 2);
      if ((tid & 31) == 0) leave_kernel();
    }
  }
}

__device__ __forceinline__ float ldf(const bf16* p) { return __bfloat162float(*p); }
__global__ void __launch_bounds__(256) plain_gemm(const bf16* A, const bf16* B, bf16* C, int k, int ldb, int n) {
  __shared__ float sa[16][65], sb[16][64];
  const int tx = threadIdx.x & 15, ty = threadIdx.x >> 4, m0 = blockIdx.y * 64, n0 = blockIdx.x * 64;
  float acc[4][4] = {};
  for (int k0 = 0; k0 < k; k0 += 16) {
    for (int i = threadIdx.x; i < 1024; i += 256) {
      sa[i & 15][i >> 4] = ldf(A + (size_t)(m0 + (i >> 4)) * k + k0 + (i & 15));
      sb[i >> 6][i & 63] = ldf(B + (size_t)(k0 + (i >> 6)) * ldb + n0 + (i & 63));
    }
    __syncthreads();
    for (int kk = 0; kk < 16; kk++)
      for (int i = 0; i < 4; i++)
        for (int j = 0; j < 4; j++) acc[i][j] += sa[kk][ty * 4 + i] * sb[kk][tx + 16 * j];
    __syncthreads();
  }
  for (int i = 0; i < 4; i++)
    for (int j = 0; j < 4; j++) C[(size_t)(m0 + ty * 4 + i) * n + n0 + tx + 16 * j] = __float2bfloat16_rn(acc[i][j]);
}
__global__ void __launch_bounds__(256) plain_attn(int half) {
  const int lane = threadIdx.x & 31, t = blockIdx.x * 8 + (threadIdx.x >> 5), c = blockIdx.y * HD + lane * 4;
  bf16* io = g_ctx + (size_t)t * HDIM + half * (HDIM / 2) + c;
  float q[4], o[4] = {}, m = -INFINITY, l = 0.f;
  for (int i = 0; i < 4; i++) q[i] = ldf(io + i) * 0.08838834764831845f;
  for (int j = 0; j <= t; j++) {
    float s = 0.f;
    for (int i = 0; i < 4; i++) s += q[i] * ldf(g_k + (size_t)j * (HDIM / 2) + c + i);
    for (int x = 16; x; x >>= 1) s += __shfl_xor_sync(0xffffffffu, s, x);
    const float mn = fmaxf(m, s), al = __expf(m - mn), p = __expf(s - mn);
    for (int i = 0; i < 4; i++) o[i] = o[i] * al + p * ldf(g_v + (size_t)j * (HDIM / 2) + c + i);
    l = l * al + p;
    m = mn;
  }
  for (int i = 0; i < 4; i++) io[i] = __float2bfloat16_rn(o[i] / l);
}
__global__ void __launch_bounds__(256) plain_gate(const bf16* x, const bf16* w) {
  const int lane = threadIdx.x & 31, t = blockIdx.x * 8 + (threadIdx.x >> 5);
  float s = 0.f;
  for (int i = lane; i < DM; i += 32) s += bf16_round(ldf(x + (size_t)t * DM + i) * ldf(w + i));
  for (int o = 16; o; o >>= 1) s += __shfl_xor_sync(0xffffffffu, s, o);
  if (lane == 0) g_gate[t] = bf16_round(1.0f / (1.0f + __expf(-bf16_round(s))));
}
__global__ void __launch_bounds__(256) plain_conv(const bf16* x, const bf16* k, const bf16* v, const bf16* shift_k,
                                                  const bf16* ssm_k, const bf16* ssm_D, bf16* out) {
  __shared__ float u[S_LEN], h[S_LEN];
  const int c = blockIdx.x;
  for (int t = threadIdx.x; t < S_LEN; t += 256) {
    float s = 0.f;
    for (int i = 3; i >= 0; i--)
      if (t >= i) s = bf16_round(s + bf16_round(ldf(k + (size_t)(t - i) * DM + c) * ldf(shift_k + c * 4 + i)));
    u[t] = bf16_round(s * ldf(v + (size_t)t * DM + c));
    h[t] = ldf(ssm_k + (size_t)c * S_LEN + t);
  }
  __syncthreads();
  for (int t = threadIdx.x; t < S_LEN; t += 256) {
    float y = 0.f;
    for (int i = 0; i <= t; i++) y += h[i] * u[t - i];
    y = bf16_round(bf16_round(y) + bf16_round(u[t] * ldf(ssm_D + c)));
    const float g = g_gate[t], b = bf16_round(ldf(x + (size_t)t * DM + c) * y);
    bf16* o = out + (size_t)t * DM + c;
    *o = __float2bfloat16_rn(bf16_round(g * ldf(o)) + bf16_round(bf16_round(1.0f - g) * b));
  }
}

typedef CUresult (*PFN_tmapEncode)(CUtensorMap*, CUtensorMapDataType, cuuint32_t, void*, const cuuint64_t*,
                                   const cuuint64_t*, const cuuint32_t*, const cuuint32_t*, CUtensorMapInterleave,
                                   CUtensorMapSwizzle, CUtensorMapL2promotion, CUtensorMapFloatOOBfill);
static PFN_tmapEncode s_encode = nullptr;

static void make_map_2d(CUtensorMap* m, const void* ptr, int rows, int cols, int box_rows,
                        CUtensorMapL2promotion prom = CU_TENSOR_MAP_L2_PROMOTION_L2_256B) {
  cuuint64_t dims[2] = {(cuuint64_t)cols, (cuuint64_t)rows};
  cuuint64_t strides[1] = {(cuuint64_t)cols * 2};
  cuuint32_t box[2] = {64, (cuuint32_t)box_rows};
  cuuint32_t es[2] = {1, 1};
  s_encode(m, CU_TENSOR_MAP_DATA_TYPE_BFLOAT16, 2, const_cast<void*>(ptr), dims, strides, box, es,
           CU_TENSOR_MAP_INTERLEAVE_NONE, CU_TENSOR_MAP_SWIZZLE_128B, prom,
           CU_TENSOR_MAP_FLOAT_OOB_FILL_NONE);
}
static void make_map_3d(CUtensorMap* m, const void* ptr, int rows, int cols, int box_rows, int box_chunks) {
  cuuint64_t dims[3] = {64, (cuuint64_t)rows, (cuuint64_t)(cols / 64)};
  cuuint64_t strides[2] = {(cuuint64_t)cols * 2, 128};
  cuuint32_t box[3] = {64, (cuuint32_t)box_rows, (cuuint32_t)box_chunks};
  cuuint32_t es[3] = {1, 1, 1};
  s_encode(m, CU_TENSOR_MAP_DATA_TYPE_BFLOAT16, 3, const_cast<void*>(ptr), dims, strides, box, es,
           CU_TENSOR_MAP_INTERLEAVE_NONE, CU_TENSOR_MAP_SWIZZLE_128B, CU_TENSOR_MAP_L2_PROMOTION_L2_256B,
           CU_TENSOR_MAP_FLOAT_OOB_FILL_NONE);
}

static void make_map_4d(CUtensorMap* m, const void* ptr, int rows, int cols, int b2, int groups) {
  cuuint64_t dims[4] = {(cuuint64_t)cols, 8, 8, (cuuint64_t)(rows / 64)};
  cuuint64_t strides[3] = {(cuuint64_t)cols * 16, (cuuint64_t)cols * 2, (cuuint64_t)cols * 128};
  cuuint32_t box[4] = {64, 8, (cuuint32_t)b2, (cuuint32_t)groups};
  cuuint32_t es[4] = {1, 1, 1, 1};
  s_encode(m, CU_TENSOR_MAP_DATA_TYPE_BFLOAT16, 4, const_cast<void*>(ptr), dims, strides, box, es,
           CU_TENSOR_MAP_INTERLEAVE_NONE, CU_TENSOR_MAP_SWIZZLE_128B, CU_TENSOR_MAP_L2_PROMOTION_L2_256B,
           CU_TENSOR_MAP_FLOAT_OOB_FILL_NONE);
}

static cudaLaunchConfig_t fused_cfg(cudaLaunchAttribute* at) {
  cudaLaunchConfig_t cfg = {};
  cfg.gridDim = dim3(132);
  cfg.blockDim = dim3(384);
  cfg.dynamicSmemBytes = SMEM_BYTES;
  cfg.stream = cudaStreamPerThread;
  at[0].id = cudaLaunchAttributeClusterDimension;
  at[0].val.clusterDim.x = 2;
  at[0].val.clusterDim.y = 1;
  at[0].val.clusterDim.z = 1;
  cfg.attrs = at;
  cfg.numAttrs = 1;
  return cfg;
}

extern "C" void kernel_launch(void* const* d_in, const int* in_sizes, int n_in, void* d_out, int out_size) {
  const bf16* x = (const bf16*)d_in[0];
  const bf16* ckv = (const bf16*)d_in[1];
  const bf16* wq = (const bf16*)d_in[2];
  const bf16* wuk = (const bf16*)d_in[3];
  const bf16* wuv = (const bf16*)d_in[4];
  const bf16* wo = (const bf16*)d_in[5];
  const bf16* bk = (const bf16*)d_in[7];
  const bf16* bv = (const bf16*)d_in[8];
  const bf16* shift_k = (const bf16*)d_in[9];
  const bf16* ssm_k = (const bf16*)d_in[10];
  const bf16* ssm_D = (const bf16*)d_in[11];
  const bf16* gate_w = (const bf16*)d_in[12];
  bf16* out = (bf16*)d_out;

  static void *pk = nullptr, *pv = nullptr, *pctx = nullptr, *pb = nullptr;
  static int max_clusters = 0;
  if (!s_encode) {
    void* fn = nullptr;
    cudaDriverEntryPointQueryResult qres;
    cudaGetDriverEntryPoint("cuTensorMapEncodeTiled", &fn, cudaEnableDefault, &qres);
    s_encode = (PFN_tmapEncode)fn;
    cudaGetSymbolAddress(&pk, g_k);
    cudaGetSymbolAddress(&pv, g_v);
    cudaGetSymbolAddress(&pctx, g_ctx);
    cudaGetSymbolAddress(&pb, g_y2T);
    cudaFuncSetAttribute(fused_kernel, cudaFuncAttributeMaxDynamicSharedMemorySize, SMEM_BYTES);
    cudaLaunchAttribute at[1];
    cudaLaunchConfig_t cfg = fused_cfg(at);
    if (cudaOccupancyMaxActiveClusters(&max_clusters, fused_kernel, &cfg) != cudaSuccess) max_clusters = 0;
  }

  Maps all = {};
  make_map_2d(&all.a[0], ckv, S_LEN, DC, 128);
  make_map_2d(&all.a[1], x, S_LEN, DM, 128);
  make_map_3d(&all.b[0], wuk, DC, HDIM, 64, 4);
  make_map_3d(&all.b[1], wuv, DC, HDIM, 64, 4);
  make_map_3d(&all.b[2], wq, DM, HDIM, 64, 4);
  make_map_2d(&all.c[0], pk, S_LEN, HDIM / 2, 64);
  make_map_2d(&all.c[1], pv, S_LEN, HDIM / 2, 64);
  make_map_3d(&all.k, pk, S_LEN, HDIM / 2, 128, 2);
  make_map_3d(&all.v, pv, S_LEN, HDIM / 2, 128, 2);
  make_map_2d(&all.c[2], pctx, S_LEN, HDIM, 64);
  all.ssm_k = ssm_k;
  all.ssm_D = ssm_D;
  make_map_4d(&all.oa, pctx, S_LEN, HDIM, 8, 2);
  make_map_4d(&all.ox, x, S_LEN, DM, 8, 2);
  make_map_2d(&all.ob, wo, HDIM, DM, 64);
  make_map_4d(&all.oc, out, S_LEN, DM, 2, 1);
  make_map_2d(&all.y, pb, DM, S_LEN, 112);
  make_map_2d(&all.y2, pb, DM, S_LEN, 16);

  make_map_2d(&all.bk, bk, S_LEN, DM, 35, CU_TENSOR_MAP_L2_PROMOTION_L2_128B);
  make_map_2d(&all.bv, bv, S_LEN, DM, 32, CU_TENSOR_MAP_L2_PROMOTION_L2_128B);
  for (int b = 0; b < 128; b++) {
    const int c = b >> 1, r = b & 1;
    const int G = c < 4 ? 0 : c < 36 ? (c - 4) % 8 : 1 + (c - 36) % 7;
    const int i = c < 4 ? 4 + c : c < 36 ? (c - 4) / 8 : 4 + (c - 36) / 7;
    all.id[b][0] = r + 2 * (i & 1) + 4 * (G & 3) + 16 * (i >> 1) + 64 * (G >> 2);
    all.id[b][1] = (r ? 15 - i : i) + 16 * G;
    all.id[b][2] = r + 2 * G + 16 * i;
  }
  all.shift_k = shift_k;
  all.x = x;
  all.gate_w = gate_w;
  cudaLaunchAttribute at[1];
  cudaLaunchConfig_t cfg = fused_cfg(at);
  if (max_clusters >= 66) {
    cudaLaunchKernelEx(&cfg, fused_kernel, all);
  } else {
    const cudaStream_t st = cudaStreamPerThread;
    plain_gemm<<<dim3(HDIM / 64, S_LEN / 64), 256, 0, st>>>(x, wq, (bf16*)pctx, DM, HDIM, HDIM);
    for (int half = 0; half < 2; half++) {
      plain_gemm<<<dim3(HDIM / 128, S_LEN / 64), 256, 0, st>>>(ckv, wuk + half * (HDIM / 2), (bf16*)pk, DC, HDIM, HDIM / 2);
      plain_gemm<<<dim3(HDIM / 128, S_LEN / 64), 256, 0, st>>>(ckv, wuv + half * (HDIM / 2), (bf16*)pv, DC, HDIM, HDIM / 2);
      plain_attn<<<dim3(S_LEN / 8, NH / 2), 256, 0, st>>>(half);
    }
    plain_gemm<<<dim3(DM / 64, S_LEN / 64), 256, 0, st>>>((const bf16*)pctx, wo, out, HDIM, DM, DM);
    plain_gate<<<S_LEN / 8, 256, 0, st>>>(x, gate_w);
    plain_conv<<<DM, 256, 0, st>>>(x, bk, bv, shift_k, ssm_k, ssm_D, out);
  }
}
```
